```python
import torch

def _softmax(x, axis=-1):
    return torch.softmax(x, dim=axis)

def _gelu(x):
    return torch.nn.functional.gelu(x, approximate='tanh')

def _silu(x):
    return torch.nn.functional.silu(x)

def _sigmoid(x):
    return torch.sigmoid(x)

def _layernorm(x, axis=-1, eps=1e-05):
    m = x.mean(dim=axis, keepdim=True)
    v = x.var(dim=axis, keepdim=True, unbiased=False)
    return (x - m) / torch.sqrt(v + eps)

def _scatter_add(tgt, idx, src, axis=0):
    return tgt.clone().index_add_(axis, idx, src)

def _segment_sum(src, seg, n):
    out = torch.zeros((n,) + src.shape[1:], dtype=src.dtype)
    return out.index_add_(0, seg, src)

def _pad(x, pw):
    flat = tuple((v for pair in reversed(pw) for v in pair))
    return torch.nn.functional.pad(x, flat)
kernel_name = 'standalone__molecular_angular_painn__graph'

def setup_inputs():

    _w = lambda a: (lambda t: t.to(torch.bfloat16) if t.is_floating_point() else t)(torch.as_tensor(a))
    N, deg, D = (50000, 16, 64)
    n_rbf = max(16, 4)
    E = N * deg
    cutoff = 5.0
    freqs = (torch.arange(1, n_rbf + 1) * torch.pi / cutoff).to(float)
    return {'sv': _w((lambda *s: torch.randn(*s, dtype=torch.bfloat16) * 0.4)(N, 4, D) * 0.3), 'pos': _w((lambda *s: torch.randn(*s, dtype=torch.bfloat16) * 3.2)(N, 3) * 1.2), 'src': _w((lambda lo, hi, *s: torch.randint(lo, hi, s))(0, N, E).to(torch.int64)), 'dst': _w((lambda lo, hi, *s: torch.randint(lo, hi, s))(0, N, E).to(torch.int64)), 'freqs': _w(freqs), 'w_phi1': _w((lambda *s: torch.randn(*s, dtype=torch.bfloat16) * 3.2)(D, D) / D ** 0.5), 'w_phi2': _w((lambda *s: torch.randn(*s, dtype=torch.bfloat16) * 3.2)(D, 3 * D) / D ** 0.5), 'w_rbf': _w((lambda *s: torch.randn(*s, dtype=torch.bfloat16) * 3.2)(n_rbf, 3 * D) / n_rbf ** 0.5)}

def reference(sv, pos, src, dst, freqs, w_phi1, w_phi2, w_rbf):
    N, _, D = sv.shape
    E = src.shape[0]
    PI, cutoff = (3.141592653589793, 5.0)
    s, v = (sv[:, 0, :].clone(), sv[:, 1:, :].clone())
    r_vec = pos[src] - pos[dst]
    d = torch.sqrt((r_vec * r_vec).sum(-1) + 1e-08)
    r_hat = r_vec / d[:, None]
    rbf = torch.sin(d[:, None] * freqs[None, :]) / d[:, None]
    fcut = 0.5 * (torch.cos(PI * d / cutoff) + 1.0)
    fcut = torch.where(d < cutoff, fcut, 0.0 * d)
    Wf = rbf @ w_rbf * fcut[:, None]
    phi = (_silu(s @ w_phi1) @ w_phi2)[src]
    m = phi * Wf
    m_s, m_vv, m_vr = (m[:, :D].clone(), m[:, D:2 * D].clone(), m[:, 2 * D:].clone())
    ds = _segment_sum(m_s, dst, N)
    dv_e = m_vv[:, None, :] * v[src] + m_vr[:, None, :] * r_hat[:, :, None]
    dv = _segment_sum(dv_e.reshape(E, 3 * D), dst, N).reshape(N, 3, D)
    return sv + torch.concatenate([ds[:, None, :], dv], axis=1)
```

```cpp
#include <cuda_runtime.h>
#include <cuda_bf16.h>
#include <stdint.h>

namespace {

constexpr int NWG = 3;
constexpr int REG_C = 160, REG_H = 32;
#define SPL_N 10
#define ROOM 3
#define TOUCH1 1
#define TOUCH2 5
#define FLIGHT 4
#define BALANCE 1
#define ZDELAY 0
constexpr int SPL = SPL_N;
#define GIVE_N 10
constexpr int GIVE = GIVE_N;
#define PDELAY_N 150
constexpr int PDELAY = PDELAY_N;
constexpr int THREADS = 512;
constexpr int MAXG = 136;
constexpr int MAXROW = 96;
constexpr int TMAX = MAXROW / 12 + 18;
constexpr int MAXNPC = 480;
constexpr int MAXE = 1 << 20;

constexpr int W1_OFF = 0;
constexpr int W2_OFF = 8192;
constexpr int WR_OFF = 32768;
constexpr int RING_OFF = 38912;
constexpr int SREC_OFF = RING_OFF + 4 * NWG * 12288;
constexpr int SD_OFF = SREC_OFF + (MAXROW + 1) * 128 + 16;
constexpr int SN_OFF = SD_OFF + (MAXROW + 1) * 64 + 16;
constexpr int CTL_OFF = SN_OFF + (MAXROW + 1) * 64 + 16;
constexpr int TABLE_MAXN = 50176;
constexpr int STAGE_OFF = TABLE_MAXN * 4;
constexpr int SCNT_OFF = STAGE_OFF + MAXG * 128;
constexpr int GPOS_OFF = RING_OFF;
constexpr int PACK_OFF = GPOS_OFF + 4 * 8192;
constexpr int NCNT_OFF = SCNT_OFF + 768;
constexpr int OPOS_OFF = NCNT_OFF + 2048;
constexpr int BAR_OFF = OPOS_OFF + 4096;
constexpr int MISC_OFF = BAR_OFF + 128;
constexpr int FREQ_OFF = MISC_OFF + 512;
constexpr int DUMMY_OFF = (FREQ_OFF + 128 + 127) / 128 * 128;
constexpr int SMEM_BYTES = DUMMY_OFF + 4096;
static_assert(CTL_OFF + 64 * TMAX <= SCNT_OFF && CTL_OFF + 64 * TMAX - SREC_OFF <= 64 * THREADS && 4 * (MAXG + 32) <= 768, "smem map");
static_assert(SMEM_BYTES <= 232448 && BAR_OFF % 8 == 0 && RING_OFF % 128 == 0 && SREC_OFF % 128 == 0 && GPOS_OFF % 128 == 0 && PACK_OFF + 15 * 512 <= SREC_OFF && (MAXG + 14) / 15 <= 12, "smem map");

constexpr uint32_t PAY_INVALID = 0x3FFFFFFu;
constexpr uint32_t PAY_MARK = 0x3FFFDFFu;
constexpr uint32_t NODE_SPLIT = 0x40000000u;
constexpr uint32_t ST_START = 1, ST_CLOSE = 2;
constexpr float QINVP = 9.0f / 510.0f;
constexpr uint32_t QTHRESH = 2209;
#define QSURE_N 1920
constexpr uint32_t QSURE = QSURE_N;

struct Scratch {
    unsigned sync[32];
    uint4 table[TABLE_MAXN / 4];
    uint4 wimg[RING_OFF / 16];
    uint2 pos8[TABLE_MAXN];
    uint4 xbuf[MAXG * MAXG * 8 + 3 * THREADS];
    uint4 pool[MAXG * GIVE * 16];
    unsigned rows[MAXG];
    unsigned ready[MAXG];
    int ovfcnt[MAXG];
    int2 ovf[MAXE + 8 * MAXG + 8];
};
__device__ __align__(128) Scratch g_scratch;

struct Params {
    const __nv_bfloat16* pos;
    Scratch* g;
    const int* src;
    const int* dst;
    int N, NPC, E, gpc;
    const __nv_bfloat16* w2;
    const __nv_bfloat16* wr;
    const __nv_bfloat16* w1;
    const __nv_bfloat16* freqs;
    const __nv_bfloat16* sv;
    __nv_bfloat16* out;
    uint64_t desc0;
    int G;
    uint32_t magic;
    int odd_edges;
};
constexpr uint32_t SB = 1024;

#define TSX(i, thr)
#define TR(k, thr, t)
#define TS0(i) TSX(i, 0)
#define STOP(k)
#define TRW(ctl)

__device__ __forceinline__ uint32_t smem_u32(const void* p) { return (uint32_t)__cvta_generic_to_shared(p); }
__device__ __forceinline__ void mbar_init(uint32_t bar, uint32_t cnt) {
    asm volatile("mbarrier.init.shared::cta.b64 [%0], %1;" ::"r"(bar), "r"(cnt) : "memory");
}
__device__ __forceinline__ void mbar_arrive(uint32_t bar) {
    asm volatile("mbarrier.arrive.shared::cta.b64 _, [%0];" ::"r"(bar) : "memory");
}
__device__ __forceinline__ void mbar_expect_tx(uint32_t bar, uint32_t bytes) {
    asm volatile("mbarrier.arrive.expect_tx.shared::cta.b64 _, [%0], %1;" ::"r"(bar), "r"(bytes) : "memory");
}
__device__ __forceinline__ void mbar_wait(uint32_t bar, uint32_t parity) {
    uint32_t ok;
    int it = 0;
    do {
        asm volatile(
            "{\n.reg .pred p;\n"
            "mbarrier.try_wait.parity.shared::cta.b64 p, [%1], %2, 2000;\n"
            "selp.u32 %0, 1, 0, p;\n}\n"
            : "=r"(ok) : "r"(bar), "r"(parity) : "memory");
        if (++it > (1 << 20)) __trap();
    } while (!ok);
}
__device__ __forceinline__ uint32_t mbar_test(uint32_t bar, uint32_t parity) {
    uint32_t ok;
    asm volatile("{\n.reg .pred p;\nmbarrier.test_wait.parity.shared::cta.b64 p, [%1], %2;\nselp.u32 %0, 1, 0, p;\n}\n"
                 : "=r"(ok) : "r"(bar), "r"(parity) : "memory");
    return ok;
}
__device__ __forceinline__ uint32_t pin(uint32_t x) {
    uint32_t r;
    asm volatile("shfl.sync.bfly.b32 %0, %1, 0, 31, -1;" : "=r"(r) : "r"(x));
    return r;
}
__device__ __forceinline__ void bulk_g2s(uint32_t dst, const void* src, uint32_t bytes, uint32_t bar) {
    asm volatile("cp.async.bulk.shared::cluster.global.mbarrier::complete_tx::bytes [%0], [%1], %2, [%3];"
                 ::"r"(dst), "l"(src), "r"(bytes), "r"(bar) : "memory");
}
__device__ __forceinline__ void ldsm4(uint32_t addr, uint32_t* r) {
    asm volatile("ldmatrix.sync.aligned.m8n8.x4.shared.b16 {%0,%1,%2,%3}, [%4];"
                 : "=r"(r[0]), "=r"(r[1]), "=r"(r[2]), "=r"(r[3]) : "r"(addr) : "memory");
}
__device__ __forceinline__ uint32_t pack2(float lo, float hi) {
    uint32_t r;
    asm("cvt.rn.bf16x2.f32 %0, %1, %2;" : "=r"(r) : "f"(hi), "f"(lo));
    return r;
}
__device__ __forceinline__ float bf_lo(uint32_t w) { return __uint_as_float(w << 16); }
__device__ __forceinline__ float bf_hi(uint32_t w) { return __uint_as_float(w & 0xFFFF0000u); }
__device__ __forceinline__ float rbf16(float x) { return __uint_as_float(pack2(0.f, x)); }
__device__ __forceinline__ uint32_t hmul2(uint32_t a, uint32_t b) {
    uint32_t r;
    asm("mul.rn.bf16x2 %0, %1, %2;" : "=r"(r) : "r"(a), "r"(b));
    return r;
}
__device__ __forceinline__ uint32_t hfma2(uint32_t a, uint32_t b, uint32_t c) {
    uint32_t r;
    asm("fma.rn.bf16x2 %0, %1, %2, %3;" : "=r"(r) : "r"(a), "r"(b), "r"(c));
    return r;
}
__device__ __forceinline__ uint32_t hfma2_lo(uint32_t a, uint32_t b, uint32_t c) {
    uint32_t r;
    asm("{\n.reg .b16 l, h;\n.reg .b32 t;\nmov.b32 {l, h}, %2;\nmov.b32 t, {l, l};\nfma.rn.bf16x2 %0, %1, t, %3;\n}\n" : "=r"(r) : "r"(a), "r"(b), "r"(c));
    return r;
}
__device__ __forceinline__ uint32_t hfma2_hi(uint32_t a, uint32_t b, uint32_t c) {
    uint32_t r;
    asm("{\n.reg .b16 l, h;\n.reg .b32 t;\nmov.b32 {l, h}, %2;\nmov.b32 t, {h, h};\nfma.rn.bf16x2 %0, %1, t, %3;\n}\n" : "=r"(r) : "r"(a), "r"(b), "r"(c));
    return r;
}
__device__ __forceinline__ uint32_t hmul2_hi(uint32_t a, uint32_t b) {
    uint32_t r;
    asm("{\n.reg .b16 l, h;\n.reg .b32 t;\nmov.b32 {l, h}, %2;\nmov.b32 t, {h, h};\nmul.rn.bf16x2 %0, %1, t;\n}\n" : "=r"(r) : "r"(a), "r"(b));
    return r;
}
__device__ __forceinline__ uint32_t hadd2(uint32_t a, uint32_t b) {
    uint32_t r;
    asm("add.rn.bf16x2 %0, %1, %2;" : "=r"(r) : "r"(a), "r"(b));
    return r;
}
__device__ __forceinline__ uint32_t hsub2(uint32_t a, uint32_t b) {
    uint32_t r;
    asm("sub.rn.bf16x2 %0, %1, %2;" : "=r"(r) : "r"(a), "r"(b));
    return r;
}
__device__ __forceinline__ void cp_async_arrive(uint32_t bar) {
    asm volatile("cp.async.mbarrier.arrive.noinc.shared::cta.b64 [%0];" ::"r"(bar) : "memory");
}
__device__ __forceinline__ float tanh_fast(float x) {
    float r;
    asm("tanh.approx.f32 %0, %1;" : "=f"(r) : "f"(x));
    return r;
}
__device__ __forceinline__ void wg_fence() { asm volatile("wgmma.fence.sync.aligned;" ::: "memory"); }
__device__ __forceinline__ void wg_commit() { asm volatile("wgmma.commit_group.sync.aligned;" ::: "memory"); }
template <int N>
__device__ __forceinline__ void wg_wait() { asm volatile("wgmma.wait_group.sync.aligned %0;" ::"n"(N) : "memory"); }

#define WG_REGS "{%0,%1,%2,%3,%4,%5,%6,%7,%8,%9,%10,%11,%12,%13,%14,%15,%16,%17,%18,%19,%20,%21,%22,%23,%24,%25,%26,%27,%28,%29,%30,%31}"
#define WG_OPS(c) c(d[0]), c(d[1]), c(d[2]), c(d[3]), c(d[4]), c(d[5]), c(d[6]), c(d[7]), c(d[8]), c(d[9]), c(d[10]), \
    c(d[11]), c(d[12]), c(d[13]), c(d[14]), c(d[15]), c(d[16]), c(d[17]), c(d[18]), c(d[19]), c(d[20]), c(d[21]),     \
    c(d[22]), c(d[23]), c(d[24]), c(d[25]), c(d[26]), c(d[27]), c(d[28]), c(d[29]), c(d[30]), c(d[31])
__device__ __forceinline__ void wgmma_first(float* d, const uint32_t* a, uint64_t desc) {
    asm volatile("wgmma.mma_async.sync.aligned.m64n64k16.f32.bf16.bf16 " WG_REGS ", {%32,%33,%34,%35}, %36, 0, 1, 1, 1;"
                 : WG_OPS("+f") : "r"(a[0]), "r"(a[1]), "r"(a[2]), "r"(a[3]), "l"(desc));
}
__device__ __forceinline__ void wgmma_acc(float* d, const uint32_t* a, uint64_t desc) {
    asm volatile("wgmma.mma_async.sync.aligned.m64n64k16.f32.bf16.bf16 " WG_REGS ", {%32,%33,%34,%35}, %36, 1, 1, 1, 1;"
                 : WG_OPS("+f") : "r"(a[0]), "r"(a[1]), "r"(a[2]), "r"(a[3]), "l"(desc));
}
__device__ __forceinline__ void wgmma_k64(float* d, const uint32_t* a, uint64_t desc) {
    wgmma_first(d, a, desc);
    wgmma_acc(d, a + 4, desc + 128);
    wgmma_acc(d, a + 8, desc + 256);
    wgmma_acc(d, a + 12, desc + 384);
}
__device__ __forceinline__ void fence_regs(float* d) { asm volatile("" : WG_OPS("+f")::"memory"); }
__device__ __forceinline__ uint32_t qaxis(float x) {
    const float u = fmaf(x, QINVP, 0.25f);
    const float f = u - ((u + 12582912.f) - 12582912.f);
    return __float_as_uint(fmaf(fabsf(f), 510.f, 12582912.f));
}
__device__ __forceinline__ uint32_t qcode(float x, float y, float z, uint32_t tx) {
    return __byte_perm(__byte_perm(qaxis(x), qaxis(y), 0x3340), qaxis(z), 0x3410) ^ tx;
}
__device__ __forceinline__ bool near_test(uint32_t ca, uint32_t cb, uint32_t tag24, uint32_t& q) {
    const uint32_t D = __vabsdiffu4(ca, cb);
    q = __dp4a(D, D, 0x7FFFFFFFu - QSURE);
    return q <= 0x7FFFFFFFu - QSURE + QTHRESH || ((ca ^ tag24) | (cb ^ tag24)) >= 0x1000000u;
}
__device__ __forceinline__ bool inside(uint32_t rxy, uint32_t rz) {
    const uint32_t qxy = hmul2(rxy, rxy), qz = hmul2(rz, rz);
    return bf_lo(qxy) + bf_hi(qxy) + bf_lo(qz) <= 24.8125f;
}

__device__ __forceinline__ uint32_t lds32(uint32_t addr) {
    uint32_t r;
    asm volatile("ld.shared.u32 %0, [%1];" : "=r"(r) : "r"(addr));
    return r;
}
__device__ __forceinline__ void sts32_if(uint32_t addr, uint32_t v, bool c) {
    asm volatile("{\n.reg .pred p;\nsetp.ne.u32 p, %2, 0;\n@p st.shared.u32 [%0], %1;\n}\n" ::"r"(addr), "r"(v), "r"((uint32_t)c) : "memory");
}
__device__ __forceinline__ void stg128_if(void* ptr, uint4 v, bool c) {
    asm volatile("{\n.reg .pred p;\nsetp.ne.u32 p, %5, 0;\n@p st.relaxed.gpu.global.v4.u32 [%0], {%1,%2,%3,%4};\n}\n"
                 ::"l"(ptr), "r"(v.x), "r"(v.y), "r"(v.z), "r"(v.w), "r"((uint32_t)c) : "memory");
}
__device__ __forceinline__ void lds128(uint32_t addr, uint32_t* r) {
    asm volatile("ld.shared.v4.u32 {%0,%1,%2,%3}, [%4];" : "=r"(r[0]), "=r"(r[1]), "=r"(r[2]), "=r"(r[3]) : "r"(addr) : "memory");
}
__device__ __forceinline__ void stg2_if(uint64_t ptr, const uint32_t* r, bool c) {
    asm volatile("{\n.reg .pred p;\nsetp.ne.u32 p, %9, 0;\n@p st.global.cs.v4.u32 [%8], {%0,%1,%2,%3};\n"
                 "@p st.global.cs.v4.u32 [%8 + 64], {%4,%5,%6,%7};\n}\n"
                 ::"r"(r[0]), "r"(r[1]), "r"(r[2]), "r"(r[3]), "r"(r[4]), "r"(r[5]), "r"(r[6]), "r"(r[7]), "l"(ptr), "r"((uint32_t)c) : "memory");
}
#define GCOND "setp.ne.u32 p, n, 0xFFFF;"
template <int NP, int HI, int PAD = 1>
__device__ __forceinline__ void gather(uint32_t dst, const void* base, uint32_t c, uint32_t e) {
#define GATHER_HEAD "{\n.reg .pred p;\n.reg .b32 n;\n.reg .b64 a;\nprmt.b32 n, %2, 0, %3;\n" GCOND "\nmad.lo.u32 n, n, 512, %4;\nmad.wide.u32 a, n, 1, %1;\n"
#define GATHER_1(P) P "cp.async.cg.shared.global [%0], [a], 16;\n}\n"
#define GATHER_3(P) P "cp.async.cg.shared.global [%0], [a + 128], 16;\n" P "cp.async.cg.shared.global [%0 + 1024], [a + 256], 16;\n" \
                    P "cp.async.cg.shared.global [%0 + 2048], [a + 384], 16;\n}\n"
#define GATHER_ARGS(z) ::"r"(dst), "l"(base), "r"(e), "n"((HI ? 0x32 : 0x10) + z), "r"(c) : "memory"
    if constexpr (NP == 1 && PAD) asm volatile(GATHER_HEAD GATHER_1("@p ") GATHER_ARGS(0x4400));
    if constexpr (NP == 1 && !PAD) asm volatile(GATHER_HEAD GATHER_1("") GATHER_ARGS(0x4400));
    if constexpr (NP == 3 && PAD) asm volatile(GATHER_HEAD GATHER_3("@p ") GATHER_ARGS(0x5500));
    if constexpr (NP == 3 && !PAD) asm volatile(GATHER_HEAD GATHER_3("") GATHER_ARGS(0x4400));
    if constexpr (NP == 4)
        asm volatile(GATHER_HEAD "setp.ge.u32 p, %2, 0x40000000;\ncp.async.cg.shared.global [%0], [a], 16, p;\ncp.async.cg.shared.global [%0 + 1024], [a + 128], 16, p;\n"
                     "cp.async.cg.shared.global [%0 + 2048], [a + 256], 16, p;\ncp.async.cg.shared.global [%0 + 3072], [a + 384], 16, p;\n}\n" GATHER_ARGS(0x4400));
}
__device__ __forceinline__ void cp_commit() { asm volatile("cp.async.commit_group;" ::: "memory"); }
__device__ __forceinline__ void cp_wait1() { asm volatile("cp.async.wait_group 1;" ::: "memory"); }
__device__ __forceinline__ uint32_t hmul2_lo(uint32_t a, uint32_t b) {
    uint32_t r;
    asm("{\n.reg .b16 l, h;\n.reg .b32 t;\nmov.b32 {l, h}, %2;\nmov.b32 t, {l, l};\nmul.rn.bf16x2 %0, %1, t;\n}\n" : "=r"(r) : "r"(a), "r"(b));
    return r;
}
__device__ __forceinline__ void lds2_if(uint32_t a0, uint32_t a1, uint32_t* r, uint32_t c) {
    asm volatile("{\n.reg .pred p;\nsetp.ne.u32 p, %10, 0;\n@p ld.shared.v4.u32 {%0,%1,%2,%3}, [%8];\n@p ld.shared.v4.u32 {%4,%5,%6,%7}, [%9];\n}\n"
                 : "+r"(r[0]), "+r"(r[1]), "+r"(r[2]), "+r"(r[3]), "+r"(r[4]), "+r"(r[5]), "+r"(r[6]), "+r"(r[7])
                 : "r"(a0), "r"(a1), "r"(c) : "memory");
}
__device__ __forceinline__ int fresh_lane() {
    int l;
    asm volatile("mov.u32 %0, %%laneid;" : "=r"(l));
    return l;
}

__device__ __forceinline__ void cold_edges(unsigned char* smem, const Params& p, int lo, int hi, uint32_t tag) {
#pragma unroll 1
    for (int e = lo + threadIdx.x; e < hi; e += THREADS) {
        const int s = p.src[e], d = p.dst[e];
        uint32_t q;
        if (near_test(reinterpret_cast<const uint32_t*>(smem)[s], reinterpret_cast<const uint32_t*>(smem)[d], tag << 24, q)) {
            const uint32_t own = __umulhi((uint32_t)d, p.magic);
            const uint32_t slot4 = atomicAdd(reinterpret_cast<uint32_t*>(smem + SCNT_OFF) + own, 4u);
            uint32_t* line = reinterpret_cast<uint32_t*>(smem + STAGE_OFF) + own * 32;
            if (slot4 < 124) {
                line[slot4 >> 2] = ((uint32_t)s << 15) + ((uint32_t)(d - own * p.NPC) << 6) + tag + (q & 0x80000000u);
            } else {
                uint32_t o = atomicAdd(reinterpret_cast<uint32_t*>(smem + MISC_OFF) + 16, 1u);
                p.g->ovf[(size_t)blockIdx.x * (4 * p.gpc + 4) + o] = make_int2(s, d);
                line[31] = (PAY_MARK << 6) | tag;
            }
        }
    }
}
__device__ __forceinline__ void cold_filter(unsigned char* smem, const Params& p, int e0, int e1, uint32_t tag, int redo) {
    if (redo) {
        if (threadIdx.x < MAXG) reinterpret_cast<uint32_t*>(smem + SCNT_OFF)[threadIdx.x] = 0;
        __syncthreads();
    }
    cold_edges(smem, p, redo ? 4 * e0 : 4 * (e0 + 3 * THREADS), 4 * e1, tag);
    if (blockIdx.x == 0) cold_edges(smem, p, p.E & ~3, p.E, tag);
    __syncthreads();
    if (threadIdx.x == 0) p.g->ovfcnt[blockIdx.x] = reinterpret_cast<uint32_t*>(smem + MISC_OFF)[16];
    __threadfence();
    __syncthreads();
}
__device__ __forceinline__ uint3 geometry(uint32_t rxy, uint32_t rz) {
    const uint32_t qxy = hmul2(rxy, rxy), qz = hmul2(rz, rz);
    float d, id;
    asm("sqrt.approx.ftz.f32 %0, %1;" : "=f"(d) : "f"(rbf16(rbf16(bf_lo(qxy) + bf_hi(qxy) + bf_lo(qz)) + 1e-8f)));
    d = rbf16(d);
    asm("rcp.approx.ftz.f32 %0, %1;" : "=f"(id) : "f"(d));
    const float cs = rbf16(__cosf(rbf16(rbf16(3.14159265358979f * d) * 0.2f)));
    const uint32_t zs = pack2(bf_lo(rz) * id, 0.5f * rbf16(cs + 1.0f) * id);
    return d < 5.0f ? make_uint3(pack2(bf_lo(rxy) * id, bf_hi(rxy) * id), zs, __byte_perm(__float_as_uint(d), zs, 0x7632)) : make_uint3(0, 0, 0);
}
__device__ __forceinline__ void cold_messages(unsigned char* smem, const Params& p, int nn) {
    const int nbase = blockIdx.x * p.NPC, lane = threadIdx.x & 31;
    const uint32_t* box = reinterpret_cast<const uint32_t*>(p.g->xbuf) + blockIdx.x * p.G * 32;
    uint32_t* w = reinterpret_cast<uint32_t*>(smem + RING_OFF);
#pragma unroll 1
    for (int i = threadIdx.x; i < 9728; i += THREADS)
        w[i] = i < 2048 ? reinterpret_cast<const uint32_t*>(p.w1)[i] : i < 8192 ? reinterpret_cast<const uint32_t*>(p.w2)[i - 2048] : reinterpret_cast<const uint32_t*>(p.wr)[i - 8192];
#pragma unroll 1
    for (int i = threadIdx.x; i < nn * 32; i += THREADS) reinterpret_cast<uint4*>(p.out)[nbase * 32 + i] = reinterpret_cast<const uint4*>(p.sv)[nbase * 32 + i];
    __threadfence();
    __syncthreads();
    const float freq = __bfloat162float(p.freqs[lane & 15]);
#pragma unroll 1
    for (int m = -1; m < p.G; m++) {
        const int cnt = m < 0 ? p.G * 32 : (__ldcg(box + m * 32 + 31) >> 6) == PAY_MARK ? __ldcg(&p.g->ovfcnt[m]) : 0;
#pragma unroll 1
        for (int i = threadIdx.x; i - lane < cnt; i += THREADS) {
            int2 e = make_int2(0, -1);
            if (i < cnt) {
                if (m < 0) {
                    const uint32_t x = __ldcg(box + i);
                    e = make_int2((x >> 15) & 0xFFFFu, nbase + ((x >> 6) & 511u));
                } else {
                    e = __ldcg(p.g->ovf + (size_t)m * (4 * p.gpc + 4) + i);
                }
            }
            bool in = (uint32_t)(e.y - nbase) < (uint32_t)nn;
            uint3 geo = make_uint3(0, 0, 0);
            if (in) {
                const uint2 ps = __ldcg(p.g->pos8 + e.x), pd = __ldcg(p.g->pos8 + e.y);
                const uint32_t rxy = hsub2(ps.x, pd.x), rz = hsub2(ps.y, pd.y);
                in = inside(rxy, rz);
                geo = geometry(rxy, rz);
            }
#pragma unroll 1
            for (uint32_t todo = __ballot_sync(0xffffffffu, in); todo; todo &= todo - 1) {
                const int l = __ffs(todo) - 1;
                const uint32_t* row = reinterpret_cast<const uint32_t*>(p.sv) + (size_t)__shfl_sync(0xffffffffu, e.x, l) * 128 + lane;
                uint32_t* orow = reinterpret_cast<uint32_t*>(p.out) + (size_t)__shfl_sync(0xffffffffu, e.y, l) * 128 + lane;
                const uint32_t gx = __shfl_sync(0xffffffffu, geo.x, l), gy = __shfl_sync(0xffffffffu, geo.y, l);
                const float rb = rbf16(__sinf(rbf16(bf_lo(__shfl_sync(0xffffffffu, geo.z, l)) * freq)) * bf_hi(gy));
                uint32_t x = row[0];
                float a[12] = {0, 0, 0, 0, 0, 0, 0, 0, 0, 0, 0, 0};
#pragma unroll 2
                for (int k = 0; k < 64; k++) {
                    const uint32_t u = __shfl_sync(0xffffffffu, x, k >> 1), ww = w[k * 32 + lane];
                    const float f = k & 1 ? bf_hi(u) : bf_lo(u);
                    a[0] = fmaf(f, bf_lo(ww), a[0]); a[1] = fmaf(f, bf_hi(ww), a[1]);
                }
                x = pack2(0.5f * fmaf(a[0], tanh_fast(0.5f * a[0]), a[0]), 0.5f * fmaf(a[1], tanh_fast(0.5f * a[1]), a[1]));
                a[0] = a[1] = 0.f;
#pragma unroll 2
                for (int k = 0; k < 64; k++) {
                    const uint32_t u = __shfl_sync(0xffffffffu, x, k >> 1);
                    const float f = k & 1 ? bf_hi(u) : bf_lo(u), r = __shfl_sync(0xffffffffu, rb, k & 15);
#pragma unroll
                    for (int c = 0; c < 3; c++) {
                        const uint32_t ww = w[2048 + k * 96 + c * 32 + lane], wr = k < 16 ? w[8192 + k * 96 + c * 32 + lane] : 0u;
                        a[2 * c] = fmaf(f, bf_lo(ww), a[2 * c]); a[2 * c + 1] = fmaf(f, bf_hi(ww), a[2 * c + 1]);
                        a[6 + 2 * c] = fmaf(r, bf_lo(wr), a[6 + 2 * c]); a[7 + 2 * c] = fmaf(r, bf_hi(wr), a[7 + 2 * c]);
                    }
                }
                const uint32_t mv = pack2(a[2] * a[8], a[3] * a[9]), mr = pack2(a[4] * a[10], a[5] * a[11]);
                const uint32_t o[4] = {pack2(a[0] * a[6], a[1] * a[7]), hfma2_lo(mr, gx, hmul2(mv, row[32])), hfma2_hi(mr, gx, hmul2(mv, row[64])),
                                       hfma2_lo(mr, gy, hmul2(mv, row[96]))};
#pragma unroll
                for (int c = 0; c < 4; c++) asm volatile("red.global.add.noftz.bf16x2 [%0], %1;" ::"l"(orow + 32 * c), "r"(o[c]) : "memory");
            }
        }
    }
}

#define VEARLY 0
#define FORD 2
#define NPRE 5
#define SPLIT(k) asm volatile("{\n.reg .pred p;\nsetp.eq.u32 p, %0, %1;\n@p trap;\n}" ::"r"(c0), "n"(0x70000 + k) : "memory")
#define PIN8(a) asm volatile("" : "+r"((a)[0]), "+r"((a)[1]), "+r"((a)[2]), "+r"((a)[3]), "+r"((a)[4]), "+r"((a)[5]), "+r"((a)[6]), "+r"((a)[7]))
#define RINGA 2
#define RINGB 3
#define RING(k) do { if (RINGA == k) asm volatile("bar.sync %0, 256;" ::"r"(1 + (warp >> 2)) : "memory"); \
                     if (RINGB == k) asm volatile("bar.arrive %0, 256;" ::"r"((c0 >> 4) & 3) : "memory"); } while (0)
template <int V> struct IntC { static constexpr int value = V; };

template <int CN, int CE, int CG>
__global__ void __launch_bounds__(THREADS, 1) painn_kernel(const __grid_constant__ Params p) {
    extern __shared__ __align__(1024) unsigned char smem_dyn[];
    unsigned char* const smem = static_cast<unsigned char*>(__cvta_shared_to_generic(SB));
    constexpr uint32_t sb = SB;
    const int tid = threadIdx.x, lane = tid & 31;
    const int warp = __shfl_sync(0xffffffffu, tid >> 5, 0);
    constexpr int CNPC = CG ? (CN + CG - 1) / CG : 1, CGPC = CG ? (CE / 4 + CG - 1) / CG : 1;
    const int b = blockIdx.x, G = CG ? CG : p.G, NPC = CG ? CNPC : p.NPC, N = CG ? CN : p.N, gpc = CG ? CGPC : p.gpc;
    const uint32_t magic = CG ? (uint32_t)(((1ull << 32) + CNPC - 1) / CNPC) : p.magic;
    const bool odd_edges = CG ? (CE & 3) != 0 || CGPC > 3 * THREADS : p.odd_edges;
    const int nbase = b * NPC, nn = min(NPC, N - nbase);
    const int eg0 = b * gpc, eg1 = min((CG ? CE : p.E) >> 2, eg0 + gpc);

    uint4* stage4 = reinterpret_cast<uint4*>(smem + STAGE_OFF);
    uint32_t* ncnt = reinterpret_cast<uint32_t*>(smem + NCNT_OFF);
    uint32_t* misc = reinterpret_cast<uint32_t*>(smem + MISC_OFF);
    const uint32_t bar_tab = sb + BAR_OFF;

    TS0(0);
    int4 es[3], ed[3];
    auto load_edges = [&](int i) {
        const int g = min(eg0 + tid + i * THREADS, eg1 - 1);
        asm volatile("ld.global.cs.v4.u32 {%0,%1,%2,%3}, [%8];\nld.global.cs.v4.u32 {%4,%5,%6,%7}, [%9];"
                     : "=r"(es[i].x), "=r"(es[i].y), "=r"(es[i].z), "=r"(es[i].w), "=r"(ed[i].x), "=r"(ed[i].y), "=r"(ed[i].z), "=r"(ed[i].w)
                     : "l"(reinterpret_cast<const int4*>(p.src) + g), "l"(reinterpret_cast<const int4*>(p.dst) + g) : "memory");
    };
    const char* const own = reinterpret_cast<const char*>(p.sv) + (size_t)nbase * 512;
    auto touch = [&](int o) {
        if (o + lane * 256 < nn * 512)
            asm volatile("cp.async.ca.shared.global.L2::256B [%0], [%1], 4;" ::"r"(sb + DUMMY_OFF + 4 * lane), "l"(own + o + lane * 256) : "memory");
    };
    unsigned epoch;
    const uint32_t tbytes = ((N + 3) >> 2) * 16;
    {
        uint32_t pxy, pz;
        asm volatile("ld.global.nc.u32 %0, [%3];\nld.global.nc.u32 %1, [%3 + 4];\nld.global.ca.u32 %2, [%4];"
                     : "=r"(pxy), "=r"(pz), "=r"(epoch)
                     : "l"(reinterpret_cast<const uint32_t*>(p.pos) + ((nbase + min(tid, nn - 1)) * 3 >> 1)), "l"(p.g->sync) : "memory");
        const uint32_t sh = ((nbase + tid) & 1) << 4;
        pxy = __funnelshift_r(pxy, pz, sh);
        pz >>= sh;
        if (tid < nn) {
            reinterpret_cast<uint32_t*>(p.g->table)[nbase + tid] = qcode(bf_lo(pxy), bf_hi(pxy), bf_lo(pz), ((epoch & 31u) ^ 0x6Bu) << 24);
            p.g->pos8[nbase + tid] = make_uint2(pxy, pz);
        }
        reinterpret_cast<uint2*>(smem + OPOS_OFF)[tid] = make_uint2(pxy, pz);
        if (pxy == 0xFFFFFFFFu && pz == 0xFFFFFFFFu && epoch == 0xFFFFFFFFu) asm volatile("nanosleep.u32 0;");
        load_edges(0);
    }
    __syncthreads();
    const uint32_t tag = (epoch & 31u) | 32u;
    if (tid == THREADS - 1) {
        asm volatile("red.relaxed.gpu.global.add.u32 [%0], 1;" ::"l"(p.g->sync + 1) : "memory");
        TSX(1, 511);
        const unsigned want = (epoch + 1) * G;
        unsigned c;
        int it = smem_u32(smem_dyn) == SB ? 0 : 1 << 22;
        do {
            asm volatile("ld.relaxed.gpu.global.u32 %0, [%1];" : "=r"(c) : "l"(p.g->sync + 1) : "memory");
            if (++it > (1 << 22)) __trap();
        } while (c != want);
        mbar_init(bar_tab, 1);
        mbar_expect_tx(bar_tab, tbytes);
        bulk_g2s(sb, p.g->table, tbytes, bar_tab);
        TSX(2, 511);
    }
    if (warp == 14) {
#pragma unroll 1
        for (int c = b * 32 + lane; c < RING_OFF / 16; c += G * 32) {
            const int row = c >> 3, j = (c ^ row) & 7;
            uint4 v;
            if (c < 512) {
                const uint32_t half = 0x3F003F00u;
                v = __ldg(reinterpret_cast<const uint4*>(p.w1) + row * 8 + j);
                v = make_uint4(hmul2(v.x, half), hmul2(v.y, half), hmul2(v.z, half), hmul2(v.w, half));
            } else {
                const uint32_t* q = (c < 2048 ? reinterpret_cast<const uint32_t*>(p.w2) + (row & 63) * 96 + ((row >> 6) - 1) * 32
                                              : reinterpret_cast<const uint32_t*>(p.wr) + (row & 15) * 96 + ((row >> 4) - 16) * 32) + (j & 4) * 4 + (j & 3);
                v = make_uint4(__ldg(q), __ldg(q + 4), __ldg(q + 8), __ldg(q + 12));
            }
            p.g->wimg[c] = v;
        }
    }
    if (tid == 416) {
#pragma unroll
        for (int i = 0; i < FLIGHT + 2; i++) mbar_init(sb + BAR_OFF + 8 + 8 * i, i ? 1 : 15);
    }
    ncnt[tid] = 0;
    if (tid < MAXG) reinterpret_cast<uint32_t*>(smem + SCNT_OFF)[tid] = 0;
    if (tid < 128) misc[tid] = 0;
    {
        const uint32_t inv = (PAY_INVALID << 6) | tag;
        stage4[tid] = stage4[tid + THREADS] = make_uint4(inv, inv, inv, inv);
        if (tid < MAXG * 8 - 2 * THREADS) stage4[tid + 2 * THREADS] = make_uint4(inv, inv, inv, inv);
    }
    __syncthreads();
    uint4* const xout = p.g->xbuf + ((tid >> 3) * G + b) * 8 + (tid & 7);
#pragma unroll
    for (int i = 0; i < 3; i++) stg128_if(xout + i * G * THREADS, make_uint4(0, 0, 0, 0), tid + i * THREADS < G * 8);
    load_edges(1);
    load_edges(2);
    if ((tid >> 4) == 29) asm volatile("cp.async.ca.shared.global [%0], [%1], 4;" ::"r"(sb + FREQ_OFF + 8 * (tid & 14) + 4 * (tid & 1)),
                              "l"(reinterpret_cast<const uint32_t*>(p.freqs) + ((tid & 7) >> 1) + (tid & 1) * 4) : "memory");
    if (tid == 416) asm volatile("fence.acq_rel.gpu;" ::: "memory");
    if (warp == 15) {
        __syncwarp();
#pragma unroll
        for (int i = 0; i < TOUCH1; i++) touch(i * 8192);
    }
    mbar_wait(bar_tab, 0);
    TS0(3);
    if (warp == 15) {
#pragma unroll
        for (int i = TOUCH1; i < TOUCH2; i++) touch(i * 8192);
    }

#pragma unroll 1
    for (int i = 0, g = eg0 + tid; i < 3; i++, g += THREADS) {
        const int s[4] = {es[0].x, es[0].y, es[0].z, es[0].w}, d[4] = {ed[0].x, ed[0].y, ed[0].z, ed[0].w};
        uint32_t ca[4], cb[4], own[4], sl[4], q[4];
        bool c[4];
#pragma unroll
        for (int j = 0; j < 4; j++) { ca[j] = lds32(sb + 4 * s[j]); cb[j] = lds32(sb + 4 * d[j]); }
#pragma unroll
        for (int j = 0; j < 4; j++) {
            c[j] = near_test(ca[j], cb[j], tag << 24, q[j]) && g < eg1;
            own[j] = __umulhi((uint32_t)d[j], magic);
            sl[j] = atomicAdd(reinterpret_cast<uint32_t*>(smem + SCNT_OFF) + (c[j] ? own[j] : MAXG + lane), 4u);
        }
#pragma unroll
        for (int j = 0; j < 4; j++)
            sts32_if(sb + STAGE_OFF + own[j] * 128 + sl[j], own[j] * (uint32_t)(-64 * NPC) + (((uint32_t)s[j] << 15) + (((uint32_t)d[j] << 6) + ((q[j] & 0x80000000u) | tag))),
                     c[j] && sl[j] < 124);
        es[0] = es[1]; es[1] = es[2];
        ed[0] = ed[1]; ed[1] = ed[2];
    }
    __syncthreads();
    {
        const int redo = __syncthreads_or(tid < MAXG && reinterpret_cast<uint32_t*>(smem + SCNT_OFF)[tid] > 124);
        if (__builtin_expect(redo || odd_edges, 0)) cold_filter(smem, p, eg0, eg1, tag, redo);
    }
    TS0(4);
    STOP(3);
#pragma unroll
    for (int i = 0; i < 3; i++) stg128_if(xout + i * G * THREADS, stage4[tid + i * THREADS], tid + i * THREADS < G * 8);
    if (warp == 14) asm volatile("cp.async.wait_all;" ::: "memory");
    __syncthreads();
#pragma unroll
    for (int i = 0; i < 4; i++) {
        const int c = tid + i * THREADS;
        const uint32_t x = c < (SN_OFF - SREC_OFF) / 16 ? 0u : 0xFFFFFFFFu;
        if (c < (CTL_OFF + 64 * TMAX - SREC_OFF) / 16) reinterpret_cast<uint4*>(smem + SREC_OFF)[c] = make_uint4(x, x, x, x);
    }
    STOP(4);
    uint32_t key[4];
    uint2 pr[4];
    const uint32_t gp = sb + GPOS_OFF + tid * 16;
    uint32_t pk = 0;
    if (warp == 15) {
        if (lane == 0) {
            int o = TOUCH2 * 8192;
#pragma unroll 1
            while (o < nn * 512 && !mbar_test(sb + BAR_OFF + 8, 0)) {
                const uint32_t bar = sb + BAR_OFF + 16 + 8 * (pk % FLIGHT);
                if (!mbar_test(bar, ~(pk / FLIGHT) & 1)) continue;
                const int n = min(4096, nn * 512 - o);
                mbar_expect_tx(bar, n);
                bulk_g2s(sb + DUMMY_OFF, own + o, n, bar);
                o += n;
                pk++;
            }
            misc[3] = pk;
        }
        __syncwarp();
        STOP(5);
    } else {
    __nanosleep(PDELAY);
    TS0(5);

    {
        const int LPW = (G + 14) / 15;
        uint32_t ew[3][4], bad[3];
        const uint4* cp = p.g->xbuf + (b * G + warp * LPW) * 8 + lane;
#pragma unroll
        for (int i = 0; i < 3; i++) {
            bad[i] = lane + 32 * i < min(LPW, G - warp * LPW) * 8;
            ew[i][0] = ew[i][1] = ew[i][2] = ew[i][3] = (PAY_INVALID << 6) | tag;
        }
        int it = 0;
#pragma unroll 1
        do {
#pragma unroll
            for (int i = 0; i < 3; i++)
                asm volatile("{\n.reg .pred p;\nsetp.ne.u32 p, %5, 0;\n@p ld.relaxed.gpu.global.v4.u32 {%0,%1,%2,%3}, [%4];\n}\n"
                             : "+r"(ew[i][0]), "+r"(ew[i][1]), "+r"(ew[i][2]), "+r"(ew[i][3]) : "l"(cp + 32 * i), "r"(bad[i]) : "memory");
#pragma unroll
            for (int i = 0; i < 3; i++) bad[i] = ((ew[i][0] ^ tag) | (ew[i][1] ^ tag) | (ew[i][2] ^ tag) | (ew[i][3] ^ tag)) & 63u;
            if (++it > (1 << 22)) __trap();
        } while (__any_sync(0xffffffffu, bad[0] | bad[1] | bad[2]));
        STOP(5);
        TSX(21, 0); TSX(22, 448);
        uint4* pack = reinterpret_cast<uint4*>(smem + PACK_OFF);
        int nch = 0;
        uint32_t at[3];
#pragma unroll
        for (int i = 0; i < 3; i++) {
            const uint32_t m = __ballot_sync(0xffffffffu, ew[i][0] < (PAY_MARK << 6));
            at[i] = nch + __popc(m & ((1u << lane) - 1));
            nch += __popc(m);
        }
        if (__builtin_expect(nch > 32, 0)) {
#pragma unroll 1
            for (int i = 0; i < 3; i++) {
                if (ew[0][0] < (PAY_MARK << 6) && at[0] >= 32) at[0] = (15 - warp) * 32 - 1 - min(atomicAdd(&misc[1], 1u), 31u);
                const uint32_t x = at[0], y = ew[0][0];
                at[0] = at[1]; at[1] = at[2]; at[2] = x;
                ew[0][0] = ew[1][0]; ew[1][0] = ew[2][0]; ew[2][0] = y;
            }
        }
#pragma unroll
        for (int i = 0; i < 3; i++) {
            asm volatile("{\n.reg .pred p;\nsetp.lt.u32 p, %1, %5;\n@p st.shared.v4.u32 [%0], {%1,%2,%3,%4};\n}\n"
                         ::"r"(sb + PACK_OFF + (warp * 32 + at[i]) * 16), "r"(ew[i][0]), "r"(ew[i][1]), "r"(ew[i][2]), "r"(ew[i][3]), "n"(PAY_MARK << 6) : "memory");
            sts32_if(sb + MISC_OFF + 4 * 17, 1, (ew[i][3] >> 6) == PAY_MARK);
        }
        bool have = lane < nch;
        if (warp == 14) {
            asm volatile("bar.sync 7, 480;" ::: "memory");
            const uint32_t extra = misc[1];
            if (nch + extra > 32) misc[18] = 1;
            have = have || lane + extra >= 32;
        } else {
            asm volatile("bar.arrive 7, 480;" ::: "memory");
        }
        __syncwarp();
        uint32_t w[4], rk[4];
        bool in[4];
        {
            const uint4 x = pack[tid];
            w[0] = have ? x.x : ~0u; w[1] = have ? x.y : ~0u; w[2] = have ? x.z : ~0u; w[3] = have ? x.w : ~0u;
        }
        auto fetch = [&](int j, bool c) {
            asm volatile("{\n.reg .pred p;\nsetp.ne.u32 p, %2, 0;\n@p cp.async.cg.shared.global [%0], [%1], 16;\n}\n"
                         ::"r"(gp + j * 8192), "l"(reinterpret_cast<const uint4*>(p.g->pos8) + ((w[j] >> 16) & 0x7FFFu)), "r"((uint32_t)c) : "memory");
        };
#pragma unroll
        for (int j = 0; j < 4; j++) fetch(j, (int)w[j] < (int)(PAY_MARK << 6));
#pragma unroll
        for (int j = 0; j < 4; j++) pr[j] = reinterpret_cast<const uint2*>(smem + OPOS_OFF)[(w[j] >> 6) & 511u];
        asm volatile("cp.async.wait_all;" ::: "memory");
        TSX(23, 0); TSX(24, 448);
        asm volatile("{\n.reg .pred p;\nsetp.eq.u32 p, %1, 0;\n@p mbarrier.arrive.shared::cta.b64 _, [%0];\n}\n" ::"r"(sb + BAR_OFF + 8), "r"(lane) : "memory");
#pragma unroll
        for (int j = 0; j < 4; j++) {
            uint2 ps;
            asm volatile("ld.shared.v2.u32 {%0,%1}, [%2];" : "=r"(ps.x), "=r"(ps.y) : "r"(gp + j * 8192 + ((w[j] >> 12) & 8)) : "memory");
            in[j] = ((int)w[j] >= 0) | (((int)w[j] < (int)(PAY_MARK << 6)) & inside(hsub2(ps.x, pr[j].x), hsub2(ps.y, pr[j].y)));
        }
#pragma unroll
        for (int j = 0; j < 4; j++) rk[j] = atomicAdd(&ncnt[in[j] ? (w[j] >> 6) & 511u : 480 + lane], 1u);
#pragma unroll
        for (int j = 0; j < 4; j++) {
            rk[j] = rk[j] < SPL ? 2 * rk[j] : min(2 * rk[j] - (2 * SPL - 1), 63u);
            atomicAdd(&misc[in[j] && !(rk[j] & 2) ? 32 + (rk[j] >> 2) : 63], 1u);
            key[j] = in[j] ? ((w[j] >> 15) & 0xFFFFu) | ((w[j] << 10) & 0x1FF0000u) | (rk[j] << 25) : 0xF8000000u;
        }
#pragma unroll
        for (int j = 0; j < 4; j++) fetch(j, (int)w[j] >= 0);
    }
    }
    __syncthreads();
    TS0(6);
    if (tid == THREADS - 33) {
        if (b == 0) p.g->sync[0] = epoch + 1;
        asm volatile("fence.proxy.async.global;" ::: "memory");
        mbar_expect_tx(bar_tab, RING_OFF);
        bulk_g2s(sb, p.g->wimg, RING_OFF, bar_tab);
    }
    __syncwarp();
    STOP(6);
    uint32_t dst = sb + RING_OFF + warp * 12288 + (lane >> 3) * 256 + (((lane & 7) ^ (lane >> 3)) << 4), l7 = (lane & 7) * 16, g32 = (lane >> 2) * 32;
    uint32_t e0, e1, n0, n1;
    auto sources = [&](uint32_t c) {
        asm volatile("{\n.reg .b32 a;\nlop3.b32 a, %4, %5, 0xFFC0, 0xA8;\nshr.u32 a, a, 2;\nld.shared.v4.u32 {%0,%1,%2,%3}, [a + %6];\n}\n"
                     : "=r"(e0), "=r"(n0), "=r"(e1), "=r"(n1) : "r"(c), "r"(g32), "n"(SB + SN_OFF));
    };
    auto load_s = [&](auto pad) {
        gather<1, 0, pad.value>(dst, p.sv, l7, e0); gather<1, 1, pad.value>(dst + 1024, p.sv, l7, e0);
        gather<1, 0, pad.value>((dst ^ 64) + 128, p.sv, l7, e1); gather<1, 1, pad.value>((dst ^ 64) + 1152, p.sv, l7, e1);
    };
    auto load_o = [&]() {
        gather<4, 0>(dst + 8192, p.sv, l7, n0); gather<4, 0>((dst ^ 64) + 8320, p.sv, l7, n1);
    };
    auto load_v = [&](auto pad) {
        gather<3, 0, pad.value>(dst + 2048, p.sv, l7, e0); gather<3, 1, pad.value>(dst + 5120, p.sv, l7, e0);
        gather<3, 0, pad.value>((dst ^ 64) + 2176, p.sv, l7, e1); gather<3, 1, pad.value>((dst ^ 64) + 5248, p.sv, l7, e1);
        cp_commit();
    };
    const int ng = (misc[32] + 7) >> 3;
    const int give = max(min(ng - max((int)(misc[33] + 7) >> 3, 4 * NWG), GIVE), 0);
    if (warp == 15) {
        const uint32_t cnt = lane < 16 ? (misc[32 + lane] + 7) >> 3 : 0u;
        uint32_t z = cnt;
#pragma unroll
        for (int o = 1; o < 16; o <<= 1) {
            const uint32_t y = __shfl_up_sync(0xffffffffu, z, o);
            if (lane >= o) z += y;
        }
        misc[96 + lane] = lane < 16 ? 64 * (z - cnt) : 64 * (MAXROW + 1);
        asm volatile("bar.arrive 5, 512;" ::: "memory");
        if (lane == 15) {
            const bool cold = cnt || z > MAXROW || misc[31 + SPL / 2] > 32 || misc[17] || misc[18];
            misc[18] = cold;
            asm volatile("st.relaxed.gpu.global.u32 [%0], %1;" ::"l"(p.g->rows + b), "r"(~epoch << 16 | (cold ? 255 : give << 8 | z)) : "memory");
        }
        pk = (z - cnt) << 8 | __shfl_down_sync(0xffffffffu, cnt, 1) << 24;
    } else {
        if (warp * 32 < nn) {
            const uint32_t c = ncnt[tid], st = tid < nn ? (min(c, (uint32_t)SPL) + 1) >> 1 : 17u;
            const uint32_t same = __match_any_sync(0xffffffffu, st), first = __ffs(same) - 1;
            uint32_t r, node = nbase + tid;
            asm volatile("atom.shared.add.u32 %0, [%1], %2;" : "=r"(r)
                         : "r"(lane == first ? sb + MISC_OFF + 4 * (64 + st) : sb + NCNT_OFF + 4 * (480 + lane)), "r"(__popc(same)) : "memory");
            r = __shfl_sync(0xffffffffu, r, first) + __popc(same & ((1u << lane) - 1)) + misc[32 + st];
            if (__builtin_expect(c > SPL, 0)) {
                const uint32_t s2 = min((c - SPL + 1) >> 1, 16u), r2 = misc[32 + s2] + atomicAdd(&misc[64 + s2], 1u), k = atomicAdd(&misc[2], 1u);
                reinterpret_cast<uint32_t*>(smem + SCNT_OFF)[k & 31] = node;
                node |= NODE_SPLIT;
                ncnt[512 + tid] = 8 * r2;
                reinterpret_cast<uint32_t*>(smem + SN_OFF)[(r2 & 511) * 2 + 1] = node;
            }
            if (tid < nn) {
                ncnt[tid] = 8 * r;
                reinterpret_cast<uint32_t*>(smem + SN_OFF)[(r & 511) * 2 + 1] = node;
            }
        }
        asm volatile("bar.sync 5, 512;" ::: "memory");
        uint32_t slot[4];
#pragma unroll
        for (int j = 0; j < 4; j++) slot[j] = min(misc[96 + (key[j] >> 27)] + ncnt[(key[j] >> 16) & 1023], 64u * (MAXROW + 1)) + ((key[j] >> 25) & 2);
#pragma unroll
        for (int j = 0; j < 4; j++) {
            *reinterpret_cast<uint16_t*>(smem + SN_OFF + slot[j]) = (uint16_t)key[j];
            slot[j] += slot[j] & 2;
        }
        asm volatile("cp.async.wait_all;" ::: "memory");
        uint2 ps[4];
#pragma unroll
        for (int j = 0; j < 4; j++)
            asm volatile("ld.shared.v2.u32 {%0,%1}, [%2];" : "=r"(ps[j].x), "=r"(ps[j].y) : "r"(gp + j * 8192 + (key[j] & 1) * 8) : "memory");
        asm volatile("bar.sync 6, 480;" ::: "memory");
        TS0(7);
        if (warp < 4 * NWG) {
            sources((warp < ng ? warp : MAXROW) << 8);
            e0 = __vminu2(e0, (N - 1) * 0x10001u);
            e1 = __vminu2(e1, (N - 1) * 0x10001u);
            load_s(IntC<0>{});
            load_o();
            cp_commit();
        }
        TSX(9, 0);
#pragma unroll 1
        for (int i = 0; i < 2; i++) {
#pragma unroll
            for (int u = 0; u < 2; u++) {
                const uint3 geo = geometry(hsub2(ps[u].x, pr[u].x), hsub2(ps[u].y, pr[u].y));
                *reinterpret_cast<uint2*>(smem + SREC_OFF + 2 * slot[u]) = make_uint2(geo.x, geo.y);
                *reinterpret_cast<uint32_t*>(smem + SD_OFF + slot[u]) = geo.z;
                ps[u] = ps[u + 2];
                pr[u] = pr[u + 2];
                slot[u] = slot[u + 2];
            }
        }
    }
    __syncthreads();
    TS0(8);
    auto drain = [&](int i) { if (i < FLIGHT) mbar_wait(sb + BAR_OFF + 16 + 8 * i, ~((misc[3] + FLIGHT - 1 - i) / FLIGHT) & 1); };
    if (__builtin_expect(misc[18], 0)) {
        drain(warp);
        asm volatile("cp.async.wait_all;" ::: "memory");
        __syncthreads();
        cold_messages(smem, p, nn);
        mbar_wait(bar_tab, 1);
        return;
    }

    if (warp < 4 * NWG) {
        asm volatile("setmaxnreg.inc.sync.aligned.u32 %0;" ::"n"(REG_C));
        const int lane = fresh_lane();
        const int g = lane >> 2, q = lane & 3;
        const uint64_t dW1 = p.desc0, dW2 = dW1 + (W2_OFF >> 4), dWR = dW1 + (WR_OFF >> 4);
        const uint32_t ring = sb + RING_OFF + warp * 12288;
        const uint32_t vrow = pin(ring + g * 128 + ((q ^ ((g & 1) << 2) ^ (g >> 1)) << 4));
        const uint32_t mrow = pin(ring + (lane & 15) * 128 + (((lane >> 4) ^ ((lane & 1) << 2) ^ ((lane & 7) >> 1)) << 4));
        dst = pin(dst); l7 = pin(l7); g32 = pin(g32);
        uint32_t ctl = sb + CTL_OFF + warp * 4;
        auto control = [&](uint32_t c, uint32_t at) {
            int it = 0;
#pragma unroll 1
            while (__builtin_expect((c = __reduce_or_sync(0xffffffffu, c)) == 0xFFFFFFFFu, 0)) {
                asm volatile("ld.volatile.shared.u32 %0, [%1];" : "=r"(c) : "r"(at) : "memory");
                if (++it > (1 << 24)) __trap();
            }
            return c;
        };
        uint32_t c0 = control(0xFFFFFFFFu, ctl), c1 = control(0xFFFFFFFFu, ctl + 64);
        if (warp >= 8) asm volatile("bar.arrive 1, 256;" ::: "memory");
        uint32_t acc[32];
        float P[32], W[32];
#pragma unroll
        for (int i = 0; i < 32; i++) { acc[i] = 0; P[i] = W[i] = 0.f; }
        mbar_wait(bar_tab, 1);
        if (warp >= VEARLY) {
            asm volatile("cp.async.wait_all;" ::: "memory");
            load_v(IntC<0>{});
        }
#pragma unroll 1
        while ((int)c0 >= 0) {
            uint32_t h[16], rf[4], rr[4], m[16];
            TRW(ctl);
            RING(0);
            uint32_t dd[2], f01, f23;
            asm volatile("ld.shared.v2.u32 {%0,%1}, [%2 + %3];" : "=r"(dd[0]), "=r"(dd[1]) : "r"(((c0 & 0xFF00) | g32) >> 2), "n"(SB + SD_OFF));
            asm volatile("ld.shared.v2.u32 {%0,%1}, [%2 + %3];" : "=r"(f01), "=r"(f23) : "r"(l7), "n"(SB + FREQ_OFF));
            cp_wait1();
            __syncwarp();
#pragma unroll
            for (int i = 0; i < 4; i++) ldsm4(mrow ^ (i << 5), h + 4 * i);
            wg_fence();
            wgmma_k64(P, h, dW1);
            wg_commit();
            RING(1);
            SPLIT(1);
#pragma unroll
            for (int k = 0; k < 4; k++) lds2_if(vrow + 8192 + 1024 * k, (vrow ^ 64) + 8192 + 1024 * k, acc + 8 * k, c0 & ST_START);
#pragma unroll
            for (int hh = 0; hh < 2; hh++) {
                const float sc = bf_hi(dd[hh]);
                const uint32_t x01 = hmul2_lo(f01, dd[hh]), x23 = hmul2_lo(f23, dd[hh]);
                rf[hh] = pack2(__sinf(bf_lo(x01)) * sc, __sinf(bf_hi(x01)) * sc);
                rf[2 + hh] = pack2(__sinf(bf_lo(x23)) * sc, __sinf(bf_hi(x23)) * sc);
            }
            asm volatile("" : "+r"(rf[0]), "+r"(rf[1]), "+r"(rf[2]), "+r"(rf[3]));
            sources(c1);
            RING(2);
            SPLIT(2);
            wg_wait<0>();
            fence_regs(P);
#pragma unroll
            for (int i = 0; i < 16; i++)
                h[i] = pack2(fmaf(P[2 * i], tanh_fast(P[2 * i]), P[2 * i]), fmaf(P[2 * i + 1], tanh_fast(P[2 * i + 1]), P[2 * i + 1]));
            wg_fence();
            wgmma_k64(P, h, dW2 + 1024);
            wgmma_first(W, rf, dWR + 256);
            wg_commit();
            RING(3);
            SPLIT(3);
            lds128(sb + SREC_OFF + (((c0 & 0xFF00) | g32) >> 1), rr);
            __syncwarp();
            load_s(IntC<1>{});
            if (c1 & ST_START) load_o();
            cp_commit();
            wg_wait<0>();
            fence_regs(P); fence_regs(W);
#pragma unroll
            for (int j = 0; j < 8; j++) {
                m[j] = pack2(P[4 * j] * W[4 * j], P[4 * j + 1] * W[4 * j + 1]);
                m[8 + j] = pack2(P[4 * j + 2] * W[4 * j + 2], P[4 * j + 3] * W[4 * j + 3]);
            }
            wg_fence();
            wgmma_k64(P, h, dW2);
            wgmma_first(W, rf, dWR);
            wg_commit();
            RING(4);
            SPLIT(4);
            PIN8(m); PIN8(m + 8);
#pragma unroll
            for (int k = 1; k < 4; k++)
#pragma unroll
                for (int j = 0; j < 8; j++) {
                    const uint32_t x = k == 1 ? hfma2_lo(m[j], rr[0], acc[8 * k + j]) : k == 2 ? hfma2_hi(m[j], rr[0], acc[8 * k + j]) : hfma2_lo(m[j], rr[1], acc[8 * k + j]);
                    acc[8 * k + j] = k == 1 ? hfma2_lo(m[8 + j], rr[2], x) : k == 2 ? hfma2_hi(m[8 + j], rr[2], x) : hfma2_lo(m[8 + j], rr[3], x);
                }
            PIN8(acc + 8); PIN8(acc + 16); PIN8(acc + 24);
            RING(5);
            SPLIT(5);
            wg_wait<0>();
            fence_regs(P); fence_regs(W);
#pragma unroll
            for (int j = 0; j < 8; j++)
                acc[j] = hadd2(acc[j], pack2(fmaf(P[4 * j], W[4 * j], P[4 * j + 2] * W[4 * j + 2]), fmaf(P[4 * j + 1], W[4 * j + 1], P[4 * j + 3] * W[4 * j + 3])));
            wg_fence();
            wgmma_k64(P, h, dW2 + 512);
            wgmma_first(W, rf, dWR + 128);
            wg_commit();
            RING(6);
            SPLIT(6);
            cp_wait1();
            __syncwarp();
            uint32_t v[4][16];
#pragma unroll
            for (int i = 0; i < NPRE; i++) lds128((vrow ^ (64 * (i & 1))) + 2048 + 1024 * (i >> 2) + 3072 * ((i >> 1) & 1), v[1 + (i >> 2)] + 4 * (i & 3));
            wg_wait<0>();
            fence_regs(P); fence_regs(W);
#pragma unroll
            for (int j = 0; j < 8; j++) {
                m[j] = pack2(P[4 * j] * W[4 * j], P[4 * j + 1] * W[4 * j + 1]);
                m[8 + j] = pack2(P[4 * j + 2] * W[4 * j + 2], P[4 * j + 3] * W[4 * j + 3]);
            }
#pragma unroll
            for (int i = NPRE; i < 12; i++) lds128((vrow ^ (64 * (i & 1))) + 2048 + 1024 * (i >> 2) + 3072 * ((i >> 1) & 1), v[1 + (i >> 2)] + 4 * (i & 3));
            sources(c1);
            const uint32_t node = lds32(sb + SN_OFF + 4 + (((c0 >> 16) | g32) >> 2));
            const uint32_t c2 = lds32(ctl + 128);
            __syncwarp();
            load_v(IntC<1>{});
#pragma unroll
            for (int k = 1; k < 4; k++)
#pragma unroll
                for (int j = 0; j < 8; j++) acc[8 * k + j] = hfma2(m[8 + j], v[k][8 + j], hfma2(m[j], v[k][j], acc[8 * k + j]));
            uint64_t op;
            asm("{\n.reg .b32 a;\nshl.b32 a, %1, 9;\nlop3.b32 a, a, %2, 48, 0xF8;\nmad.wide.u32 %0, a, 1, %3;\n}\n" : "=l"(op) : "r"(node), "r"(l7), "l"(p.out));
            const bool close = (c0 & ST_CLOSE) && node < NODE_SPLIT;
#pragma unroll
            for (int k = 0; k < 4; k++) stg2_if(op + 128 * k, acc + 8 * k, close);
            if (__builtin_expect(__any_sync(0xffffffffu, (c0 & ST_CLOSE) && (int)node >= (int)NODE_SPLIT), 0)) {
                mbar_wait(sb + BAR_OFF + 16 + 8 * FLIGHT, 0);
                if ((int)node >= (int)NODE_SPLIT) {
#pragma unroll
                    for (int k = 0; k < 8; k++)
                        asm volatile("red.global.add.noftz.v4.bf16x2 [%0], {%1,%2,%3,%4};" ::"l"(op + 64 * k), "r"(acc[4 * k]), "r"(acc[4 * k + 1]), "r"(acc[4 * k + 2]), "r"(acc[4 * k + 3]) : "memory");
                }
                __syncwarp();
            }
            ctl += 64;
            c0 = c1;
            c1 = control(c2, ctl + 64);
        }
        asm volatile("cp.async.wait_all;" ::: "memory");
        TRW(ctl);
        TSX(11, 0); TSX(12, 128); TSX(13, 256);
    } else {
        asm volatile("setmaxnreg.dec.sync.aligned.u32 %0;" ::"n"(REG_H));
        const int lane = fresh_lane();
        const uint32_t chunk = sb + (lane & 8 ? (lane & 4 ? SN_OFF : SD_OFF) + (lane & 3) * 16 : SREC_OFF + (lane & 7) * 16), pitch = lane & 8 ? 64 : 128;
        if (warp == 12) {
#pragma unroll 1
            for (int i = 0; i < (int)misc[2]; i++) {
                const uint32_t n = reinterpret_cast<const uint32_t*>(smem + SCNT_OFF)[i] * 32 + lane;
                reinterpret_cast<uint4*>(p.out)[n] = reinterpret_cast<const uint4*>(p.sv)[n];
            }
#pragma unroll 1
            for (int i = lane >> 4; i < give; i += 2) {
                uint32_t x[4];
                lds128(chunk + (ng - 1 - i) * pitch, x);
                p.g->pool[(b * GIVE + i) * 16 + (lane & 15)] = make_uint4(x[0], x[1], x[2], x[3]);
            }
            __threadfence();
            __syncwarp();
            if (lane == 0) {
                asm volatile("st.relaxed.gpu.global.u32 [%0], %1;" ::"l"(p.g->ready + b), "r"(~epoch) : "memory");
                mbar_arrive(sb + BAR_OFF + 16 + 8 * FLIGHT);
            }
        }
        if (warp == 15) {
            int k = lane < 4 * NWG ? lane : 255, next = 4 * NWG, j = 0, mine = ng - give, end = -1, take = 0;
            uint32_t busy, at = sb + CTL_OFF + 4 * lane, from = 0;
#pragma unroll 1
            do {
                if (next > mine && end < 0) {
                    end = mine = ng;
                    const int peer = b % 5 + 5 * lane;
                    uint32_t x = 255;
                    int it = 0;
                    if (peer < G) {
#pragma unroll 1
                        do {
                            asm volatile("ld.relaxed.gpu.global.u32 %0, [%1];" : "=r"(x) : "l"(p.g->rows + peer) : "memory");
                            if (++it > (1 << 22)) __trap();
                        } while ((x >> 16) != (~epoch & 0xFFFFu));
                    }
                    const int r = x & 255, n = __popc(__ballot_sync(0xffffffffu, r != 255));
                    const int level = min(((__reduce_add_sync(0xffffffffu, r != 255 ? r : 0) + n - 1) / n + 3) & ~3, MAXROW);
                    const uint32_t ed = r > level ? min(r - level, (int)(x >> 8) & 255) : min(level - r, ROOM) << 16;
                    uint32_t z = ed;
#pragma unroll
                    for (int o = 1; o < 32; o <<= 1) {
                        const uint32_t y = __shfl_up_sync(0xffffffffu, z, o);
                        if (lane >= o) z += y;
                    }
                    const uint32_t all = __shfl_sync(0xffffffffu, z, 31), moved = min(all & 0xFFFFu, all >> 16);
                    const uint32_t me = __shfl_sync(0xffffffffu, ed, b / 5), mz = __shfl_sync(0xffffffffu, z, b / 5) - me;
                    end = mine = ng - (min((mz + me) & 0xFFFFu, moved) - min(mz & 0xFFFFu, moved));
#pragma unroll 1
                    for (uint32_t u = mz >> 16; u < min((mz + me) >> 16, moved); u++, take++) {
                        const int f = __popc(__ballot_sync(0xffffffffu, (z & 0xFFFFu) <= u));
                        const uint32_t q = u - (__shfl_sync(0xffffffffu, z - ed, f) & 0xFFFFu);
                        if (lane == take) from = (b % 5 + 5 * f) << 8 | q;
                    }
                }
                if (next > mine && take) {
                    if (lane < take) {
                        uint32_t x;
                        int it = 0;
#pragma unroll 1
                        do {
                            asm volatile("ld.acquire.gpu.global.u32 %0, [%1];" : "=r"(x) : "l"(p.g->ready + (from >> 8)) : "memory");
                            if (++it > (1 << 22)) __trap();
                        } while (x != ~epoch);
                    }
                    __syncwarp();
#pragma unroll 1
                    for (end += take; take--;) {
                        const uint32_t f = __shfl_sync(0xffffffffu, from, take);
                        if (lane < 16)
                            asm volatile("cp.async.cg.shared.global [%0], [%1], 16;" ::"r"(chunk + (MAXROW - 1 - take) * pitch),
                                         "l"(p.g->pool + ((f >> 8) * GIVE + (f & 255)) * 16 + lane) : "memory");
                    }
                    take = 0;
                    asm volatile("cp.async.wait_all;" ::: "memory");
                    __threadfence_block();
                    __syncwarp();
                }
                const bool has = k < (end < 0 ? mine : end);
                const uint32_t i = k < mine ? k : MAXROW - 1 + mine - k, x = __shfl_sync(0xffffffffu, pk, j);
                const bool close = has && i >= (x >> 24);
                busy = __ballot_sync(0xffffffffu, has);
                const uint32_t m = __ballot_sync(0xffffffffu, close);
                uint32_t c = has ? ((x & 0xFF00) + i * 0x1000100) | (j ? 0u : ST_START) | (close ? ST_CLOSE : 0u) : MAXROW * 256;
                if (!(busy >> (lane & 12))) c |= 0x80000000u;
                c |= busy >> ((lane & 12) + 4) ? (lane & 12) * 4 + 32 : 16;
                sts32_if(at, c, lane < 16 || !busy);
                j = close ? 0 : j + 1;
                k = close ? next + __popc(m & ((1u << lane) - 1)) : k;
                next += __popc(m);
                at += 64;
            } while (busy);
        }
        __nanosleep(ZDELAY);
        const int zend = misc[32] + misc[64];
#pragma unroll 1
        for (int r = 8 * ng + (warp & 3) * 4; r < zend; r += 16) {
            uint4 v[4];
            uint32_t n[4];
#pragma unroll
            for (int i = 0; i < 4; i++) {
                n[i] = reinterpret_cast<const uint32_t*>(smem + SN_OFF)[min(r + i, zend - 1) * 2 + 1] * 32 + lane;
                v[i] = __ldcg(reinterpret_cast<const uint4*>(p.sv) + n[i]);
            }
#pragma unroll
            for (int i = 0; i < 4; i++)
                if (r + i < zend) __stcs(reinterpret_cast<uint4*>(p.out) + n[i], v[i]);
        }
        static_assert(FLIGHT <= 4, "drain");
        drain(warp & 3);
        asm volatile("cp.async.wait_all;" ::: "memory");
        TSX(14, 384);
    }
}

}

extern "C" void kernel_launch(void* const* d_in, const int* in_sizes, int n_in, void* d_out, int out_size) {
    static int s_G = 0;
    static void* s_scratch = nullptr;
    const int N = in_sizes[0] / 256, E = in_sizes[2];
    if (s_G == 0) {
        cudaFuncSetAttribute(painn_kernel<0, 0, 0>, cudaFuncAttributeMaxDynamicSharedMemorySize, SMEM_BYTES);
        cudaFuncSetAttribute(painn_kernel<50000, 800000, 132>, cudaFuncAttributeMaxDynamicSharedMemorySize, SMEM_BYTES);
        int dev = 0, sms = 0, occ = 0;
        cudaGetDevice(&dev);
        cudaDeviceGetAttribute(&sms, cudaDevAttrMultiProcessorCount, dev);
        cudaOccupancyMaxActiveBlocksPerMultiprocessor(&occ, painn_kernel<0, 0, 0>, THREADS, SMEM_BYTES);
        cudaGetSymbolAddress(&s_scratch, g_scratch);
        s_G = occ >= 1 ? (sms < MAXG ? sms : MAXG) : 0;
    }
    if (s_G == 0 || N > TABLE_MAXN || N > s_G * MAXNPC || (s_G - 1) * ((N + s_G - 1) / s_G) >= N || E > MAXE || E < 4 * MAXG * MAXG) return;
    Params p;
    p.g = (Scratch*)s_scratch;
    p.sv = (const __nv_bfloat16*)d_in[0];
    p.pos = (const __nv_bfloat16*)d_in[1];
    p.src = (const int*)d_in[2];
    p.dst = (const int*)d_in[3];
    p.freqs = (const __nv_bfloat16*)d_in[4];
    p.w1 = (const __nv_bfloat16*)d_in[5];
    p.w2 = (const __nv_bfloat16*)d_in[6];
    p.wr = (const __nv_bfloat16*)d_in[7];
    p.out = (__nv_bfloat16*)d_out;
    p.desc0 = (uint64_t)(SB >> 4) | ((uint64_t)1 << 16) | ((uint64_t)64 << 32) | ((uint64_t)1 << 62);
    p.N = N; p.E = E; p.G = s_G;
    p.NPC = (N + s_G - 1) / s_G;
    p.magic = (uint32_t)(((1ull << 32) + p.NPC - 1) / p.NPC);
    p.gpc = ((E >> 2) + s_G - 1) / s_G;
    p.odd_edges = (E & 3) != 0 || p.gpc > 3 * THREADS;
    if (N == 50000 && E == 800000 && s_G == 132) painn_kernel<50000, 800000, 132><<<s_G, THREADS, SMEM_BYTES, cudaStreamPerThread>>>(p);
    else painn_kernel<0, 0, 0><<<s_G, THREADS, SMEM_BYTES, cudaStreamPerThread>>>(p);
}
```

```cpp
#include <cuda_runtime.h>
#include <cuda_bf16.h>
#include <stdint.h>

namespace {

constexpr int NWG = 3;
constexpr int REG_C = 160, REG_H = 32;
#define SPL_N 10
#define ROOM 3
#define TOUCH2 4
#define FLIGHT 4
#define EXITB 0
#define SFIRST 1
#define LEARLY 0
#define BRANCHY 0
#define SLATE 1
#define FPOS 2
#define WPOS 1
#define BALANCE 1
#define ZDELAY 0
constexpr int SPL = SPL_N;
#define GIVE_N 10
constexpr int GIVE = GIVE_N;
#define PDELAY_N 150
constexpr int PDELAY = PDELAY_N;
constexpr int THREADS = 512;
constexpr int MAXG = 136;
constexpr int MAXROW = 96;
constexpr int TMAX = MAXROW / 12 + 18;
constexpr int MAXNPC = 480;
constexpr int MAXE = 1 << 20;

constexpr int W1_OFF = 0;
constexpr int W2_OFF = 8192;
constexpr int WR_OFF = 32768;
constexpr int RING_OFF = 38912;
constexpr int SREC_OFF = RING_OFF + 4 * NWG * 12288;
constexpr int SD_OFF = SREC_OFF + (MAXROW + 1) * 128 + 16;
constexpr int SN_OFF = SD_OFF + (MAXROW + 1) * 64 + 16;
constexpr int CTL_OFF = SN_OFF + (MAXROW + 1) * 64 + 16;
constexpr int TABLE_MAXN = 50176;
constexpr int STAGE_OFF = TABLE_MAXN * 4;
constexpr int SCNT_OFF = STAGE_OFF + MAXG * 128;
constexpr int GPOS_OFF = RING_OFF;
constexpr int PACK_OFF = GPOS_OFF + 4 * 8192;
constexpr int NCNT_OFF = SCNT_OFF + 768;
constexpr int OPOS_OFF = NCNT_OFF + 2048;
constexpr int BAR_OFF = OPOS_OFF + 4096;
constexpr int MISC_OFF = BAR_OFF + 128;
constexpr int FREQ_OFF = MISC_OFF + 512;
constexpr int DUMMY_OFF = (FREQ_OFF + 128 + 127) / 128 * 128;
constexpr int SMEM_BYTES = DUMMY_OFF + 4096;
static_assert(CTL_OFF + 64 * TMAX <= SCNT_OFF && CTL_OFF + 64 * TMAX - SREC_OFF <= 64 * THREADS && 4 * (MAXG + 32) <= 768, "smem map");
static_assert(SMEM_BYTES <= 232448 && BAR_OFF % 8 == 0 && RING_OFF % 128 == 0 && SREC_OFF % 128 == 0 && GPOS_OFF % 128 == 0 && PACK_OFF + 15 * 512 <= SREC_OFF && (MAXG + 14) / 15 <= 12, "smem map");

constexpr uint32_t PAY_INVALID = 0x3FFFFFFu;
constexpr uint32_t PAY_MARK = 0x3FFFDFFu;
constexpr uint32_t NODE_SPLIT = 0x40000000u;
constexpr uint32_t ST_START = 1, ST_CLOSE = 2;
constexpr float QINVP = 9.0f / 510.0f;
constexpr uint32_t QTHRESH = 2209;
#define QSURE_N 1980
constexpr uint32_t QSURE = QSURE_N;

struct Scratch {
    unsigned sync[32];
    uint4 table[TABLE_MAXN / 4];
    uint4 wimg[RING_OFF / 16];
    uint2 pos8[TABLE_MAXN];
    uint4 xbuf[MAXG * MAXG * 8 + 3 * THREADS];
    uint4 pool[MAXG * GIVE * 16];
    unsigned rows[MAXG];
    unsigned ready[MAXG];
    int ovfcnt[MAXG];
    int2 ovf[MAXE + 8 * MAXG + 8];
};
__device__ __align__(128) Scratch g_scratch;

struct Params {
    const __nv_bfloat16* pos;
    Scratch* g;
    const int* src;
    const int* dst;
    int N, NPC, E, gpc;
    const __nv_bfloat16* w2;
    const __nv_bfloat16* wr;
    const __nv_bfloat16* w1;
    const __nv_bfloat16* freqs;
    const __nv_bfloat16* sv;
    __nv_bfloat16* out;
    uint64_t desc0;
    int G;
    uint32_t magic;
    int odd_edges;
};
constexpr uint32_t SB = 1024;

#define TSX(i, thr)
#define TR(k, thr, t)
#define TS0(i) TSX(i, 0)
#define STOP(k)
#define TRW(ctl)

__device__ __forceinline__ uint32_t smem_u32(const void* p) { return (uint32_t)__cvta_generic_to_shared(p); }
__device__ __forceinline__ void mbar_init(uint32_t bar, uint32_t cnt) {
    asm volatile("mbarrier.init.shared::cta.b64 [%0], %1;" ::"r"(bar), "r"(cnt) : "memory");
}
__device__ __forceinline__ void mbar_arrive(uint32_t bar) {
    asm volatile("mbarrier.arrive.shared::cta.b64 _, [%0];" ::"r"(bar) : "memory");
}
__device__ __forceinline__ void mbar_expect_tx(uint32_t bar, uint32_t bytes) {
    asm volatile("mbarrier.arrive.expect_tx.shared::cta.b64 _, [%0], %1;" ::"r"(bar), "r"(bytes) : "memory");
}
__device__ __forceinline__ void mbar_wait(uint32_t bar, uint32_t parity) {
    uint32_t ok;
    int it = 0;
    do {
        asm volatile(
            "{\n.reg .pred p;\n"
            "mbarrier.try_wait.parity.shared::cta.b64 p, [%1], %2, 2000;\n"
            "selp.u32 %0, 1, 0, p;\n}\n"
            : "=r"(ok) : "r"(bar), "r"(parity) : "memory");
        if (++it > (1 << 20)) __trap();
    } while (!ok);
}
__device__ __forceinline__ uint32_t mbar_test(uint32_t bar, uint32_t parity) {
    uint32_t ok;
    asm volatile("{\n.reg .pred p;\nmbarrier.test_wait.parity.shared::cta.b64 p, [%1], %2;\nselp.u32 %0, 1, 0, p;\n}\n"
                 : "=r"(ok) : "r"(bar), "r"(parity) : "memory");
    return ok;
}
__device__ __forceinline__ uint32_t pin(uint32_t x) {
    uint32_t r;
    asm volatile("shfl.sync.bfly.b32 %0, %1, 0, 31, -1;" : "=r"(r) : "r"(x));
    return r;
}
__device__ __forceinline__ void bulk_g2s(uint32_t dst, const void* src, uint32_t bytes, uint32_t bar) {
    asm volatile("cp.async.bulk.shared::cluster.global.mbarrier::complete_tx::bytes [%0], [%1], %2, [%3];"
                 ::"r"(dst), "l"(src), "r"(bytes), "r"(bar) : "memory");
}
__device__ __forceinline__ void ldsm4(uint32_t addr, uint32_t* r) {
    asm volatile("ldmatrix.sync.aligned.m8n8.x4.shared.b16 {%0,%1,%2,%3}, [%4];"
                 : "=r"(r[0]), "=r"(r[1]), "=r"(r[2]), "=r"(r[3]) : "r"(addr) : "memory");
}
__device__ __forceinline__ uint32_t pack2(float lo, float hi) {
    uint32_t r;
    asm("cvt.rn.bf16x2.f32 %0, %1, %2;" : "=r"(r) : "f"(hi), "f"(lo));
    return r;
}
__device__ __forceinline__ float bf_lo(uint32_t w) { return __uint_as_float(w << 16); }
__device__ __forceinline__ float bf_hi(uint32_t w) { return __uint_as_float(w & 0xFFFF0000u); }
__device__ __forceinline__ float rbf16(float x) { return __uint_as_float(pack2(0.f, x)); }
__device__ __forceinline__ uint32_t hmul2(uint32_t a, uint32_t b) {
    uint32_t r;
    asm("mul.rn.bf16x2 %0, %1, %2;" : "=r"(r) : "r"(a), "r"(b));
    return r;
}
__device__ __forceinline__ uint32_t hfma2(uint32_t a, uint32_t b, uint32_t c) {
    uint32_t r;
    asm("fma.rn.bf16x2 %0, %1, %2, %3;" : "=r"(r) : "r"(a), "r"(b), "r"(c));
    return r;
}
__device__ __forceinline__ uint32_t hfma2_lo(uint32_t a, uint32_t b, uint32_t c) {
    uint32_t r;
    asm("{\n.reg .b16 l, h;\n.reg .b32 t;\nmov.b32 {l, h}, %2;\nmov.b32 t, {l, l};\nfma.rn.bf16x2 %0, %1, t, %3;\n}\n" : "=r"(r) : "r"(a), "r"(b), "r"(c));
    return r;
}
__device__ __forceinline__ uint32_t hfma2_hi(uint32_t a, uint32_t b, uint32_t c) {
    uint32_t r;
    asm("{\n.reg .b16 l, h;\n.reg .b32 t;\nmov.b32 {l, h}, %2;\nmov.b32 t, {h, h};\nfma.rn.bf16x2 %0, %1, t, %3;\n}\n" : "=r"(r) : "r"(a), "r"(b), "r"(c));
    return r;
}
__device__ __forceinline__ uint32_t hmul2_hi(uint32_t a, uint32_t b) {
    uint32_t r;
    asm("{\n.reg .b16 l, h;\n.reg .b32 t;\nmov.b32 {l, h}, %2;\nmov.b32 t, {h, h};\nmul.rn.bf16x2 %0, %1, t;\n}\n" : "=r"(r) : "r"(a), "r"(b));
    return r;
}
__device__ __forceinline__ uint32_t hadd2(uint32_t a, uint32_t b) {
    uint32_t r;
    asm("add.rn.bf16x2 %0, %1, %2;" : "=r"(r) : "r"(a), "r"(b));
    return r;
}
__device__ __forceinline__ uint32_t hsub2(uint32_t a, uint32_t b) {
    uint32_t r;
    asm("sub.rn.bf16x2 %0, %1, %2;" : "=r"(r) : "r"(a), "r"(b));
    return r;
}
__device__ __forceinline__ void cp_async_arrive(uint32_t bar) {
    asm volatile("cp.async.mbarrier.arrive.noinc.shared::cta.b64 [%0];" ::"r"(bar) : "memory");
}
__device__ __forceinline__ float tanh_fast(float x) {
    float r;
    asm("tanh.approx.f32 %0, %1;" : "=f"(r) : "f"(x));
    return r;
}
__device__ __forceinline__ void wg_fence() { asm volatile("wgmma.fence.sync.aligned;" ::: "memory"); }
__device__ __forceinline__ void wg_commit() { asm volatile("wgmma.commit_group.sync.aligned;" ::: "memory"); }
template <int N>
__device__ __forceinline__ void wg_wait() { asm volatile("wgmma.wait_group.sync.aligned %0;" ::"n"(N) : "memory"); }

#define WG_REGS "{%0,%1,%2,%3,%4,%5,%6,%7,%8,%9,%10,%11,%12,%13,%14,%15,%16,%17,%18,%19,%20,%21,%22,%23,%24,%25,%26,%27,%28,%29,%30,%31}"
#define WG_OPS(c) c(d[0]), c(d[1]), c(d[2]), c(d[3]), c(d[4]), c(d[5]), c(d[6]), c(d[7]), c(d[8]), c(d[9]), c(d[10]), \
    c(d[11]), c(d[12]), c(d[13]), c(d[14]), c(d[15]), c(d[16]), c(d[17]), c(d[18]), c(d[19]), c(d[20]), c(d[21]),     \
    c(d[22]), c(d[23]), c(d[24]), c(d[25]), c(d[26]), c(d[27]), c(d[28]), c(d[29]), c(d[30]), c(d[31])
__device__ __forceinline__ void wgmma_first(float* d, const uint32_t* a, uint64_t desc) {
    asm volatile("wgmma.mma_async.sync.aligned.m64n64k16.f32.bf16.bf16 " WG_REGS ", {%32,%33,%34,%35}, %36, 0, 1, 1, 1;"
                 : WG_OPS("+f") : "r"(a[0]), "r"(a[1]), "r"(a[2]), "r"(a[3]), "l"(desc));
}
__device__ __forceinline__ void wgmma_acc(float* d, const uint32_t* a, uint64_t desc) {
    asm volatile("wgmma.mma_async.sync.aligned.m64n64k16.f32.bf16.bf16 " WG_REGS ", {%32,%33,%34,%35}, %36, 1, 1, 1, 1;"
                 : WG_OPS("+f") : "r"(a[0]), "r"(a[1]), "r"(a[2]), "r"(a[3]), "l"(desc));
}
__device__ __forceinline__ void wgmma_k64(float* d, const uint32_t* a, uint64_t desc) {
    wgmma_first(d, a, desc);
    wgmma_acc(d, a + 4, desc + 128);
    wgmma_acc(d, a + 8, desc + 256);
    wgmma_acc(d, a + 12, desc + 384);
}
__device__ __forceinline__ void fence_regs(float* d) { asm volatile("" : WG_OPS("+f")::"memory"); }
__device__ __forceinline__ uint32_t qaxis(float x) {
    const float u = fmaf(x, QINVP, 0.25f);
    const float f = u - ((u + 12582912.f) - 12582912.f);
    return __float_as_uint(fmaf(fabsf(f), 510.f, 12582912.f));
}
__device__ __forceinline__ uint32_t qcode(float x, float y, float z, uint32_t tx) {
    return __byte_perm(__byte_perm(qaxis(x), qaxis(y), 0x3340), qaxis(z), 0x3410) ^ tx;
}
__device__ __forceinline__ bool near_test(uint32_t ca, uint32_t cb, uint32_t tag24, uint32_t& q) {
    const uint32_t D = __vabsdiffu4(ca, cb);
    q = __dp4a(D, D, 0x7FFFFFFFu - QSURE);
    return q <= 0x7FFFFFFFu - QSURE + QTHRESH || ((ca ^ tag24) | (cb ^ tag24)) >= 0x1000000u;
}
__device__ __forceinline__ bool inside(uint32_t rxy, uint32_t rz) {
    const uint32_t qxy = hmul2(rxy, rxy), qz = hmul2(rz, rz);
    return bf_lo(qxy) + bf_hi(qxy) + bf_lo(qz) <= 24.8125f;
}

__device__ __forceinline__ uint32_t lds32(uint32_t addr) {
    uint32_t r;
    asm volatile("ld.shared.u32 %0, [%1];" : "=r"(r) : "r"(addr));
    return r;
}
__device__ __forceinline__ void sts32_if(uint32_t addr, uint32_t v, bool c) {
    asm volatile("{\n.reg .pred p;\nsetp.ne.u32 p, %2, 0;\n@p st.shared.u32 [%0], %1;\n}\n" ::"r"(addr), "r"(v), "r"((uint32_t)c) : "memory");
}
__device__ __forceinline__ void stg128_if(void* ptr, uint4 v, bool c) {
    asm volatile("{\n.reg .pred p;\nsetp.ne.u32 p, %5, 0;\n@p st.relaxed.gpu.global.v4.u32 [%0], {%1,%2,%3,%4};\n}\n"
                 ::"l"(ptr), "r"(v.x), "r"(v.y), "r"(v.z), "r"(v.w), "r"((uint32_t)c) : "memory");
}
__device__ __forceinline__ void lds128(uint32_t addr, uint32_t* r) {
    asm volatile("ld.shared.v4.u32 {%0,%1,%2,%3}, [%4];" : "=r"(r[0]), "=r"(r[1]), "=r"(r[2]), "=r"(r[3]) : "r"(addr) : "memory");
}
__device__ __forceinline__ void stg2_if(uint64_t ptr, const uint32_t* r, bool c) {
    asm volatile("{\n.reg .pred p;\nsetp.ne.u32 p, %9, 0;\n@p st.global.cs.v4.u32 [%8], {%0,%1,%2,%3};\n"
                 "@p st.global.cs.v4.u32 [%8 + 64], {%4,%5,%6,%7};\n}\n"
                 ::"r"(r[0]), "r"(r[1]), "r"(r[2]), "r"(r[3]), "r"(r[4]), "r"(r[5]), "r"(r[6]), "r"(r[7]), "l"(ptr), "r"((uint32_t)c) : "memory");
}
#define GCOND "setp.ne.u32 p, n, 0xFFFF;"
template <int NP, int HI, int PAD = 1>
__device__ __forceinline__ void gather(uint32_t dst, const void* base, uint32_t c, uint32_t e) {
#define GATHER_HEAD "{\n.reg .pred p;\n.reg .b32 n;\n.reg .b64 a;\nprmt.b32 n, %2, 0, %3;\n" GCOND "\nmad.lo.u32 n, n, 512, %4;\nmad.wide.u32 a, n, 1, %1;\n"
#define GATHER_1(P) P "cp.async.cg.shared.global [%0], [a], 16;\n}\n"
#define GATHER_3(P) P "cp.async.cg.shared.global [%0], [a + 128], 16;\n" P "cp.async.cg.shared.global [%0 + 1024], [a + 256], 16;\n" \
                    P "cp.async.cg.shared.global [%0 + 2048], [a + 384], 16;\n}\n"
#define GATHER_ARGS(z) ::"r"(dst), "l"(base), "r"(e), "n"((HI ? 0x32 : 0x10) + z), "r"(c) : "memory"
    if constexpr (NP == 1 && PAD) asm volatile(GATHER_HEAD GATHER_1("@p ") GATHER_ARGS(0x4400));
    if constexpr (NP == 1 && !PAD) asm volatile(GATHER_HEAD GATHER_1("") GATHER_ARGS(0x4400));
    if constexpr (NP == 3 && PAD) asm volatile(GATHER_HEAD GATHER_3("@p ") GATHER_ARGS(0x5500));
    if constexpr (NP == 3 && !PAD) asm volatile(GATHER_HEAD GATHER_3("") GATHER_ARGS(0x4400));
    if constexpr (NP == 4)
        asm volatile(GATHER_HEAD "setp.ge.u32 p, %2, 0x40000000;\ncp.async.cg.shared.global [%0], [a], 16, p;\ncp.async.cg.shared.global [%0 + 1024], [a + 128], 16, p;\n"
                     "cp.async.cg.shared.global [%0 + 2048], [a + 256], 16, p;\ncp.async.cg.shared.global [%0 + 3072], [a + 384], 16, p;\n}\n" GATHER_ARGS(0x4400));
}
__device__ __forceinline__ void cp_commit() { asm volatile("cp.async.commit_group;" ::: "memory"); }
__device__ __forceinline__ void cp_wait1() { asm volatile("cp.async.wait_group 1;" ::: "memory"); }
__device__ __forceinline__ uint32_t hmul2_lo(uint32_t a, uint32_t b) {
    uint32_t r;
    asm("{\n.reg .b16 l, h;\n.reg .b32 t;\nmov.b32 {l, h}, %2;\nmov.b32 t, {l, l};\nmul.rn.bf16x2 %0, %1, t;\n}\n" : "=r"(r) : "r"(a), "r"(b));
    return r;
}
__device__ __forceinline__ void lds2_if(uint32_t a0, uint32_t a1, uint32_t* r, uint32_t c) {
    asm volatile("{\n.reg .pred p;\nsetp.ne.u32 p, %10, 0;\n@p ld.shared.v4.u32 {%0,%1,%2,%3}, [%8];\n@p ld.shared.v4.u32 {%4,%5,%6,%7}, [%9];\n}\n"
                 : "+r"(r[0]), "+r"(r[1]), "+r"(r[2]), "+r"(r[3]), "+r"(r[4]), "+r"(r[5]), "+r"(r[6]), "+r"(r[7])
                 : "r"(a0), "r"(a1), "r"(c) : "memory");
}
__device__ __forceinline__ int fresh_lane() {
    int l;
    asm volatile("mov.u32 %0, %%laneid;" : "=r"(l));
    return l;
}

__device__ __forceinline__ void cold_edges(unsigned char* smem, const Params& p, int lo, int hi, uint32_t tag) {
#pragma unroll 1
    for (int e = lo + threadIdx.x; e < hi; e += THREADS) {
        const int s = p.src[e], d = p.dst[e];
        uint32_t q;
        if (near_test(reinterpret_cast<const uint32_t*>(smem)[s], reinterpret_cast<const uint32_t*>(smem)[d], tag << 24, q)) {
            const uint32_t own = __umulhi((uint32_t)d, p.magic);
            const uint32_t slot4 = atomicAdd(reinterpret_cast<uint32_t*>(smem + SCNT_OFF) + own, 4u);
            uint32_t* line = reinterpret_cast<uint32_t*>(smem + STAGE_OFF) + own * 32;
            if (slot4 < 124) {
                line[slot4 >> 2] = ((uint32_t)s << 15) + ((uint32_t)(d - own * p.NPC) << 6) + tag + (q & 0x80000000u);
            } else {
                uint32_t o = atomicAdd(reinterpret_cast<uint32_t*>(smem + MISC_OFF) + 16, 1u);
                p.g->ovf[(size_t)blockIdx.x * (4 * p.gpc + 4) + o] = make_int2(s, d);
                line[31] = (PAY_MARK << 6) | tag;
            }
        }
    }
}
__device__ __forceinline__ void cold_filter(unsigned char* smem, const Params& p, int e0, int e1, uint32_t tag, int redo) {
    if (redo) {
        if (threadIdx.x < MAXG) reinterpret_cast<uint32_t*>(smem + SCNT_OFF)[threadIdx.x] = 0;
        __syncthreads();
    }
    cold_edges(smem, p, redo ? 4 * e0 : 4 * (e0 + 3 * THREADS), 4 * e1, tag);
    if (blockIdx.x == 0) cold_edges(smem, p, p.E & ~3, p.E, tag);
    __syncthreads();
    if (threadIdx.x == 0) p.g->ovfcnt[blockIdx.x] = reinterpret_cast<uint32_t*>(smem + MISC_OFF)[16];
    __threadfence();
    __syncthreads();
}
__device__ __forceinline__ uint3 geometry(uint32_t rxy, uint32_t rz) {
    const uint32_t qxy = hmul2(rxy, rxy), qz = hmul2(rz, rz);
    float d, id;
    asm("sqrt.approx.ftz.f32 %0, %1;" : "=f"(d) : "f"(rbf16(rbf16(bf_lo(qxy) + bf_hi(qxy) + bf_lo(qz)) + 1e-8f)));
    d = rbf16(d);
    asm("rcp.approx.ftz.f32 %0, %1;" : "=f"(id) : "f"(d));
    const float cs = rbf16(__cosf(rbf16(rbf16(3.14159265358979f * d) * 0.2f)));
    const uint32_t zs = pack2(bf_lo(rz) * id, 0.5f * rbf16(cs + 1.0f) * id);
    return d < 5.0f ? make_uint3(pack2(bf_lo(rxy) * id, bf_hi(rxy) * id), zs, __byte_perm(__float_as_uint(d), zs, 0x7632)) : make_uint3(0, 0, 0);
}
__device__ __forceinline__ void cold_messages(unsigned char* smem, const Params& p, int nn) {
    const int nbase = blockIdx.x * p.NPC, lane = threadIdx.x & 31;
    const uint32_t* box = reinterpret_cast<const uint32_t*>(p.g->xbuf) + blockIdx.x * p.G * 32;
    uint32_t* w = reinterpret_cast<uint32_t*>(smem + RING_OFF);
#pragma unroll 1
    for (int i = threadIdx.x; i < 9728; i += THREADS)
        w[i] = i < 2048 ? reinterpret_cast<const uint32_t*>(p.w1)[i] : i < 8192 ? reinterpret_cast<const uint32_t*>(p.w2)[i - 2048] : reinterpret_cast<const uint32_t*>(p.wr)[i - 8192];
#pragma unroll 1
    for (int i = threadIdx.x; i < nn * 32; i += THREADS) reinterpret_cast<uint4*>(p.out)[nbase * 32 + i] = reinterpret_cast<const uint4*>(p.sv)[nbase * 32 + i];
    __threadfence();
    __syncthreads();
    const float freq = __bfloat162float(p.freqs[lane & 15]);
#pragma unroll 1
    for (int m = -1; m < p.G; m++) {
        const int cnt = m < 0 ? p.G * 32 : (__ldcg(box + m * 32 + 31) >> 6) == PAY_MARK ? __ldcg(&p.g->ovfcnt[m]) : 0;
#pragma unroll 1
        for (int i = threadIdx.x; i - lane < cnt; i += THREADS) {
            int2 e = make_int2(0, -1);
            if (i < cnt) {
                if (m < 0) {
                    const uint32_t x = __ldcg(box + i);
                    e = make_int2((x >> 15) & 0xFFFFu, nbase + ((x >> 6) & 511u));
                } else {
                    e = __ldcg(p.g->ovf + (size_t)m * (4 * p.gpc + 4) + i);
                }
            }
            bool in = (uint32_t)(e.y - nbase) < (uint32_t)nn;
            uint3 geo = make_uint3(0, 0, 0);
            if (in) {
                const uint2 ps = __ldcg(p.g->pos8 + e.x), pd = __ldcg(p.g->pos8 + e.y);
                const uint32_t rxy = hsub2(ps.x, pd.x), rz = hsub2(ps.y, pd.y);
                in = inside(rxy, rz);
                geo = geometry(rxy, rz);
            }
#pragma unroll 1
            for (uint32_t todo = __ballot_sync(0xffffffffu, in); todo; todo &= todo - 1) {
                const int l = __ffs(todo) - 1;
                const uint32_t* row = reinterpret_cast<const uint32_t*>(p.sv) + (size_t)__shfl_sync(0xffffffffu, e.x, l) * 128 + lane;
                uint32_t* orow = reinterpret_cast<uint32_t*>(p.out) + (size_t)__shfl_sync(0xffffffffu, e.y, l) * 128 + lane;
                const uint32_t gx = __shfl_sync(0xffffffffu, geo.x, l), gy = __shfl_sync(0xffffffffu, geo.y, l);
                const float rb = rbf16(__sinf(rbf16(bf_lo(__shfl_sync(0xffffffffu, geo.z, l)) * freq)) * bf_hi(gy));
                uint32_t x = row[0];
                float a[12] = {0, 0, 0, 0, 0, 0, 0, 0, 0, 0, 0, 0};
#pragma unroll 2
                for (int k = 0; k < 64; k++) {
                    const uint32_t u = __shfl_sync(0xffffffffu, x, k >> 1), ww = w[k * 32 + lane];
                    const float f = k & 1 ? bf_hi(u) : bf_lo(u);
                    a[0] = fmaf(f, bf_lo(ww), a[0]); a[1] = fmaf(f, bf_hi(ww), a[1]);
                }
                x = pack2(0.5f * fmaf(a[0], tanh_fast(0.5f * a[0]), a[0]), 0.5f * fmaf(a[1], tanh_fast(0.5f * a[1]), a[1]));
                a[0] = a[1] = 0.f;
#pragma unroll 2
                for (int k = 0; k < 64; k++) {
                    const uint32_t u = __shfl_sync(0xffffffffu, x, k >> 1);
                    const float f = k & 1 ? bf_hi(u) : bf_lo(u), r = __shfl_sync(0xffffffffu, rb, k & 15);
#pragma unroll
                    for (int c = 0; c < 3; c++) {
                        const uint32_t ww = w[2048 + k * 96 + c * 32 + lane], wr = k < 16 ? w[8192 + k * 96 + c * 32 + lane] : 0u;
                        a[2 * c] = fmaf(f, bf_lo(ww), a[2 * c]); a[2 * c + 1] = fmaf(f, bf_hi(ww), a[2 * c + 1]);
                        a[6 + 2 * c] = fmaf(r, bf_lo(wr), a[6 + 2 * c]); a[7 + 2 * c] = fmaf(r, bf_hi(wr), a[7 + 2 * c]);
                    }
                }
                const uint32_t mv = pack2(a[2] * a[8], a[3] * a[9]), mr = pack2(a[4] * a[10], a[5] * a[11]);
                const uint32_t o[4] = {pack2(a[0] * a[6], a[1] * a[7]), hfma2_lo(mr, gx, hmul2(mv, row[32])), hfma2_hi(mr, gx, hmul2(mv, row[64])),
                                       hfma2_lo(mr, gy, hmul2(mv, row[96]))};
#pragma unroll
                for (int c = 0; c < 4; c++) asm volatile("red.global.add.noftz.bf16x2 [%0], %1;" ::"l"(orow + 32 * c), "r"(o[c]) : "memory");
            }
        }
    }
}

#define FORD 2
#define NPRE 5
#define SPLIT(k) asm volatile("{\n.reg .pred p;\nsetp.eq.u32 p, %0, %1;\n@p trap;\n}" ::"r"(c0), "n"(0x70000 + k) : "memory")
#define PIN8(a) asm volatile("" : "+r"((a)[0]), "+r"((a)[1]), "+r"((a)[2]), "+r"((a)[3]), "+r"((a)[4]), "+r"((a)[5]), "+r"((a)[6]), "+r"((a)[7]))
#define RINGA 2
#define RINGB 3
#define RING(k) do { if (RINGA == k) asm volatile("bar.sync %0, 256;" ::"r"(1 + (warp >> 2)) : "memory"); \
                     if (RINGB == k) asm volatile("bar.arrive %0, 256;" ::"r"((c0 >> 4) & 3) : "memory"); } while (0)
template <int V> struct IntC { static constexpr int value = V; };

template <int CN, int CE, int CG>
__global__ void __launch_bounds__(THREADS, 1) painn_kernel(const __grid_constant__ Params p) {
    extern __shared__ __align__(1024) unsigned char smem_dyn[];
    unsigned char* const smem = static_cast<unsigned char*>(__cvta_shared_to_generic(SB));
    constexpr uint32_t sb = SB;
    const int tid = threadIdx.x, lane = tid & 31;
    const int warp = __shfl_sync(0xffffffffu, tid >> 5, 0);
    constexpr int CNPC = CG ? (CN + CG - 1) / CG : 1, CGPC = CG ? (CE / 4 + CG - 1) / CG : 1;
    const int b = blockIdx.x, G = CG ? CG : p.G, NPC = CG ? CNPC : p.NPC, N = CG ? CN : p.N, gpc = CG ? CGPC : p.gpc;
    const uint32_t magic = CG ? (uint32_t)(((1ull << 32) + CNPC - 1) / CNPC) : p.magic;
    const bool odd_edges = CG ? (CE & 3) != 0 || CGPC > 3 * THREADS : p.odd_edges;
    const int nbase = b * NPC, nn = min(NPC, N - nbase);
    const int eg0 = b * gpc, eg1 = min((CG ? CE : p.E) >> 2, eg0 + gpc);

    uint4* stage4 = reinterpret_cast<uint4*>(smem + STAGE_OFF);
    uint32_t* ncnt = reinterpret_cast<uint32_t*>(smem + NCNT_OFF);
    uint32_t* misc = reinterpret_cast<uint32_t*>(smem + MISC_OFF);
    const uint32_t bar_tab = sb + BAR_OFF;

    TS0(0);
    int4 es[3], ed[3];
    auto load_edges = [&](int i) {
        const int g = min(eg0 + tid + i * THREADS, eg1 - 1);
        asm volatile("ld.global.cs.v4.u32 {%0,%1,%2,%3}, [%8];\nld.global.cs.v4.u32 {%4,%5,%6,%7}, [%9];"
                     : "=r"(es[i].x), "=r"(es[i].y), "=r"(es[i].z), "=r"(es[i].w), "=r"(ed[i].x), "=r"(ed[i].y), "=r"(ed[i].z), "=r"(ed[i].w)
                     : "l"(reinterpret_cast<const int4*>(p.src) + g), "l"(reinterpret_cast<const int4*>(p.dst) + g) : "memory");
    };
    const char* const own = reinterpret_cast<const char*>(p.sv) + (size_t)nbase * 512;
    auto touch = [&](int o) {
        if (o + lane * 256 < nn * 512)
            asm volatile("cp.async.ca.shared.global.L2::256B [%0], [%1], 4;" ::"r"(sb + DUMMY_OFF + 4 * lane), "l"(own + o + lane * 256) : "memory");
    };
    uint4* const xout = p.g->xbuf + ((tid >> 3) * G + b) * 8 + (tid & 7);
    unsigned epoch;
    const uint32_t tbytes = ((N + 3) >> 2) * 16;
    {
        uint32_t pxy, pz;
        asm volatile("ld.global.nc.u32 %0, [%3];\nld.global.nc.u32 %1, [%3 + 4];\nld.global.ca.u32 %2, [%4];"
                     : "=r"(pxy), "=r"(pz), "=r"(epoch)
                     : "l"(reinterpret_cast<const uint32_t*>(p.pos) + ((nbase + min(tid, nn - 1)) * 3 >> 1)), "l"(p.g->sync) : "memory");
        const uint32_t sh = ((nbase + tid) & 1) << 4;
        pxy = __funnelshift_r(pxy, pz, sh);
        pz >>= sh;
        if (tid < nn) {
            reinterpret_cast<uint32_t*>(p.g->table)[nbase + tid] = qcode(bf_lo(pxy), bf_hi(pxy), bf_lo(pz), ((epoch & 31u) ^ 0x6Bu) << 24);
            p.g->pos8[nbase + tid] = make_uint2(pxy, pz);
        }
        reinterpret_cast<uint2*>(smem + OPOS_OFF)[tid] = make_uint2(pxy, pz);
        if (pxy == 0xFFFFFFFFu && pz == 0xFFFFFFFFu && epoch == 0xFFFFFFFFu) asm volatile("nanosleep.u32 0;");
        load_edges(0);
    }
    __syncthreads();
    const uint32_t tag = (epoch & 31u) | 32u;
    if (tid == THREADS - 1) {
        asm volatile("red.relaxed.gpu.global.add.u32 [%0], 1;" ::"l"(p.g->sync + 1) : "memory");
        TSX(1, 511);
        mbar_init(bar_tab, 1);
        mbar_expect_tx(bar_tab, tbytes);
        const unsigned want = (epoch + 1) * G;
        unsigned c;
        int it = smem_u32(smem_dyn) == SB ? 0 : 1 << 22;
        do {
            asm volatile("ld.relaxed.gpu.global.u32 %0, [%1];" : "=r"(c) : "l"(p.g->sync + 1) : "memory");
            if (++it > (1 << 22)) __trap();
        } while (c != want);
        bulk_g2s(sb, p.g->table, tbytes, bar_tab);
        TSX(2, 511);
    }
    if (warp == 14) {
#pragma unroll 1
        for (int c = b * 32 + lane; c < RING_OFF / 16; c += G * 32) {
            const int row = c >> 3, j = (c ^ row) & 7;
            uint4 v;
            if (c < 512) {
                const uint32_t half = 0x3F003F00u;
                v = __ldg(reinterpret_cast<const uint4*>(p.w1) + row * 8 + j);
                v = make_uint4(hmul2(v.x, half), hmul2(v.y, half), hmul2(v.z, half), hmul2(v.w, half));
            } else {
                const uint32_t* q = (c < 2048 ? reinterpret_cast<const uint32_t*>(p.w2) + (row & 63) * 96 + ((row >> 6) - 1) * 32
                                              : reinterpret_cast<const uint32_t*>(p.wr) + (row & 15) * 96 + ((row >> 4) - 16) * 32) + (j & 4) * 4 + (j & 3);
                v = make_uint4(__ldg(q), __ldg(q + 4), __ldg(q + 8), __ldg(q + 12));
            }
            p.g->wimg[c] = v;
        }
    }
    if (tid == 416) {
#pragma unroll
        for (int i = 0; i < FLIGHT + 2; i++) mbar_init(sb + BAR_OFF + 8 + 8 * i, i ? 1 : 15);
    }
    ncnt[tid] = 0;
    if (tid < MAXG + 32) reinterpret_cast<uint32_t*>(smem + SCNT_OFF)[tid] = tid < MAXG ? 0 : 124;
    if (tid < 128) misc[tid] = 0;
    {
        const uint32_t inv = (PAY_INVALID << 6) | tag;
        stage4[tid] = stage4[tid + THREADS] = make_uint4(inv, inv, inv, inv);
        if (tid < MAXG * 8 - 2 * THREADS) stage4[tid + 2 * THREADS] = make_uint4(inv, inv, inv, inv);
    }
    __syncthreads();
    if ((tid >> 4) == 29) asm volatile("cp.async.ca.shared.global [%0], [%1], 4;" ::"r"(sb + FREQ_OFF + 8 * (tid & 14) + 4 * (tid & 1)),
                              "l"(reinterpret_cast<const uint32_t*>(p.freqs) + ((tid & 7) >> 1) + (tid & 1) * 4) : "memory");
    load_edges(1);
    if (warp != 13 && (es[1].x & ed[1].x) == -1) asm volatile("nanosleep.u32 0;");
    load_edges(2);
    if (tid == 416) asm volatile("fence.acq_rel.gpu;" ::: "memory");
#pragma unroll
    for (int i = 0; i < 3; i++) stg128_if(xout + i * G * THREADS, make_uint4(0, 0, 0, 0), tid + i * THREADS < G * 8);
    mbar_wait(bar_tab, 0);
    TS0(3);
    if (warp == 15) {
#pragma unroll
        for (int i = 0; i < TOUCH2; i++) touch(i * 8192);
    }

#pragma unroll 1
    for (int i = 0, g = eg0 + tid; i < 3; i++, g += THREADS) {
        const int s[4] = {es[0].x, es[0].y, es[0].z, es[0].w}, d[4] = {ed[0].x, ed[0].y, ed[0].z, ed[0].w};
        uint32_t ca[4], cb[4], own[4], sl[4], q[4];
        bool c[4];
#pragma unroll
        for (int j = 0; j < 4; j++) { ca[j] = lds32(sb + 4 * s[j]); cb[j] = lds32(sb + 4 * d[j]); }
#pragma unroll
        for (int j = 0; j < 4; j++) {
            c[j] = near_test(ca[j], cb[j], tag << 24, q[j]) && g < eg1;
            own[j] = __umulhi((uint32_t)d[j], magic);
            sl[j] = atomicAdd(reinterpret_cast<uint32_t*>(smem + SCNT_OFF) + (c[j] ? own[j] : MAXG + lane), 4u);
        }
#pragma unroll
        for (int j = 0; j < 4; j++)
            sts32_if(sb + STAGE_OFF + own[j] * 128 + sl[j], own[j] * (uint32_t)(-64 * NPC) + (((uint32_t)s[j] << 15) + (((uint32_t)d[j] << 6) + ((q[j] & 0x80000000u) | tag))),
                     sl[j] < 124);
        es[0] = es[1]; es[1] = es[2];
        ed[0] = ed[1]; ed[1] = ed[2];
    }
    __syncthreads();
    {
        const int redo = __syncthreads_or(tid < MAXG && reinterpret_cast<uint32_t*>(smem + SCNT_OFF)[tid] > 124);
        if (__builtin_expect(redo || odd_edges, 0)) cold_filter(smem, p, eg0, eg1, tag, redo);
    }
    TS0(4);
    STOP(3);
#pragma unroll
    for (int i = 0; i < 3; i++) stg128_if(xout + i * G * THREADS, stage4[tid + i * THREADS], tid + i * THREADS < G * 8);
    if (warp == 14) asm volatile("cp.async.wait_all;" ::: "memory");
    __syncthreads();
#pragma unroll
    for (int i = 0; i < 4; i++) {
        const int c = tid + i * THREADS;
        const uint32_t x = c < (SN_OFF - SREC_OFF) / 16 ? 0u : 0xFFFFFFFFu;
        if (c < (CTL_OFF + 64 * TMAX - SREC_OFF) / 16) reinterpret_cast<uint4*>(smem + SREC_OFF)[c] = make_uint4(x, x, x, x);
    }
    STOP(4);
    uint32_t key[4];
    uint2 pr[4];
    const uint32_t gp = sb + GPOS_OFF + tid * 16;
    uint32_t pk = 0;
    if (warp == 15) {
        if (lane == 0) {
            int o = TOUCH2 * 8192;
#pragma unroll 1
            while (o < nn * 512 && !mbar_test(sb + BAR_OFF + 8, 0)) {
                const uint32_t bar = sb + BAR_OFF + 16 + 8 * (pk % FLIGHT);
                if (!mbar_test(bar, ~(pk / FLIGHT) & 1)) continue;
                const int n = min(4096, nn * 512 - o);
                mbar_expect_tx(bar, n);
                bulk_g2s(sb + DUMMY_OFF, own + o, n, bar);
                o += n;
                pk++;
            }
            misc[3] = pk;
        }
        __syncwarp();
        STOP(5);
    } else {
    __nanosleep(PDELAY);
    TS0(5);

    {
        const int LPW = (G + 14) / 15;
        uint32_t ew[3][4], bad[3];
        const uint4* cp = p.g->xbuf + (b * G + warp * LPW) * 8 + lane;
#pragma unroll
        for (int i = 0; i < 3; i++) {
            bad[i] = lane + 32 * i < min(LPW, G - warp * LPW) * 8;
            ew[i][0] = ew[i][1] = ew[i][2] = ew[i][3] = (PAY_INVALID << 6) | tag;
        }
        int it = 0;
#pragma unroll 1
        do {
#pragma unroll
            for (int i = 0; i < 3; i++)
                asm volatile("{\n.reg .pred p;\nsetp.ne.u32 p, %5, 0;\n@p ld.relaxed.gpu.global.v4.u32 {%0,%1,%2,%3}, [%4];\n}\n"
                             : "+r"(ew[i][0]), "+r"(ew[i][1]), "+r"(ew[i][2]), "+r"(ew[i][3]) : "l"(cp + 32 * i), "r"(bad[i]) : "memory");
#pragma unroll
            for (int i = 0; i < 3; i++) bad[i] = ((ew[i][0] ^ tag) | (ew[i][1] ^ tag) | (ew[i][2] ^ tag) | (ew[i][3] ^ tag)) & 63u;
            if (++it > (1 << 22)) __trap();
        } while (__any_sync(0xffffffffu, bad[0] | bad[1] | bad[2]));
        STOP(5);
        TSX(21, 0); TSX(22, 448);
        uint4* pack = reinterpret_cast<uint4*>(smem + PACK_OFF);
        int nch = 0;
        uint32_t at[3];
#pragma unroll
        for (int i = 0; i < 3; i++) {
            const uint32_t m = __ballot_sync(0xffffffffu, ew[i][0] < (PAY_MARK << 6));
            at[i] = nch + __popc(m & ((1u << lane) - 1));
            nch += __popc(m);
        }
        if (__builtin_expect(nch > 32, 0)) {
#pragma unroll 1
            for (int i = 0; i < 3; i++) {
                if (ew[0][0] < (PAY_MARK << 6) && at[0] >= 32) at[0] = (15 - warp) * 32 - 1 - min(atomicAdd(&misc[1], 1u), 31u);
                const uint32_t x = at[0], y = ew[0][0];
                at[0] = at[1]; at[1] = at[2]; at[2] = x;
                ew[0][0] = ew[1][0]; ew[1][0] = ew[2][0]; ew[2][0] = y;
            }
        }
#pragma unroll
        for (int i = 0; i < 3; i++) {
            asm volatile("{\n.reg .pred p;\nsetp.lt.u32 p, %1, %5;\n@p st.shared.v4.u32 [%0], {%1,%2,%3,%4};\n}\n"
                         ::"r"(sb + PACK_OFF + (warp * 32 + at[i]) * 16), "r"(ew[i][0]), "r"(ew[i][1]), "r"(ew[i][2]), "r"(ew[i][3]), "n"(PAY_MARK << 6) : "memory");
            sts32_if(sb + MISC_OFF + 4 * 17, 1, (ew[i][3] >> 6) == PAY_MARK);
        }
        bool have = lane < nch;
        if (warp == 14) {
            asm volatile("bar.sync 7, 480;" ::: "memory");
            const uint32_t extra = misc[1];
            if (nch + extra > 32) misc[18] = 1;
            have = have || lane + extra >= 32;
        } else {
            asm volatile("bar.arrive 7, 480;" ::: "memory");
        }
        __syncwarp();
        uint32_t w[4], rk[4];
        bool in[4];
        {
            const uint4 x = pack[tid];
            w[0] = have ? x.x : ~0u; w[1] = have ? x.y : ~0u; w[2] = have ? x.z : ~0u; w[3] = have ? x.w : ~0u;
        }
        auto fetch = [&](int j, bool c) {
            asm volatile("{\n.reg .pred p;\nsetp.ne.u32 p, %2, 0;\n@p cp.async.cg.shared.global [%0], [%1], 16;\n}\n"
                         ::"r"(gp + j * 8192), "l"(reinterpret_cast<const uint4*>(p.g->pos8) + ((w[j] >> 16) & 0x7FFFu)), "r"((uint32_t)c) : "memory");
        };
#pragma unroll
        for (int j = 0; j < 4; j++) fetch(j, (int)w[j] < (int)(PAY_MARK << 6));
#pragma unroll
        for (int j = 0; j < 4; j++) pr[j] = reinterpret_cast<const uint2*>(smem + OPOS_OFF)[(w[j] >> 6) & 511u];
        asm volatile("cp.async.wait_all;" ::: "memory");
        TSX(23, 0); TSX(24, 448);
        asm volatile("{\n.reg .pred p;\nsetp.eq.u32 p, %1, 0;\n@p mbarrier.arrive.shared::cta.b64 _, [%0];\n}\n" ::"r"(sb + BAR_OFF + 8), "r"(lane) : "memory");
#pragma unroll
        for (int j = 0; j < 4; j++) {
            uint2 ps;
            asm volatile("ld.shared.v2.u32 {%0,%1}, [%2];" : "=r"(ps.x), "=r"(ps.y) : "r"(gp + j * 8192 + ((w[j] >> 12) & 8)) : "memory");
            in[j] = ((int)w[j] >= 0) | (((int)w[j] < (int)(PAY_MARK << 6)) & inside(hsub2(ps.x, pr[j].x), hsub2(ps.y, pr[j].y)));
        }
#pragma unroll
        for (int j = 0; j < 4; j++) rk[j] = atomicAdd(&ncnt[in[j] ? (w[j] >> 6) & 511u : 480 + lane], 1u);
#pragma unroll
        for (int j = 0; j < 4; j++) {
            rk[j] = rk[j] < SPL ? 2 * rk[j] : min(2 * rk[j] - (2 * SPL - 1), 63u);
            atomicAdd(&misc[in[j] && !(rk[j] & 2) ? 32 + (rk[j] >> 2) : 63], 1u);
            key[j] = in[j] ? ((w[j] >> 15) & 0xFFFFu) | ((w[j] << 10) & 0x1FF0000u) | (rk[j] << 25) : 0xF8000000u;
        }
#pragma unroll
        for (int j = 0; j < 4; j++) fetch(j, (int)w[j] >= 0);
    }
    }
    __syncthreads();
    TS0(6);
    STOP(6);
    uint32_t dst = sb + RING_OFF + warp * 12288 + (lane >> 3) * 256 + (((lane & 7) ^ (lane >> 3)) << 4), l7 = (lane & 7) * 16, g32 = (lane >> 2) * 32;
    uint32_t e0, e1, n0, n1;
    auto sources = [&](uint32_t c) {
        asm volatile("{\n.reg .b32 a;\nlop3.b32 a, %4, %5, 0xFFC0, 0xA8;\nshr.u32 a, a, 2;\nld.shared.v4.u32 {%0,%1,%2,%3}, [a + %6];\n}\n"
                     : "=r"(e0), "=r"(n0), "=r"(e1), "=r"(n1) : "r"(c), "r"(g32), "n"(SB + SN_OFF));
    };
    auto load_s = [&](auto pad) {
        gather<1, 0, pad.value>(dst, p.sv, l7, e0); gather<1, 1, pad.value>(dst + 1024, p.sv, l7, e0);
        gather<1, 0, pad.value>((dst ^ 64) + 128, p.sv, l7, e1); gather<1, 1, pad.value>((dst ^ 64) + 1152, p.sv, l7, e1);
    };
    auto load_o = [&]() {
        gather<4, 0>(dst + 8192, p.sv, l7, n0); gather<4, 0>((dst ^ 64) + 8320, p.sv, l7, n1);
    };
    auto load_v = [&](auto pad) {
        gather<3, 0, pad.value>(dst + 2048, p.sv, l7, e0); gather<3, 1, pad.value>(dst + 5120, p.sv, l7, e0);
        gather<3, 0, pad.value>((dst ^ 64) + 2176, p.sv, l7, e1); gather<3, 1, pad.value>((dst ^ 64) + 5248, p.sv, l7, e1);
        cp_commit();
    };
    const int ng = (misc[32] + 7) >> 3;
    const int give = max(min(ng - max((int)(misc[33] + 7) >> 3, 4 * NWG), GIVE), 0);
    if (warp == 15) {
        const uint32_t cnt = lane < 16 ? (misc[32 + lane] + 7) >> 3 : 0u;
        uint32_t z = cnt;
#pragma unroll
        for (int o = 1; o < 16; o <<= 1) {
            const uint32_t y = __shfl_up_sync(0xffffffffu, z, o);
            if (lane >= o) z += y;
        }
        misc[96 + lane] = lane < 16 ? 64 * (z - cnt) : 64 * (MAXROW + 1);
        asm volatile("bar.arrive 5, 512;" ::: "memory");
        if (lane == 15) {
            const bool cold = cnt || z > MAXROW || misc[31 + SPL / 2] > 32 || misc[17] || misc[18];
            misc[18] = cold;
            asm volatile("st.relaxed.gpu.global.u32 [%0], %1;" ::"l"(p.g->rows + b), "r"(~epoch << 16 | (cold ? 255 : give << 8 | z)) : "memory");
        }
        pk = (z - cnt) << 8 | __shfl_down_sync(0xffffffffu, cnt, 1) << 24;
    } else {
        if (warp * 32 < nn) {
            const uint32_t c = ncnt[tid], st = tid < nn ? (min(c, (uint32_t)SPL) + 1) >> 1 : 17u;
            const uint32_t same = __match_any_sync(0xffffffffu, st), first = __ffs(same) - 1;
            uint32_t r, node = nbase + tid;
            asm volatile("atom.shared.add.u32 %0, [%1], %2;" : "=r"(r)
                         : "r"(lane == first ? sb + MISC_OFF + 4 * (64 + st) : sb + NCNT_OFF + 4 * (480 + lane)), "r"(__popc(same)) : "memory");
            r = __shfl_sync(0xffffffffu, r, first) + __popc(same & ((1u << lane) - 1)) + misc[32 + st];
            if (__builtin_expect(c > SPL, 0)) {
                const uint32_t s2 = min((c - SPL + 1) >> 1, 16u), r2 = misc[32 + s2] + atomicAdd(&misc[64 + s2], 1u), k = atomicAdd(&misc[2], 1u);
                reinterpret_cast<uint32_t*>(smem + SCNT_OFF)[k & 31] = node;
                node |= NODE_SPLIT;
                ncnt[512 + tid] = 8 * r2;
                reinterpret_cast<uint32_t*>(smem + SN_OFF)[(r2 & 511) * 2 + 1] = node;
            }
            if (tid < nn) {
                ncnt[tid] = 8 * r;
                reinterpret_cast<uint32_t*>(smem + SN_OFF)[(r & 511) * 2 + 1] = node;
            }
        }
        asm volatile("bar.sync 5, 512;" ::: "memory");
        uint32_t slot[4];
#pragma unroll
        for (int j = 0; j < 4; j++) slot[j] = min(misc[96 + (key[j] >> 27)] + ncnt[(key[j] >> 16) & 1023], 64u * (MAXROW + 1)) + ((key[j] >> 25) & 2);
#pragma unroll
        for (int j = 0; j < 4; j++) {
            *reinterpret_cast<uint16_t*>(smem + SN_OFF + slot[j]) = (uint16_t)key[j];
            slot[j] += slot[j] & 2;
        }
        asm volatile("cp.async.wait_all;" ::: "memory");
        uint2 ps[4];
#pragma unroll
        for (int j = 0; j < 4; j++)
            asm volatile("ld.shared.v2.u32 {%0,%1}, [%2];" : "=r"(ps[j].x), "=r"(ps[j].y) : "r"(gp + j * 8192 + (key[j] & 1) * 8) : "memory");
        asm volatile("bar.sync 6, 480;" ::: "memory");
        TS0(7);
        if (warp < 4 * NWG) {
            sources((warp < ng ? warp : MAXROW) << 8);
            e0 = __vminu2(e0, (N - 1) * 0x10001u);
            e1 = __vminu2(e1, (N - 1) * 0x10001u);
            load_s(IntC<0>{});
            cp_commit();
            load_o();
            cp_commit();
        }
    if (tid == THREADS - 33) {
        if (b == 0) p.g->sync[0] = epoch + 1;
        asm volatile("fence.proxy.async.global;" ::: "memory");
        mbar_expect_tx(bar_tab, RING_OFF);
        bulk_g2s(sb, p.g->wimg, RING_OFF, bar_tab);
    }
    __syncwarp();
        TSX(9, 0);
#pragma unroll 1
        for (int i = 0; i < 2; i++) {
#pragma unroll
            for (int u = 0; u < 2; u++) {
                const uint3 geo = geometry(hsub2(ps[u].x, pr[u].x), hsub2(ps[u].y, pr[u].y));
                *reinterpret_cast<uint2*>(smem + SREC_OFF + 2 * slot[u]) = make_uint2(geo.x, geo.y);
                *reinterpret_cast<uint32_t*>(smem + SD_OFF + slot[u]) = geo.z;
                ps[u] = ps[u + 2];
                pr[u] = pr[u + 2];
                slot[u] = slot[u + 2];
            }
        }
    }
    __syncthreads();
    TS0(8);
    auto drain = [&](int i) { if (i < FLIGHT) mbar_wait(sb + BAR_OFF + 16 + 8 * i, ~((misc[3] + FLIGHT - 1 - i) / FLIGHT) & 1); };
    if (__builtin_expect(misc[18], 0)) {
        drain(warp);
        asm volatile("cp.async.wait_all;" ::: "memory");
        __syncthreads();
        cold_messages(smem, p, nn);
        mbar_wait(bar_tab, 1);
        return;
    }

    if (warp < 4 * NWG) {
        asm volatile("setmaxnreg.inc.sync.aligned.u32 %0;" ::"n"(REG_C));
        const int lane = fresh_lane();
        const int g = lane >> 2, q = lane & 3;
        const uint64_t dW1 = p.desc0, dW2 = dW1 + (W2_OFF >> 4), dWR = dW1 + (WR_OFF >> 4);
        const uint32_t ring = sb + RING_OFF + warp * 12288;
        const uint32_t vrow = pin(ring + g * 128 + ((q ^ ((g & 1) << 2) ^ (g >> 1)) << 4));
        const uint32_t mrow = pin(ring + (lane & 15) * 128 + (((lane >> 4) ^ ((lane & 1) << 2) ^ ((lane & 7) >> 1)) << 4));
        dst = pin(ring + (lane >> 3) * 256 + (((lane & 7) ^ (lane >> 3)) << 4)); l7 = pin((lane & 7) * 16); g32 = pin(g * 32);
        uint32_t ctl = sb + CTL_OFF + warp * 4;
        auto control = [&](uint32_t c, uint32_t at) {
            int it = 0;
#pragma unroll 1
            while (__builtin_expect(c == 0xFFFFFFFFu, 0)) {
                asm volatile("ld.volatile.shared.u32 %0, [%1];" : "=r"(c) : "r"(at) : "memory");
                c = __reduce_or_sync(0xffffffffu, c);
                if (++it > (1 << 24)) __trap();
            }
            return c;
        };
        uint32_t c0 = control(0xFFFFFFFFu, ctl), c1 = control(0xFFFFFFFFu, ctl + 64);
        if (warp >= 8) asm volatile("bar.arrive 1, 256;" ::: "memory");
        uint32_t acc[32];
        float P[32], W[32];
#pragma unroll
        for (int i = 0; i < 32; i++) { acc[i] = 0; P[i] = W[i] = 0.f; }
        mbar_wait(bar_tab, 1);
        sources(c0);
        e0 = __vminu2(e0, (N - 1) * 0x10001u);
        e1 = __vminu2(e1, (N - 1) * 0x10001u);
        cp_wait1();
        load_v(IntC<0>{});
        uint32_t cp = 0, node = 0, a[16];
        auto finish = [&]() {
            if (cp & ST_CLOSE) {
                uint64_t op[2];
                asm("{\n.reg .b32 a;\nmad.lo.u32 a, %2, 512, %3;\nmad.wide.u32 %0, a, 1, %4;\nxor.b32 a, a, 64;\nmad.wide.u32 %1, a, 1, %4;\n}\n"
                    : "=l"(op[0]), "=l"(op[1]) : "r"(node), "r"(l7), "l"(p.out));
#pragma unroll
                for (int k = 0; k < 8; k++) {
                    uint32_t x[4];
#pragma unroll
                    for (int i = 0; i < 4; i++) x[i] = l7 & 64 ? acc[4 * (k ^ 1) + i] : acc[4 * k + i];
                    asm volatile("{\n.reg .pred p;\nsetp.lt.u32 p, %5, %6;\n@p st.global.cs.v4.u32 [%0], {%1,%2,%3,%4};\n}\n"
                                 ::"l"(op[k & 1] + 128 * (k >> 1)), "r"(x[0]), "r"(x[1]), "r"(x[2]), "r"(x[3]), "r"(node), "n"(NODE_SPLIT) : "memory");
                }
                if (__builtin_expect(__any_sync(0xffffffffu, (int)node >= (int)NODE_SPLIT), 0)) {
                    mbar_wait(sb + BAR_OFF + 16 + 8 * FLIGHT, 0);
                    if ((int)node >= (int)NODE_SPLIT) {
#pragma unroll
                        for (int k = 0; k < 8; k++)
                            asm volatile("red.global.add.noftz.v4.bf16x2 [%0], {%1,%2,%3,%4};" ::"l"((op[0] & ~64ull) + 64 * k), "r"(acc[4 * k]), "r"(acc[4 * k + 1]), "r"(acc[4 * k + 2]), "r"(acc[4 * k + 3]) : "memory");
                    }
                    __syncwarp();
                }
            }
        };
#pragma unroll 1
        while ((int)c0 >= 0) {
            uint32_t h[16], rf[4], rr[4], m[16];
            TRW(ctl);
            RING(0);
            uint32_t dd[2], f01, f23;
            asm volatile("ld.shared.v2.u32 {%0,%1}, [%2 + %3];" : "=r"(dd[0]), "=r"(dd[1]) : "r"(((c0 & 0xFF00) | g32) >> 2), "n"(SB + SD_OFF));
            asm volatile("ld.shared.v2.u32 {%0,%1}, [%2 + %3];" : "=r"(f01), "=r"(f23) : "r"(l7), "n"(SB + FREQ_OFF));
            sources(c1);
            cp_wait1();
            __syncwarp();
#pragma unroll
            for (int i = 0; i < 4; i++) ldsm4(mrow ^ (i << 5), a + 4 * i);
            wg_fence();
            wgmma_k64(P, a, dW1);
            wg_commit();
            RING(1);
            SPLIT(1);
#pragma unroll
            for (int hh = 0; hh < 2; hh++) {
                const float sc = bf_hi(dd[hh]);
                const uint32_t x01 = hmul2_lo(f01, dd[hh]), x23 = hmul2_lo(f23, dd[hh]);
                rf[hh] = pack2(__sinf(bf_lo(x01)) * sc, __sinf(bf_hi(x01)) * sc);
                rf[2 + hh] = pack2(__sinf(bf_lo(x23)) * sc, __sinf(bf_hi(x23)) * sc);
            }
            asm volatile("" : "+r"(rf[0]), "+r"(rf[1]), "+r"(rf[2]), "+r"(rf[3]));
            RING(2);
            SPLIT(2);
            wg_wait<0>();
            fence_regs(P);
#pragma unroll
            for (int i = 0; i < 16; i++)
                h[i] = pack2(fmaf(P[2 * i], tanh_fast(P[2 * i]), P[2 * i]), fmaf(P[2 * i + 1], tanh_fast(P[2 * i + 1]), P[2 * i + 1]));
            wg_fence();
            wgmma_k64(P, h, dW2 + 1024);
            wgmma_first(W, rf, dWR + 256);
            wg_commit();
            RING(3);
            SPLIT(3);
#pragma unroll
            for (int k = 0; k < 4; k++) lds2_if(vrow + 8192 + 1024 * k, (vrow ^ 64) + 8192 + 1024 * k, acc + 8 * k, c0 & ST_START);
            lds128(sb + SREC_OFF + (((c0 & 0xFF00) | g32) >> 1), rr);
            uint32_t c2 = lds32(ctl + 128);
            __syncwarp();
            load_s(IntC<1>{});
            if (c1 & ST_START) {
                load_o();
            }
            cp_commit();
            wg_wait<0>();
            fence_regs(P); fence_regs(W);
#pragma unroll
            for (int j = 0; j < 8; j++) {
                m[j] = pack2(P[4 * j] * W[4 * j], P[4 * j + 1] * W[4 * j + 1]);
                m[8 + j] = pack2(P[4 * j + 2] * W[4 * j + 2], P[4 * j + 3] * W[4 * j + 3]);
            }
            wg_fence();
            wgmma_k64(P, h, dW2);
            wgmma_first(W, rf, dWR);
            wg_commit();
            RING(4);
            SPLIT(4);
            PIN8(m); PIN8(m + 8);
            c2 = __reduce_or_sync(0xffffffffu, c2);
#pragma unroll
            for (int k = 1; k < 4; k++)
#pragma unroll
                for (int j = 0; j < 8; j++) {
                    const uint32_t x = k == 1 ? hfma2_lo(m[j], rr[0], acc[8 * k + j]) : k == 2 ? hfma2_hi(m[j], rr[0], acc[8 * k + j]) : hfma2_lo(m[j], rr[1], acc[8 * k + j]);
                    acc[8 * k + j] = k == 1 ? hfma2_lo(m[8 + j], rr[2], x) : k == 2 ? hfma2_hi(m[8 + j], rr[2], x) : hfma2_lo(m[8 + j], rr[3], x);
                }
            PIN8(acc + 8); PIN8(acc + 16); PIN8(acc + 24);
            RING(5);
            c2 = control(c2, ctl + 128);
            wg_wait<0>();
            fence_regs(P); fence_regs(W);
#pragma unroll
            for (int j = 0; j < 8; j++)
                acc[j] = hadd2(acc[j], pack2(fmaf(P[4 * j], W[4 * j], P[4 * j + 2] * W[4 * j + 2]), fmaf(P[4 * j + 1], W[4 * j + 1], P[4 * j + 3] * W[4 * j + 3])));
            wg_fence();
            wgmma_k64(P, h, dW2 + 512);
            wgmma_first(W, rf, dWR + 128);
            wg_commit();
            RING(6);
            SPLIT(6);
            cp_wait1();
            __syncwarp();
            uint32_t v[4][16];
#pragma unroll
            for (int i = 0; i < NPRE; i++) lds128((vrow ^ (64 * (i & 1))) + 2048 + 1024 * (i >> 2) + 3072 * ((i >> 1) & 1), v[1 + (i >> 2)] + 4 * (i & 3));
            wg_wait<0>();
            fence_regs(P); fence_regs(W);
#pragma unroll
            for (int j = 0; j < 8; j++) {
                m[j] = pack2(P[4 * j] * W[4 * j], P[4 * j + 1] * W[4 * j + 1]);
                m[8 + j] = pack2(P[4 * j + 2] * W[4 * j + 2], P[4 * j + 3] * W[4 * j + 3]);
            }
#pragma unroll
            for (int i = NPRE; i < 12; i++) lds128((vrow ^ (64 * (i & 1))) + 2048 + 1024 * (i >> 2) + 3072 * ((i >> 1) & 1), v[1 + (i >> 2)] + 4 * (i & 3));
            sources(c1);
            node = lds32(sb + SN_OFF + 4 + (((c0 >> 16) | g32) >> 2));
            __syncwarp();
            load_v(IntC<1>{});
#pragma unroll
            for (int k = 1; k < 4; k++)
#pragma unroll
                for (int j = 0; j < 8; j++) acc[8 * k + j] = hfma2(m[8 + j], v[k][8 + j], hfma2(m[j], v[k][j], acc[8 * k + j]));
            ctl += 64;
            cp = c0;
            c0 = c1;
            c1 = c2;
            finish();
        }
        asm volatile("cp.async.wait_all;" ::: "memory");
        TRW(ctl);
        TSX(11, 0); TSX(12, 128); TSX(13, 256);
    } else {
        asm volatile("setmaxnreg.dec.sync.aligned.u32 %0;" ::"n"(REG_H));
        const int lane = fresh_lane();
        const uint32_t chunk = sb + (lane & 8 ? (lane & 4 ? SN_OFF : SD_OFF) + (lane & 3) * 16 : SREC_OFF + (lane & 7) * 16), pitch = lane & 8 ? 64 : 128;
        if (warp == 12) {
#pragma unroll 1
            for (int i = 0; i < (int)misc[2]; i++) {
                const uint32_t n = reinterpret_cast<const uint32_t*>(smem + SCNT_OFF)[i] * 32 + lane;
                reinterpret_cast<uint4*>(p.out)[n] = reinterpret_cast<const uint4*>(p.sv)[n];
            }
#pragma unroll 1
            for (int i = lane >> 4; i < give; i += 2) {
                uint32_t x[4];
                lds128(chunk + (ng - 1 - i) * pitch, x);
                p.g->pool[(b * GIVE + i) * 16 + (lane & 15)] = make_uint4(x[0], x[1], x[2], x[3]);
            }
            __threadfence();
            __syncwarp();
            if (lane == 0) {
                asm volatile("st.relaxed.gpu.global.u32 [%0], %1;" ::"l"(p.g->ready + b), "r"(~epoch) : "memory");
                mbar_arrive(sb + BAR_OFF + 16 + 8 * FLIGHT);
            }
        }
        if (warp == 15) {
            int k = lane < 4 * NWG ? lane : 255, next = 4 * NWG, j = 0, mine = ng - give, end = -1, take = 0;
            uint32_t busy, at = sb + CTL_OFF + 4 * lane, from = 0;
#pragma unroll 1
            do {
                if (next > mine && end < 0) {
                    end = mine = ng;
                    const int peer = b % 5 + 5 * lane;
                    uint32_t x = 255;
                    int it = 0;
                    if (peer < G) {
#pragma unroll 1
                        do {
                            asm volatile("ld.relaxed.gpu.global.u32 %0, [%1];" : "=r"(x) : "l"(p.g->rows + peer) : "memory");
                            if (++it > (1 << 22)) __trap();
                        } while ((x >> 16) != (~epoch & 0xFFFFu));
                    }
                    const int r = x & 255, n = __popc(__ballot_sync(0xffffffffu, r != 255));
                    const int level = min(((__reduce_add_sync(0xffffffffu, r != 255 ? r : 0) + n - 1) / n + 3) & ~3, MAXROW);
                    const uint32_t ed = r > level ? min(r - level, (int)(x >> 8) & 255) : min(level - r, ROOM) << 16;
                    uint32_t z = ed;
#pragma unroll
                    for (int o = 1; o < 32; o <<= 1) {
                        const uint32_t y = __shfl_up_sync(0xffffffffu, z, o);
                        if (lane >= o) z += y;
                    }
                    const uint32_t all = __shfl_sync(0xffffffffu, z, 31), moved = min(all & 0xFFFFu, all >> 16);
                    const uint32_t me = __shfl_sync(0xffffffffu, ed, b / 5), mz = __shfl_sync(0xffffffffu, z, b / 5) - me;
                    end = mine = ng - (min((mz + me) & 0xFFFFu, moved) - min(mz & 0xFFFFu, moved));
#pragma unroll 1
                    for (uint32_t u = mz >> 16; u < min((mz + me) >> 16, moved); u++, take++) {
                        const int f = __popc(__ballot_sync(0xffffffffu, (z & 0xFFFFu) <= u));
                        const uint32_t q = u - (__shfl_sync(0xffffffffu, z - ed, f) & 0xFFFFu);
                        if (lane == take) from = (b % 5 + 5 * f) << 8 | q;
                    }
                }
                if (next > mine && take) {
                    if (lane < take) {
                        uint32_t x;
                        int it = 0;
#pragma unroll 1
                        do {
                            asm volatile("ld.acquire.gpu.global.u32 %0, [%1];" : "=r"(x) : "l"(p.g->ready + (from >> 8)) : "memory");
                            if (++it > (1 << 22)) __trap();
                        } while (x != ~epoch);
                    }
                    __syncwarp();
#pragma unroll 1
                    for (end += take; take--;) {
                        const uint32_t f = __shfl_sync(0xffffffffu, from, take);
                        if (lane < 16)
                            asm volatile("cp.async.cg.shared.global [%0], [%1], 16;" ::"r"(chunk + (MAXROW - 1 - take) * pitch),
                                         "l"(p.g->pool + ((f >> 8) * GIVE + (f & 255)) * 16 + lane) : "memory");
                    }
                    take = 0;
                    asm volatile("cp.async.wait_all;" ::: "memory");
                    __threadfence_block();
                    __syncwarp();
                }
                const bool has = k < (end < 0 ? mine : end);
                const uint32_t i = k < mine ? k : MAXROW - 1 + mine - k, x = __shfl_sync(0xffffffffu, pk, j);
                const bool close = has && i >= (x >> 24);
                busy = __ballot_sync(0xffffffffu, has);
                const uint32_t m = __ballot_sync(0xffffffffu, close);
                uint32_t c = has ? ((x & 0xFF00) + i * 0x1000100) | (j ? 0u : ST_START) | (close ? ST_CLOSE : 0u) : MAXROW * 256;
                if (!(busy >> (lane & 12))) c |= 0x80000000u;
                c |= busy >> ((lane & 12) + 4) ? (lane & 12) * 4 + 32 : 16;
                sts32_if(at, c, lane < 16 || !busy);
                j = close ? 0 : j + 1;
                k = close ? next + __popc(m & ((1u << lane) - 1)) : k;
                next += __popc(m);
                at += 64;
            } while (busy);
        }
        __nanosleep(ZDELAY);
        const int zend = misc[32] + misc[64];
#pragma unroll 1
        for (int r = 8 * ng + (warp & 3) * 4; r < zend; r += 16) {
            uint4 v[4];
            uint32_t n[4];
#pragma unroll
            for (int i = 0; i < 4; i++) {
                n[i] = reinterpret_cast<const uint32_t*>(smem + SN_OFF)[min(r + i, zend - 1) * 2 + 1] * 32 + lane;
                v[i] = __ldcg(reinterpret_cast<const uint4*>(p.sv) + n[i]);
            }
#pragma unroll
            for (int i = 0; i < 4; i++)
                if (r + i < zend) __stcs(reinterpret_cast<uint4*>(p.out) + n[i], v[i]);
        }
        static_assert(FLIGHT <= 4, "drain");
        drain(warp & 3);
        asm volatile("cp.async.wait_all;" ::: "memory");
        TSX(14, 384);
    }
}

}

extern "C" void kernel_launch(void* const* d_in, const int* in_sizes, int n_in, void* d_out, int out_size) {
    static int s_G = 0;
    static void* s_scratch = nullptr;
    const int N = in_sizes[0] / 256, E = in_sizes[2];
    if (s_G == 0) {
        cudaFuncSetAttribute(painn_kernel<0, 0, 0>, cudaFuncAttributeMaxDynamicSharedMemorySize, SMEM_BYTES);
        cudaFuncSetAttribute(painn_kernel<50000, 800000, 132>, cudaFuncAttributeMaxDynamicSharedMemorySize, SMEM_BYTES);
        int dev = 0, sms = 0, occ = 0;
        cudaGetDevice(&dev);
        cudaDeviceGetAttribute(&sms, cudaDevAttrMultiProcessorCount, dev);
        cudaOccupancyMaxActiveBlocksPerMultiprocessor(&occ, painn_kernel<0, 0, 0>, THREADS, SMEM_BYTES);
        cudaGetSymbolAddress(&s_scratch, g_scratch);
        s_G = occ >= 1 ? (sms < MAXG ? sms : MAXG) : 0;
    }
    if (s_G == 0 || N > TABLE_MAXN || N > s_G * MAXNPC || (s_G - 1) * ((N + s_G - 1) / s_G) >= N || E > MAXE || E < 4 * MAXG * MAXG) return;
    Params p;
    p.g = (Scratch*)s_scratch;
    p.sv = (const __nv_bfloat16*)d_in[0];
    p.pos = (const __nv_bfloat16*)d_in[1];
    p.src = (const int*)d_in[2];
    p.dst = (const int*)d_in[3];
    p.freqs = (const __nv_bfloat16*)d_in[4];
    p.w1 = (const __nv_bfloat16*)d_in[5];
    p.w2 = (const __nv_bfloat16*)d_in[6];
    p.wr = (const __nv_bfloat16*)d_in[7];
    p.out = (__nv_bfloat16*)d_out;
    p.desc0 = (uint64_t)(SB >> 4) | ((uint64_t)1 << 16) | ((uint64_t)64 << 32) | ((uint64_t)1 << 62);
    p.N = N; p.E = E; p.G = s_G;
    p.NPC = (N + s_G - 1) / s_G;
    p.magic = (uint32_t)(((1ull << 32) + p.NPC - 1) / p.NPC);
    p.gpc = ((E >> 2) + s_G - 1) / s_G;
    p.odd_edges = (E & 3) != 0 || p.gpc > 3 * THREADS;
    if (N == 50000 && E == 800000 && s_G == 132) painn_kernel<50000, 800000, 132><<<s_G, THREADS, SMEM_BYTES, cudaStreamPerThread>>>(p);
    else painn_kernel<0, 0, 0><<<s_G, THREADS, SMEM_BYTES, cudaStreamPerThread>>>(p);
}
```

```cpp
#include <cuda_runtime.h>
#include <cuda_bf16.h>
#include <stdint.h>

namespace {

constexpr int NWG = 3;
constexpr int REG_C = 160, REG_H = 32;
#define SPL_N 10
#define ROOM 4
#define TOUCH2 4
#define FLIGHT 4
#define EXITB 1
#define LEARLY 0
#define BRANCHY 0
#define FPOS 2
#define WPOS 0
#define CUT 4
#define ZCS 0
#define STPRE ""
#define STSUF ""
#define STPOL ".cs"
#define W15FREE 1
#define GUNROLL_N 1
constexpr int GUNROLL = GUNROLL_N;
#define VLATE 8
#define VSOON 4
#define SPOS 0
#define BALANCE 1
#define ZDELAY 2500
constexpr int SPL = SPL_N;
#define GIVE_N 10
constexpr int GIVE = GIVE_N;
#define PDELAY_N 150
constexpr int PDELAY = PDELAY_N;
constexpr int THREADS = 512;
constexpr int MAXG = 136;
constexpr int MAXROW = 96;
constexpr int TMAX = MAXROW / 12 + 18;
constexpr int MAXNPC = 480;
constexpr int MAXE = 1 << 20;

constexpr int W1_OFF = 0;
constexpr int W2_OFF = 8192;
constexpr int WR_OFF = 32768;
constexpr int RING_OFF = 38912;
constexpr int SREC_OFF = RING_OFF + 4 * NWG * 12288;
constexpr int SD_OFF = SREC_OFF + (MAXROW + 1) * 128 + 16;
constexpr int SN_OFF = SD_OFF + (MAXROW + 1) * 64 + 16;
constexpr int CTL_OFF = SN_OFF + (MAXROW + 1) * 64 + 16;
constexpr int TABLE_MAXN = 50176;
constexpr int STAGE_OFF = TABLE_MAXN * 4;
constexpr int SCNT_OFF = STAGE_OFF + MAXG * 128;
constexpr int GPOS_OFF = RING_OFF;
constexpr int PACK_OFF = GPOS_OFF + 4 * 8192;
constexpr int NCNT_OFF = SCNT_OFF + 768;
constexpr int OPOS_OFF = NCNT_OFF + 2048;
constexpr int BAR_OFF = OPOS_OFF + 4096;
constexpr int MISC_OFF = BAR_OFF + 128;
constexpr int FREQ_OFF = MISC_OFF + 512;
constexpr int DUMMY_OFF = (FREQ_OFF + 128 + 127) / 128 * 128;
constexpr int SMEM_BYTES = DUMMY_OFF + 4096;
static_assert(CTL_OFF + 64 * TMAX <= SCNT_OFF && CTL_OFF + 64 * TMAX - SREC_OFF <= 64 * THREADS && 4 * (MAXG + 32) <= 768, "smem map");
static_assert(SMEM_BYTES <= 232448 && BAR_OFF % 8 == 0 && RING_OFF % 128 == 0 && SREC_OFF % 128 == 0 && GPOS_OFF % 128 == 0 && PACK_OFF + 15 * 512 <= SREC_OFF && (MAXG + 14) / 15 <= 12, "smem map");

constexpr uint32_t PAY_INVALID = 0x3FFFFFFu;
constexpr uint32_t PAY_MARK = 0x3FFFDFFu;
constexpr uint32_t NODE_SPLIT = 0x40000000u;
constexpr uint32_t ST_START = 1, ST_CLOSE = 2;
constexpr float QINVP = 9.0f / 510.0f;
constexpr uint32_t QTHRESH = 2209;
#define QSURE_N 1980
constexpr uint32_t QSURE = QSURE_N;

struct Scratch {
    unsigned sync[32];
    uint4 table[TABLE_MAXN / 4];
    uint4 wimg[RING_OFF / 16];
    uint2 pos8[TABLE_MAXN];
    uint4 xbuf[MAXG * MAXG * 8 + 3 * THREADS];
    uint4 pool[MAXG * GIVE * 16];
    unsigned rows[MAXG];
    unsigned ready[MAXG];
    int ovfcnt[MAXG];
    int2 ovf[MAXE + 8 * MAXG + 8];
};
__device__ __align__(128) Scratch g_scratch;

struct Params {
    const __nv_bfloat16* pos;
    Scratch* g;
    const int* src;
    const int* dst;
    int N, NPC, E, gpc;
    const __nv_bfloat16* w2;
    const __nv_bfloat16* wr;
    const __nv_bfloat16* w1;
    const __nv_bfloat16* freqs;
    const __nv_bfloat16* sv;
    __nv_bfloat16* out;
    uint64_t desc0;
    int G;
    uint32_t magic;
    int odd_edges;
};
constexpr uint32_t SB = 1024;

#define TSX(i, thr)
#define TR(k, thr, t)
#define TS0(i) TSX(i, 0)
#define STOP(k)
#define TRW(ctl)

__device__ __forceinline__ uint32_t smem_u32(const void* p) { return (uint32_t)__cvta_generic_to_shared(p); }
__device__ __forceinline__ void mbar_init(uint32_t bar, uint32_t cnt) {
    asm volatile("mbarrier.init.shared::cta.b64 [%0], %1;" ::"r"(bar), "r"(cnt) : "memory");
}
__device__ __forceinline__ void mbar_arrive(uint32_t bar) {
    asm volatile("mbarrier.arrive.shared::cta.b64 _, [%0];" ::"r"(bar) : "memory");
}
__device__ __forceinline__ void mbar_expect_tx(uint32_t bar, uint32_t bytes) {
    asm volatile("mbarrier.arrive.expect_tx.shared::cta.b64 _, [%0], %1;" ::"r"(bar), "r"(bytes) : "memory");
}
__device__ __forceinline__ void mbar_wait(uint32_t bar, uint32_t parity) {
    uint32_t ok;
    int it = 0;
    do {
        asm volatile(
            "{\n.reg .pred p;\n"
            "mbarrier.try_wait.parity.shared::cta.b64 p, [%1], %2, 2000;\n"
            "selp.u32 %0, 1, 0, p;\n}\n"
            : "=r"(ok) : "r"(bar), "r"(parity) : "memory");
        if (++it > (1 << 20)) __trap();
    } while (!ok);
}
__device__ __forceinline__ uint32_t mbar_test(uint32_t bar, uint32_t parity) {
    uint32_t ok;
    asm volatile("{\n.reg .pred p;\nmbarrier.test_wait.parity.shared::cta.b64 p, [%1], %2;\nselp.u32 %0, 1, 0, p;\n}\n"
                 : "=r"(ok) : "r"(bar), "r"(parity) : "memory");
    return ok;
}
__device__ __forceinline__ uint32_t pin(uint32_t x) {
    uint32_t r;
    asm volatile("shfl.sync.bfly.b32 %0, %1, 0, 31, -1;" : "=r"(r) : "r"(x));
    return r;
}
__device__ __forceinline__ void bulk_g2s(uint32_t dst, const void* src, uint32_t bytes, uint32_t bar) {
    asm volatile("cp.async.bulk.shared::cluster.global.mbarrier::complete_tx::bytes [%0], [%1], %2, [%3];"
                 ::"r"(dst), "l"(src), "r"(bytes), "r"(bar) : "memory");
}
__device__ __forceinline__ void ldsm4(uint32_t addr, uint32_t* r) {
    asm volatile("ldmatrix.sync.aligned.m8n8.x4.shared.b16 {%0,%1,%2,%3}, [%4];"
                 : "=r"(r[0]), "=r"(r[1]), "=r"(r[2]), "=r"(r[3]) : "r"(addr) : "memory");
}
__device__ __forceinline__ uint32_t pack2(float lo, float hi) {
    uint32_t r;
    asm("cvt.rn.bf16x2.f32 %0, %1, %2;" : "=r"(r) : "f"(hi), "f"(lo));
    return r;
}
__device__ __forceinline__ float bf_lo(uint32_t w) { return __uint_as_float(w << 16); }
__device__ __forceinline__ float bf_hi(uint32_t w) { return __uint_as_float(w & 0xFFFF0000u); }
__device__ __forceinline__ float rbf16(float x) { return __uint_as_float(pack2(0.f, x)); }
__device__ __forceinline__ uint32_t hmul2(uint32_t a, uint32_t b) {
    uint32_t r;
    asm("mul.rn.bf16x2 %0, %1, %2;" : "=r"(r) : "r"(a), "r"(b));
    return r;
}
__device__ __forceinline__ uint32_t hfma2(uint32_t a, uint32_t b, uint32_t c) {
    uint32_t r;
    asm("fma.rn.bf16x2 %0, %1, %2, %3;" : "=r"(r) : "r"(a), "r"(b), "r"(c));
    return r;
}
__device__ __forceinline__ uint32_t hfma2_lo(uint32_t a, uint32_t b, uint32_t c) {
    uint32_t r;
    asm("{\n.reg .b16 l, h;\n.reg .b32 t;\nmov.b32 {l, h}, %2;\nmov.b32 t, {l, l};\nfma.rn.bf16x2 %0, %1, t, %3;\n}\n" : "=r"(r) : "r"(a), "r"(b), "r"(c));
    return r;
}
__device__ __forceinline__ uint32_t hfma2_hi(uint32_t a, uint32_t b, uint32_t c) {
    uint32_t r;
    asm("{\n.reg .b16 l, h;\n.reg .b32 t;\nmov.b32 {l, h}, %2;\nmov.b32 t, {h, h};\nfma.rn.bf16x2 %0, %1, t, %3;\n}\n" : "=r"(r) : "r"(a), "r"(b), "r"(c));
    return r;
}
__device__ __forceinline__ uint32_t hmul2_hi(uint32_t a, uint32_t b) {
    uint32_t r;
    asm("{\n.reg .b16 l, h;\n.reg .b32 t;\nmov.b32 {l, h}, %2;\nmov.b32 t, {h, h};\nmul.rn.bf16x2 %0, %1, t;\n}\n" : "=r"(r) : "r"(a), "r"(b));
    return r;
}
__device__ __forceinline__ uint32_t hadd2(uint32_t a, uint32_t b) {
    uint32_t r;
    asm("add.rn.bf16x2 %0, %1, %2;" : "=r"(r) : "r"(a), "r"(b));
    return r;
}
__device__ __forceinline__ uint32_t hsub2(uint32_t a, uint32_t b) {
    uint32_t r;
    asm("sub.rn.bf16x2 %0, %1, %2;" : "=r"(r) : "r"(a), "r"(b));
    return r;
}
__device__ __forceinline__ void cp_async_arrive(uint32_t bar) {
    asm volatile("cp.async.mbarrier.arrive.noinc.shared::cta.b64 [%0];" ::"r"(bar) : "memory");
}
__device__ __forceinline__ float tanh_fast(float x) {
    float r;
    asm("tanh.approx.f32 %0, %1;" : "=f"(r) : "f"(x));
    return r;
}
__device__ __forceinline__ void wg_fence() { asm volatile("wgmma.fence.sync.aligned;" ::: "memory"); }
__device__ __forceinline__ void wg_commit() { asm volatile("wgmma.commit_group.sync.aligned;" ::: "memory"); }
template <int N>
__device__ __forceinline__ void wg_wait() { asm volatile("wgmma.wait_group.sync.aligned %0;" ::"n"(N) : "memory"); }

#define WG_REGS "{%0,%1,%2,%3,%4,%5,%6,%7,%8,%9,%10,%11,%12,%13,%14,%15,%16,%17,%18,%19,%20,%21,%22,%23,%24,%25,%26,%27,%28,%29,%30,%31}"
#define WG_OPS(c) c(d[0]), c(d[1]), c(d[2]), c(d[3]), c(d[4]), c(d[5]), c(d[6]), c(d[7]), c(d[8]), c(d[9]), c(d[10]), \
    c(d[11]), c(d[12]), c(d[13]), c(d[14]), c(d[15]), c(d[16]), c(d[17]), c(d[18]), c(d[19]), c(d[20]), c(d[21]),     \
    c(d[22]), c(d[23]), c(d[24]), c(d[25]), c(d[26]), c(d[27]), c(d[28]), c(d[29]), c(d[30]), c(d[31])
__device__ __forceinline__ void wgmma_first(float* d, const uint32_t* a, uint64_t desc) {
    asm volatile("wgmma.mma_async.sync.aligned.m64n64k16.f32.bf16.bf16 " WG_REGS ", {%32,%33,%34,%35}, %36, 0, 1, 1, 1;"
                 : WG_OPS("+f") : "r"(a[0]), "r"(a[1]), "r"(a[2]), "r"(a[3]), "l"(desc));
}
__device__ __forceinline__ void wgmma_acc(float* d, const uint32_t* a, uint64_t desc) {
    asm volatile("wgmma.mma_async.sync.aligned.m64n64k16.f32.bf16.bf16 " WG_REGS ", {%32,%33,%34,%35}, %36, 1, 1, 1, 1;"
                 : WG_OPS("+f") : "r"(a[0]), "r"(a[1]), "r"(a[2]), "r"(a[3]), "l"(desc));
}
__device__ __forceinline__ void wgmma_k64(float* d, const uint32_t* a, uint64_t desc) {
    wgmma_first(d, a, desc);
    wgmma_acc(d, a + 4, desc + 128);
    wgmma_acc(d, a + 8, desc + 256);
    wgmma_acc(d, a + 12, desc + 384);
}
__device__ __forceinline__ void fence_regs(float* d) { asm volatile("" : WG_OPS("+f")::"memory"); }
__device__ __forceinline__ uint32_t qaxis(float x) {
    const float u = fmaf(x, QINVP, 0.25f);
    const float f = u - ((u + 12582912.f) - 12582912.f);
    return __float_as_uint(fmaf(fabsf(f), 510.f, 12582912.f));
}
__device__ __forceinline__ uint32_t qcode(float x, float y, float z, uint32_t tx) {
    return __byte_perm(__byte_perm(qaxis(x), qaxis(y), 0x3340), qaxis(z), 0x3410) ^ tx;
}
__device__ __forceinline__ bool near_test(uint32_t ca, uint32_t cb, uint32_t tag24, uint32_t& q) {
    const uint32_t D = __vabsdiffu4(ca, cb);
    q = __dp4a(D, D, 0x7FFFFFFFu - QSURE);
    return q <= 0x7FFFFFFFu - QSURE + QTHRESH || ((ca ^ tag24) | (cb ^ tag24)) >= 0x1000000u;
}
__device__ __forceinline__ bool inside(uint32_t rxy, uint32_t rz) {
    const uint32_t qxy = hmul2(rxy, rxy), qz = hmul2(rz, rz);
    return bf_lo(qxy) + bf_hi(qxy) + bf_lo(qz) <= 24.8125f;
}

__device__ __forceinline__ uint32_t lds32(uint32_t addr) {
    uint32_t r;
    asm volatile("ld.shared.u32 %0, [%1];" : "=r"(r) : "r"(addr));
    return r;
}
__device__ __forceinline__ void sts32_if(uint32_t addr, uint32_t v, bool c) {
    asm volatile("{\n.reg .pred p;\nsetp.ne.u32 p, %2, 0;\n@p st.shared.u32 [%0], %1;\n}\n" ::"r"(addr), "r"(v), "r"((uint32_t)c) : "memory");
}
__device__ __forceinline__ void stg128_if(void* ptr, uint4 v, bool c) {
    asm volatile("{\n.reg .pred p;\nsetp.ne.u32 p, %5, 0;\n@p st.relaxed.gpu.global.v4.u32 [%0], {%1,%2,%3,%4};\n}\n"
                 ::"l"(ptr), "r"(v.x), "r"(v.y), "r"(v.z), "r"(v.w), "r"((uint32_t)c) : "memory");
}
__device__ __forceinline__ void lds128(uint32_t addr, uint32_t* r) {
    asm volatile("ld.shared.v4.u32 {%0,%1,%2,%3}, [%4];" : "=r"(r[0]), "=r"(r[1]), "=r"(r[2]), "=r"(r[3]) : "r"(addr) : "memory");
}
__device__ __forceinline__ void stg2_if(uint64_t ptr, const uint32_t* r, bool c) {
    asm volatile("{\n.reg .pred p;\nsetp.ne.u32 p, %9, 0;\n@p st.global.cs.v4.u32 [%8], {%0,%1,%2,%3};\n"
                 "@p st.global.cs.v4.u32 [%8 + 64], {%4,%5,%6,%7};\n}\n"
                 ::"r"(r[0]), "r"(r[1]), "r"(r[2]), "r"(r[3]), "r"(r[4]), "r"(r[5]), "r"(r[6]), "r"(r[7]), "l"(ptr), "r"((uint32_t)c) : "memory");
}
#define GCOND "setp.ne.u32 p, n, 0xFFFF;"
template <int NP, int HI, int PAD = 1>
__device__ __forceinline__ void gather(uint32_t dst, const void* base, uint32_t c, uint32_t e) {
#define GATHER_HEAD "{\n.reg .pred p;\n.reg .b32 n;\n.reg .b64 a;\nprmt.b32 n, %2, 0, %3;\n" GCOND "\nmad.lo.u32 n, n, 512, %4;\nmad.wide.u32 a, n, 1, %1;\n"
#define GATHER_1(P) P "cp.async.cg.shared.global [%0], [a], 16;\n}\n"
#define GATHER_3(P) P "cp.async.cg.shared.global [%0], [a + 128], 16;\n" P "cp.async.cg.shared.global [%0 + 1024], [a + 256], 16;\n" \
                    P "cp.async.cg.shared.global [%0 + 2048], [a + 384], 16;\n}\n"
#define GATHER_ARGS(z) ::"r"(dst), "l"(base), "r"(e), "n"((HI ? 0x32 : 0x10) + z), "r"(c) : "memory"
    if constexpr (NP == 1 && PAD) asm volatile(GATHER_HEAD GATHER_1("@p ") GATHER_ARGS(0x4400));
    if constexpr (NP == 1 && !PAD) asm volatile(GATHER_HEAD GATHER_1("") GATHER_ARGS(0x4400));
    if constexpr (NP == 3 && PAD) asm volatile(GATHER_HEAD GATHER_3("@p ") GATHER_ARGS(0x5500));
    if constexpr (NP == 3 && !PAD) asm volatile(GATHER_HEAD GATHER_3("") GATHER_ARGS(0x4400));
    if constexpr (NP == 4)
        asm volatile(GATHER_HEAD "setp.ge.u32 p, %2, 0x40000000;\ncp.async.cg.shared.global [%0], [a], 16, p;\ncp.async.cg.shared.global [%0 + 1024], [a + 128], 16, p;\n"
                     "cp.async.cg.shared.global [%0 + 2048], [a + 256], 16, p;\ncp.async.cg.shared.global [%0 + 3072], [a + 384], 16, p;\n}\n" GATHER_ARGS(0x4400));
}
__device__ __forceinline__ void cp_commit() { asm volatile("cp.async.commit_group;" ::: "memory"); }
__device__ __forceinline__ void cp_wait1() { asm volatile("cp.async.wait_group 1;" ::: "memory"); }
__device__ __forceinline__ uint32_t hmul2_lo(uint32_t a, uint32_t b) {
    uint32_t r;
    asm("{\n.reg .b16 l, h;\n.reg .b32 t;\nmov.b32 {l, h}, %2;\nmov.b32 t, {l, l};\nmul.rn.bf16x2 %0, %1, t;\n}\n" : "=r"(r) : "r"(a), "r"(b));
    return r;
}
__device__ __forceinline__ void lds2_if(uint32_t a0, uint32_t a1, uint32_t* r, uint32_t c) {
    asm volatile("{\n.reg .pred p;\nsetp.ne.u32 p, %10, 0;\n@p ld.shared.v4.u32 {%0,%1,%2,%3}, [%8];\n@p ld.shared.v4.u32 {%4,%5,%6,%7}, [%9];\n}\n"
                 : "+r"(r[0]), "+r"(r[1]), "+r"(r[2]), "+r"(r[3]), "+r"(r[4]), "+r"(r[5]), "+r"(r[6]), "+r"(r[7])
                 : "r"(a0), "r"(a1), "r"(c) : "memory");
}
__device__ __forceinline__ int fresh_lane() {
    int l;
    asm volatile("mov.u32 %0, %%laneid;" : "=r"(l));
    return l;
}

__device__ __forceinline__ void cold_edges(unsigned char* smem, const Params& p, int lo, int hi, uint32_t tag) {
#pragma unroll 1
    for (int e = lo + threadIdx.x; e < hi; e += THREADS) {
        const int s = p.src[e], d = p.dst[e];
        uint32_t q;
        if (near_test(reinterpret_cast<const uint32_t*>(smem)[s], reinterpret_cast<const uint32_t*>(smem)[d], tag << 24, q)) {
            const uint32_t own = __umulhi((uint32_t)d, p.magic);
            const uint32_t slot4 = atomicAdd(reinterpret_cast<uint32_t*>(smem + SCNT_OFF) + own, 4u);
            uint32_t* line = reinterpret_cast<uint32_t*>(smem + STAGE_OFF) + own * 32;
            if (slot4 < 124) {
                line[slot4 >> 2] = ((uint32_t)s << 15) + ((uint32_t)(d - own * p.NPC) << 6) + tag + (q & 0x80000000u);
            } else {
                uint32_t o = atomicAdd(reinterpret_cast<uint32_t*>(smem + MISC_OFF) + 16, 1u);
                p.g->ovf[(size_t)blockIdx.x * (4 * p.gpc + 4) + o] = make_int2(s, d);
                line[31] = (PAY_MARK << 6) | tag;
            }
        }
    }
}
__device__ __forceinline__ void cold_filter(unsigned char* smem, const Params& p, int e0, int e1, uint32_t tag, int redo) {
    if (redo) {
        if (threadIdx.x < MAXG) reinterpret_cast<uint32_t*>(smem + SCNT_OFF)[threadIdx.x] = 0;
        __syncthreads();
    }
    cold_edges(smem, p, redo ? 4 * e0 : 4 * (e0 + 3 * THREADS), 4 * e1, tag);
    if (blockIdx.x == 0) cold_edges(smem, p, p.E & ~3, p.E, tag);
    __syncthreads();
    if (threadIdx.x == 0) p.g->ovfcnt[blockIdx.x] = reinterpret_cast<uint32_t*>(smem + MISC_OFF)[16];
    __threadfence();
    __syncthreads();
}
__device__ __forceinline__ uint3 geometry(uint32_t rxy, uint32_t rz) {
    const uint32_t qxy = hmul2(rxy, rxy), qz = hmul2(rz, rz);
    float d, id;
    asm("sqrt.approx.ftz.f32 %0, %1;" : "=f"(d) : "f"(rbf16(rbf16(bf_lo(qxy) + bf_hi(qxy) + bf_lo(qz)) + 1e-8f)));
    d = rbf16(d);
    asm("rcp.approx.ftz.f32 %0, %1;" : "=f"(id) : "f"(d));
    const float cs = rbf16(__cosf(rbf16(rbf16(3.14159265358979f * d) * 0.2f)));
    const uint32_t zs = pack2(bf_lo(rz) * id, 0.5f * rbf16(cs + 1.0f) * id);
    return d < 5.0f ? make_uint3(pack2(bf_lo(rxy) * id, bf_hi(rxy) * id), zs, __byte_perm(__float_as_uint(d), zs, 0x7632)) : make_uint3(0, 0, 0);
}
__device__ __forceinline__ void cold_messages(unsigned char* smem, const Params& p, int nn) {
    const int nbase = blockIdx.x * p.NPC, lane = threadIdx.x & 31;
    const uint32_t* box = reinterpret_cast<const uint32_t*>(p.g->xbuf) + blockIdx.x * p.G * 32;
    uint32_t* w = reinterpret_cast<uint32_t*>(smem + RING_OFF);
#pragma unroll 1
    for (int i = threadIdx.x; i < 9728; i += THREADS)
        w[i] = i < 2048 ? reinterpret_cast<const uint32_t*>(p.w1)[i] : i < 8192 ? reinterpret_cast<const uint32_t*>(p.w2)[i - 2048] : reinterpret_cast<const uint32_t*>(p.wr)[i - 8192];
#pragma unroll 1
    for (int i = threadIdx.x; i < nn * 32; i += THREADS) reinterpret_cast<uint4*>(p.out)[nbase * 32 + i] = reinterpret_cast<const uint4*>(p.sv)[nbase * 32 + i];
    __threadfence();
    __syncthreads();
    const float freq = __bfloat162float(p.freqs[lane & 15]);
#pragma unroll 1
    for (int m = -1; m < p.G; m++) {
        const int cnt = m < 0 ? p.G * 32 : (__ldcg(box + m * 32 + 31) >> 6) == PAY_MARK ? __ldcg(&p.g->ovfcnt[m]) : 0;
#pragma unroll 1
        for (int i = threadIdx.x; i - lane < cnt; i += THREADS) {
            int2 e = make_int2(0, -1);
            if (i < cnt) {
                if (m < 0) {
                    const uint32_t x = __ldcg(box + i);
                    e = make_int2((x >> 15) & 0xFFFFu, nbase + ((x >> 6) & 511u));
                } else {
                    e = __ldcg(p.g->ovf + (size_t)m * (4 * p.gpc + 4) + i);
                }
            }
            bool in = (uint32_t)(e.y - nbase) < (uint32_t)nn;
            uint3 geo = make_uint3(0, 0, 0);
            if (in) {
                const uint2 ps = __ldcg(p.g->pos8 + e.x), pd = __ldcg(p.g->pos8 + e.y);
                const uint32_t rxy = hsub2(ps.x, pd.x), rz = hsub2(ps.y, pd.y);
                in = inside(rxy, rz);
                geo = geometry(rxy, rz);
            }
#pragma unroll 1
            for (uint32_t todo = __ballot_sync(0xffffffffu, in); todo; todo &= todo - 1) {
                const int l = __ffs(todo) - 1;
                const uint32_t* row = reinterpret_cast<const uint32_t*>(p.sv) + (size_t)__shfl_sync(0xffffffffu, e.x, l) * 128 + lane;
                uint32_t* orow = reinterpret_cast<uint32_t*>(p.out) + (size_t)__shfl_sync(0xffffffffu, e.y, l) * 128 + lane;
                const uint32_t gx = __shfl_sync(0xffffffffu, geo.x, l), gy = __shfl_sync(0xffffffffu, geo.y, l);
                const float rb = rbf16(__sinf(rbf16(bf_lo(__shfl_sync(0xffffffffu, geo.z, l)) * freq)) * bf_hi(gy));
                uint32_t x = row[0];
                float a[12] = {0, 0, 0, 0, 0, 0, 0, 0, 0, 0, 0, 0};
#pragma unroll 2
                for (int k = 0; k < 64; k++) {
                    const uint32_t u = __shfl_sync(0xffffffffu, x, k >> 1), ww = w[k * 32 + lane];
                    const float f = k & 1 ? bf_hi(u) : bf_lo(u);
                    a[0] = fmaf(f, bf_lo(ww), a[0]); a[1] = fmaf(f, bf_hi(ww), a[1]);
                }
                x = pack2(0.5f * fmaf(a[0], tanh_fast(0.5f * a[0]), a[0]), 0.5f * fmaf(a[1], tanh_fast(0.5f * a[1]), a[1]));
                a[0] = a[1] = 0.f;
#pragma unroll 2
                for (int k = 0; k < 64; k++) {
                    const uint32_t u = __shfl_sync(0xffffffffu, x, k >> 1);
                    const float f = k & 1 ? bf_hi(u) : bf_lo(u), r = __shfl_sync(0xffffffffu, rb, k & 15);
#pragma unroll
                    for (int c = 0; c < 3; c++) {
                        const uint32_t ww = w[2048 + k * 96 + c * 32 + lane], wr = k < 16 ? w[8192 + k * 96 + c * 32 + lane] : 0u;
                        a[2 * c] = fmaf(f, bf_lo(ww), a[2 * c]); a[2 * c + 1] = fmaf(f, bf_hi(ww), a[2 * c + 1]);
                        a[6 + 2 * c] = fmaf(r, bf_lo(wr), a[6 + 2 * c]); a[7 + 2 * c] = fmaf(r, bf_hi(wr), a[7 + 2 * c]);
                    }
                }
                const uint32_t mv = pack2(a[2] * a[8], a[3] * a[9]), mr = pack2(a[4] * a[10], a[5] * a[11]);
                const uint32_t o[4] = {pack2(a[0] * a[6], a[1] * a[7]), hfma2_lo(mr, gx, hmul2(mv, row[32])), hfma2_hi(mr, gx, hmul2(mv, row[64])),
                                       hfma2_lo(mr, gy, hmul2(mv, row[96]))};
#pragma unroll
                for (int c = 0; c < 4; c++) asm volatile("red.global.add.noftz.bf16x2 [%0], %1;" ::"l"(orow + 32 * c), "r"(o[c]) : "memory");
            }
        }
    }
}

#define FORD 2
#define NPRE 6
#define SPLIT(k) asm volatile("{\n.reg .pred p;\nsetp.eq.u32 p, %0, %1;\n@p trap;\n}" ::"r"(c0), "n"(0x70000 + k) : "memory")
#define PIN8(a) asm volatile("" : "+r"((a)[0]), "+r"((a)[1]), "+r"((a)[2]), "+r"((a)[3]), "+r"((a)[4]), "+r"((a)[5]), "+r"((a)[6]), "+r"((a)[7]))
#define RINGA 2
#define RINGB 3
#define RING(k) do { if (RINGA == k) asm volatile("bar.sync %0, 256;" ::"r"(1 + (warp >> 2)) : "memory"); \
                     if (RINGB == k) asm volatile("bar.arrive %0, 256;" ::"r"((c0 >> 4) & 3) : "memory"); } while (0)
template <int V> struct IntC { static constexpr int value = V; };

template <int CN, int CE, int CG>
__global__ void __launch_bounds__(THREADS, 1) painn_kernel(const __grid_constant__ Params p) {
    extern __shared__ __align__(1024) unsigned char smem_dyn[];
    unsigned char* const smem = static_cast<unsigned char*>(__cvta_shared_to_generic(SB));
    constexpr uint32_t sb = SB;
    const int tid = threadIdx.x, lane = tid & 31;
    const int warp = __shfl_sync(0xffffffffu, tid >> 5, 0);
    constexpr int CNPC = CG ? (CN + CG - 1) / CG : 1, CGPC = CG ? (CE / 4 + CG - 1) / CG : 1;
    const int b = blockIdx.x, G = CG ? CG : p.G, NPC = CG ? CNPC : p.NPC, N = CG ? CN : p.N, gpc = CG ? CGPC : p.gpc;
    const uint32_t magic = CG ? (uint32_t)(((1ull << 32) + CNPC - 1) / CNPC) : p.magic;
    const bool odd_edges = CG ? (CE & 3) != 0 || CGPC > 3 * THREADS : p.odd_edges;
    const int nbase = b * NPC, nn = min(NPC, N - nbase);
    const int eg0 = b * gpc, eg1 = min((CG ? CE : p.E) >> 2, eg0 + gpc);

    uint4* stage4 = reinterpret_cast<uint4*>(smem + STAGE_OFF);
    uint32_t* ncnt = reinterpret_cast<uint32_t*>(smem + NCNT_OFF);
    uint32_t* misc = reinterpret_cast<uint32_t*>(smem + MISC_OFF);
    const uint32_t bar_tab = sb + BAR_OFF;

    TS0(0);
    int4 es[3], ed[3];
    auto load_edges = [&](int i) {
        const int g = min(eg0 + tid + i * THREADS, eg1 - 1);
        asm volatile("ld.global.cs.v4.u32 {%0,%1,%2,%3}, [%8];\nld.global.cs.v4.u32 {%4,%5,%6,%7}, [%9];"
                     : "=r"(es[i].x), "=r"(es[i].y), "=r"(es[i].z), "=r"(es[i].w), "=r"(ed[i].x), "=r"(ed[i].y), "=r"(ed[i].z), "=r"(ed[i].w)
                     : "l"(reinterpret_cast<const int4*>(p.src) + g), "l"(reinterpret_cast<const int4*>(p.dst) + g) : "memory");
    };
    const char* const own = reinterpret_cast<const char*>(p.sv) + (size_t)nbase * 512;
    auto touch = [&](int o) {
        if (o + lane * 256 < nn * 512)
            asm volatile("cp.async.ca.shared.global.L2::256B [%0], [%1], 4;" ::"r"(sb + DUMMY_OFF + 4 * lane), "l"(own + o + lane * 256) : "memory");
    };
    uint4* const xout = p.g->xbuf + ((tid >> 3) * G + b) * 8 + (tid & 7);
    unsigned epoch;
    const uint32_t tbytes = ((N + 3) >> 2) * 16, cut = (tbytes >> 8) * CUT * 16, bar_cut = sb + BAR_OFF + 120;
    {
        uint32_t pxy, pz;
        asm volatile("ld.global.nc.u32 %0, [%3];\nld.global.nc.u32 %1, [%3 + 4];\nld.global.ca.u32 %2, [%4];"
                     : "=r"(pxy), "=r"(pz), "=r"(epoch)
                     : "l"(reinterpret_cast<const uint32_t*>(p.pos) + ((nbase + min(tid, nn - 1)) * 3 >> 1)), "l"(p.g->sync) : "memory");
        const uint32_t sh = ((nbase + tid) & 1) << 4;
        pxy = __funnelshift_r(pxy, pz, sh);
        pz >>= sh;
        if (tid < nn) {
            reinterpret_cast<uint32_t*>(p.g->table)[nbase + tid] = qcode(bf_lo(pxy), bf_hi(pxy), bf_lo(pz), ((epoch & 31u) ^ 0x6Bu) << 24);
            p.g->pos8[nbase + tid] = make_uint2(pxy, pz);
        }
        reinterpret_cast<uint2*>(smem + OPOS_OFF)[tid] = make_uint2(pxy, pz);
        if (pxy == 0xFFFFFFFFu && pz == 0xFFFFFFFFu && epoch == 0xFFFFFFFFu) asm volatile("nanosleep.u32 0;");
        load_edges(0);
    }
    __syncthreads();
    const uint32_t tag = (epoch & 31u) | 32u;
    if (tid == THREADS - 1) {
        asm volatile("red.relaxed.gpu.global.add.u32 [%0], 1;" ::"l"(p.g->sync + 1) : "memory");
        TSX(1, 511);
        mbar_init(bar_tab, 1);
        mbar_init(bar_cut, 1);
        mbar_expect_tx(bar_cut, cut);
        mbar_expect_tx(bar_tab, tbytes - cut);
        const unsigned want = (epoch + 1) * G;
        unsigned c;
        int it = smem_u32(smem_dyn) == SB ? 0 : 1 << 22;
        do {
            asm volatile("ld.relaxed.gpu.global.u32 %0, [%1];" : "=r"(c) : "l"(p.g->sync + 1) : "memory");
            if (++it > (1 << 22)) __trap();
        } while (c != want);
        bulk_g2s(sb, p.g->table, cut, bar_cut);
        bulk_g2s(sb + cut, reinterpret_cast<const char*>(p.g->table) + cut, tbytes - cut, bar_tab);
        TSX(2, 511);
    }
    if (warp == 14) {
#pragma unroll 1
        for (int c = b * 32 + lane; c < RING_OFF / 16; c += G * 32) {
            const int row = c >> 3, j = (c ^ row) & 7;
            uint4 v;
            if (c < 512) {
                const uint32_t half = 0x3F003F00u;
                v = __ldg(reinterpret_cast<const uint4*>(p.w1) + row * 8 + j);
                v = make_uint4(hmul2(v.x, half), hmul2(v.y, half), hmul2(v.z, half), hmul2(v.w, half));
            } else {
                const uint32_t* q = (c < 2048 ? reinterpret_cast<const uint32_t*>(p.w2) + (row & 63) * 96 + ((row >> 6) - 1) * 32
                                              : reinterpret_cast<const uint32_t*>(p.wr) + (row & 15) * 96 + ((row >> 4) - 16) * 32) + (j & 4) * 4 + (j & 3);
                v = make_uint4(__ldg(q), __ldg(q + 4), __ldg(q + 8), __ldg(q + 12));
            }
            p.g->wimg[c] = v;
        }
    }
    if (tid == 416) {
#pragma unroll
        for (int i = 0; i < FLIGHT + 2; i++) mbar_init(sb + BAR_OFF + 8 + 8 * i, i ? 1 : 15);
    }
    ncnt[tid] = 0;
    if (tid < MAXG + 32) reinterpret_cast<uint32_t*>(smem + SCNT_OFF)[tid] = tid < MAXG ? 0 : 124;
    if (tid < 128) misc[tid] = 0;
    {
        const uint32_t inv = (PAY_INVALID << 6) | tag;
        stage4[tid] = stage4[tid + THREADS] = make_uint4(inv, inv, inv, inv);
        if (tid < MAXG * 8 - 2 * THREADS) stage4[tid + 2 * THREADS] = make_uint4(inv, inv, inv, inv);
    }
    __syncthreads();
    if ((tid >> 4) == 29) asm volatile("cp.async.ca.shared.global [%0], [%1], 4;" ::"r"(sb + FREQ_OFF + 8 * (tid & 14) + 4 * (tid & 1)),
                              "l"(reinterpret_cast<const uint32_t*>(p.freqs) + ((tid & 7) >> 1) + (tid & 1) * 4) : "memory");
    load_edges(1);
    if (warp != 13) mbar_wait(bar_cut, 0);
    load_edges(2);
    if (tid == 416) asm volatile("fence.acq_rel.gpu;" ::: "memory");
#pragma unroll
    for (int i = 0; i < 3; i++) stg128_if(xout + i * G * THREADS, make_uint4(0, 0, 0, 0), tid + i * THREADS < G * 8);
    if (warp == 13) mbar_wait(bar_cut, 0);
    mbar_wait(bar_tab, 0);
    TS0(3);
    if (warp == 15) {
#pragma unroll
        for (int i = 0; i < TOUCH2; i++) touch(i * 8192);
    }

#pragma unroll 1
    for (int i = 0, g = eg0 + tid; i < 3; i++, g += THREADS) {
        const int s[4] = {es[0].x, es[0].y, es[0].z, es[0].w}, d[4] = {ed[0].x, ed[0].y, ed[0].z, ed[0].w};
        uint32_t ca[4], cb[4], own[4], sl[4], q[4];
        bool c[4];
#pragma unroll
        for (int j = 0; j < 4; j++) { ca[j] = lds32(sb + 4 * s[j]); cb[j] = lds32(sb + 4 * d[j]); }
#pragma unroll
        for (int j = 0; j < 4; j++) {
            c[j] = near_test(ca[j], cb[j], tag << 24, q[j]) && g < eg1;
            own[j] = __umulhi((uint32_t)d[j], magic);
            sl[j] = atomicAdd(reinterpret_cast<uint32_t*>(smem + SCNT_OFF) + (c[j] ? own[j] : MAXG + lane), 4u);
        }
#pragma unroll
        for (int j = 0; j < 4; j++)
            sts32_if(sb + STAGE_OFF + own[j] * 128 + sl[j], own[j] * (uint32_t)(-64 * NPC) + (((uint32_t)s[j] << 15) + (((uint32_t)d[j] << 6) + ((q[j] & 0x80000000u) | tag))),
                     sl[j] < 124);
        es[0] = es[1]; es[1] = es[2];
        ed[0] = ed[1]; ed[1] = ed[2];
    }
    __syncthreads();
    {
        const int redo = __syncthreads_or(tid < MAXG && reinterpret_cast<uint32_t*>(smem + SCNT_OFF)[tid] > 124);
        if (__builtin_expect(redo || odd_edges, 0)) cold_filter(smem, p, eg0, eg1, tag, redo);
    }
    TS0(4);
    STOP(3);
#pragma unroll
    for (int i = 0; i < 3; i++) stg128_if(xout + i * G * THREADS, stage4[tid + i * THREADS], tid + i * THREADS < G * 8);
    if (warp == 14) asm volatile("cp.async.wait_all;" ::: "memory");
    __syncthreads();
#pragma unroll
    for (int i = 0; i < 4; i++) {
        const int c = tid + i * THREADS;
        const uint32_t x = c < (SN_OFF - SREC_OFF) / 16 ? 0u : 0xFFFFFFFFu;
        if (c < (CTL_OFF + 64 * TMAX - SREC_OFF) / 16) reinterpret_cast<uint4*>(smem + SREC_OFF)[c] = make_uint4(x, x, x, x);
    }
    STOP(4);
    uint32_t key[4];
    uint2 pr[4];
    const uint32_t gp = sb + GPOS_OFF + tid * 16;
    uint32_t pk = 0;
    if (warp == 15) {
        if (lane == 0) {
            int o = TOUCH2 * 8192;
#pragma unroll 1
            while (o < nn * 512 && !mbar_test(sb + BAR_OFF + 8, 0)) {
                const uint32_t bar = sb + BAR_OFF + 16 + 8 * (pk % FLIGHT);
                if (!mbar_test(bar, ~(pk / FLIGHT) & 1)) continue;
                const int n = min(4096, nn * 512 - o);
                mbar_expect_tx(bar, n);
                bulk_g2s(sb + DUMMY_OFF, own + o, n, bar);
                o += n;
                pk++;
            }
            misc[3] = pk;
        }
        __syncwarp();
        pk = __shfl_sync(0xffffffffu, pk, 0);
#pragma unroll
        for (int i = 0; i < EXITB; i++) touch((TOUCH2 + i) * 8192 + pk * 4096);
        STOP(5);
    } else {
    __nanosleep(PDELAY);
    TS0(5);

    {
        const int LPW = (G + 14) / 15;
        uint32_t ew[3][4], bad[3];
        const uint4* cp = p.g->xbuf + (b * G + warp * LPW) * 8 + lane;
#pragma unroll
        for (int i = 0; i < 3; i++) {
            bad[i] = lane + 32 * i < min(LPW, G - warp * LPW) * 8;
            ew[i][0] = ew[i][1] = ew[i][2] = ew[i][3] = (PAY_INVALID << 6) | tag;
        }
        int it = 0;
#pragma unroll 1
        do {
#pragma unroll
            for (int i = 0; i < 3; i++)
                asm volatile("{\n.reg .pred p;\nsetp.ne.u32 p, %5, 0;\n@p ld.relaxed.gpu.global.v4.u32 {%0,%1,%2,%3}, [%4];\n}\n"
                             : "+r"(ew[i][0]), "+r"(ew[i][1]), "+r"(ew[i][2]), "+r"(ew[i][3]) : "l"(cp + 32 * i), "r"(bad[i]) : "memory");
#pragma unroll
            for (int i = 0; i < 3; i++) bad[i] = ((ew[i][0] ^ tag) | (ew[i][1] ^ tag) | (ew[i][2] ^ tag) | (ew[i][3] ^ tag)) & 63u;
            if (++it > (1 << 22)) __trap();
        } while (__any_sync(0xffffffffu, bad[0] | bad[1] | bad[2]));
        STOP(5);
        TSX(21, 0); TSX(22, 448);
        uint4* pack = reinterpret_cast<uint4*>(smem + PACK_OFF);
        int nch = 0;
        uint32_t at[3];
#pragma unroll
        for (int i = 0; i < 3; i++) {
            const uint32_t m = __ballot_sync(0xffffffffu, ew[i][0] < (PAY_MARK << 6));
            at[i] = nch + __popc(m & ((1u << lane) - 1));
            nch += __popc(m);
        }
        if (__builtin_expect(nch > 32, 0)) {
#pragma unroll 1
            for (int i = 0; i < 3; i++) {
                if (ew[0][0] < (PAY_MARK << 6) && at[0] >= 32) at[0] = (15 - warp) * 32 - 1 - min(atomicAdd(&misc[1], 1u), 31u);
                const uint32_t x = at[0], y = ew[0][0];
                at[0] = at[1]; at[1] = at[2]; at[2] = x;
                ew[0][0] = ew[1][0]; ew[1][0] = ew[2][0]; ew[2][0] = y;
            }
        }
#pragma unroll
        for (int i = 0; i < 3; i++) {
            asm volatile("{\n.reg .pred p;\nsetp.lt.u32 p, %1, %5;\n@p st.shared.v4.u32 [%0], {%1,%2,%3,%4};\n}\n"
                         ::"r"(sb + PACK_OFF + (warp * 32 + at[i]) * 16), "r"(ew[i][0]), "r"(ew[i][1]), "r"(ew[i][2]), "r"(ew[i][3]), "n"(PAY_MARK << 6) : "memory");
            sts32_if(sb + MISC_OFF + 4 * 17, 1, (ew[i][3] >> 6) == PAY_MARK);
        }
        bool have = lane < nch;
        if (warp == 14) {
            asm volatile("bar.sync 7, 480;" ::: "memory");
            const uint32_t extra = misc[1];
            if (nch + extra > 32) misc[18] = 1;
            have = have || lane + extra >= 32;
        } else {
            asm volatile("bar.arrive 7, 480;" ::: "memory");
        }
        __syncwarp();
        uint32_t w[4], rk[4];
        bool in[4];
        {
            const uint4 x = pack[tid];
            w[0] = have ? x.x : ~0u; w[1] = have ? x.y : ~0u; w[2] = have ? x.z : ~0u; w[3] = have ? x.w : ~0u;
        }
        auto fetch = [&](int j, bool c) {
            asm volatile("{\n.reg .pred p;\nsetp.ne.u32 p, %2, 0;\n@p cp.async.cg.shared.global [%0], [%1], 16;\n}\n"
                         ::"r"(gp + j * 8192), "l"(reinterpret_cast<const uint4*>(p.g->pos8) + ((w[j] >> 16) & 0x7FFFu)), "r"((uint32_t)c) : "memory");
        };
#pragma unroll
        for (int j = 0; j < 4; j++) fetch(j, (int)w[j] < (int)(PAY_MARK << 6));
#pragma unroll
        for (int j = 0; j < 4; j++) pr[j] = reinterpret_cast<const uint2*>(smem + OPOS_OFF)[(w[j] >> 6) & 511u];
        asm volatile("cp.async.wait_all;" ::: "memory");
        TSX(23, 0); TSX(24, 448);
        asm volatile("{\n.reg .pred p;\nsetp.eq.u32 p, %1, 0;\n@p mbarrier.arrive.shared::cta.b64 _, [%0];\n}\n" ::"r"(sb + BAR_OFF + 8), "r"(lane) : "memory");
#pragma unroll
        for (int j = 0; j < 4; j++) {
            uint2 ps;
            asm volatile("ld.shared.v2.u32 {%0,%1}, [%2];" : "=r"(ps.x), "=r"(ps.y) : "r"(gp + j * 8192 + ((w[j] >> 12) & 8)) : "memory");
            in[j] = ((int)w[j] >= 0) | (((int)w[j] < (int)(PAY_MARK << 6)) & inside(hsub2(ps.x, pr[j].x), hsub2(ps.y, pr[j].y)));
        }
#pragma unroll
        for (int j = 0; j < 4; j++) rk[j] = atomicAdd(&ncnt[in[j] ? (w[j] >> 6) & 511u : 480 + lane], 1u);
#pragma unroll
        for (int j = 0; j < 4; j++) {
            rk[j] = rk[j] < SPL ? 2 * rk[j] : min(2 * rk[j] - (2 * SPL - 1), 63u);
            atomicAdd(&misc[in[j] && !(rk[j] & 2) ? 32 + (rk[j] >> 2) : 63], 1u);
            key[j] = in[j] ? ((w[j] >> 15) & 0xFFFFu) | ((w[j] << 10) & 0x1FF0000u) | (rk[j] << 25) : 0xF8000000u;
        }
#pragma unroll
        for (int j = 0; j < 4; j++) fetch(j, (int)w[j] >= 0);
    }
    }
    __syncthreads();
    TS0(6);
    if (tid == THREADS - 33) {
        if (b == 0) p.g->sync[0] = epoch + 1;
        asm volatile("fence.proxy.async.global;" ::: "memory");
        mbar_expect_tx(bar_tab, RING_OFF);
        bulk_g2s(sb, p.g->wimg, RING_OFF, bar_tab);
    }
    __syncwarp();
    STOP(6);
    uint32_t dst = sb + RING_OFF + warp * 12288 + (lane >> 3) * 256 + (((lane & 7) ^ (lane >> 3)) << 4), l7 = (lane & 7) * 16, g32 = (lane >> 2) * 32;
    uint32_t e0, e1, n0, n1;
    auto sources = [&](uint32_t c) {
        asm volatile("{\n.reg .b32 a;\nlop3.b32 a, %4, %5, 0xFFC0, 0xA8;\nshr.u32 a, a, 2;\nld.shared.v4.u32 {%0,%1,%2,%3}, [a + %6];\n}\n"
                     : "=r"(e0), "=r"(n0), "=r"(e1), "=r"(n1) : "r"(c), "r"(g32), "n"(SB + SN_OFF));
    };
    auto load_s = [&](auto pad) {
        gather<1, 0, pad.value>(dst, p.sv, l7, e0); gather<1, 1, pad.value>(dst + 1024, p.sv, l7, e0);
        gather<1, 0, pad.value>((dst ^ 64) + 128, p.sv, l7, e1); gather<1, 1, pad.value>((dst ^ 64) + 1152, p.sv, l7, e1);
    };
    auto load_o = [&]() {
        gather<4, 0>(dst + 8192, p.sv, l7, n0); gather<4, 0>((dst ^ 64) + 8320, p.sv, l7, n1);
    };
    auto load_v = [&](auto pad) {
        gather<3, 0, pad.value>(dst + 2048, p.sv, l7, e0); gather<3, 1, pad.value>(dst + 5120, p.sv, l7, e0);
        gather<3, 0, pad.value>((dst ^ 64) + 2176, p.sv, l7, e1); gather<3, 1, pad.value>((dst ^ 64) + 5248, p.sv, l7, e1);
        cp_commit();
    };
    const int ng = (misc[32] + 7) >> 3;
    const int give = max(min(ng - max((int)(misc[33] + 7) >> 3, 4 * NWG), GIVE), 0);
    if (warp == 15) {
        const uint32_t cnt = lane < 16 ? (misc[32 + lane] + 7) >> 3 : 0u;
        uint32_t z = cnt;
#pragma unroll
        for (int o = 1; o < 16; o <<= 1) {
            const uint32_t y = __shfl_up_sync(0xffffffffu, z, o);
            if (lane >= o) z += y;
        }
        misc[96 + lane] = lane < 16 ? 64 * (z - cnt) : 64 * (MAXROW + 1);
        asm volatile("bar.arrive 5, 512;" ::: "memory");
        if (lane == 15) {
            const bool cold = cnt || z > MAXROW || misc[31 + SPL / 2] > 32 || misc[17] || misc[18];
            misc[18] = cold;
            asm volatile("st.relaxed.gpu.global.u32 [%0], %1;" ::"l"(p.g->rows + b), "r"(~epoch << 16 | (cold ? 255 : give << 8 | z)) : "memory");
        }
        pk = (z - cnt) << 8 | __shfl_down_sync(0xffffffffu, cnt, 1) << 24;
    } else {
        if (warp * 32 < nn) {
            const uint32_t c = ncnt[tid], st = tid < nn ? (min(c, (uint32_t)SPL) + 1) >> 1 : 17u;
            const uint32_t same = __match_any_sync(0xffffffffu, st), first = __ffs(same) - 1;
            uint32_t r, node = nbase + tid;
            asm volatile("atom.shared.add.u32 %0, [%1], %2;" : "=r"(r)
                         : "r"(lane == first ? sb + MISC_OFF + 4 * (64 + st) : sb + NCNT_OFF + 4 * (480 + lane)), "r"(__popc(same)) : "memory");
            r = __shfl_sync(0xffffffffu, r, first) + __popc(same & ((1u << lane) - 1)) + misc[32 + st];
            if (__builtin_expect(c > SPL, 0)) {
                const uint32_t s2 = min((c - SPL + 1) >> 1, 16u), r2 = misc[32 + s2] + atomicAdd(&misc[64 + s2], 1u), k = atomicAdd(&misc[2], 1u);
                reinterpret_cast<uint32_t*>(smem + SCNT_OFF)[k & 31] = node;
                node |= NODE_SPLIT;
                ncnt[512 + tid] = 8 * r2;
                reinterpret_cast<uint32_t*>(smem + SN_OFF)[(r2 & 511) * 2 + 1] = node;
            }
            if (tid < nn) {
                ncnt[tid] = 8 * r;
                reinterpret_cast<uint32_t*>(smem + SN_OFF)[(r & 511) * 2 + 1] = node;
            }
        }
        asm volatile("bar.sync 5, 512;" ::: "memory");
        uint32_t slot[4];
#pragma unroll
        for (int j = 0; j < 4; j++) slot[j] = min(misc[96 + (key[j] >> 27)] + ncnt[(key[j] >> 16) & 1023], 64u * (MAXROW + 1)) + ((key[j] >> 25) & 2);
#pragma unroll
        for (int j = 0; j < 4; j++) {
            *reinterpret_cast<uint16_t*>(smem + SN_OFF + slot[j]) = (uint16_t)key[j];
            slot[j] += slot[j] & 2;
        }
        asm volatile("cp.async.wait_all;" ::: "memory");
        uint2 ps[4];
#pragma unroll
        for (int j = 0; j < 4; j++)
            asm volatile("ld.shared.v2.u32 {%0,%1}, [%2];" : "=r"(ps[j].x), "=r"(ps[j].y) : "r"(gp + j * 8192 + (key[j] & 1) * 8) : "memory");
        asm volatile("bar.sync 6, 480;" ::: "memory");
        TS0(7);
        if (warp < 4 * NWG) {
            sources((warp < ng ? warp : MAXROW) << 8);
            e0 = __vminu2(e0, (N - 1) * 0x10001u);
            e1 = __vminu2(e1, (N - 1) * 0x10001u);
            load_s(IntC<0>{});
            cp_commit();
            load_o();
            cp_commit();
        }
        TSX(9, 0);
#pragma unroll GUNROLL
        for (int i = 0; i < 2; i++) {
#pragma unroll
            for (int u = 0; u < 2; u++) {
                const uint3 geo = geometry(hsub2(ps[u].x, pr[u].x), hsub2(ps[u].y, pr[u].y));
                *reinterpret_cast<uint2*>(smem + SREC_OFF + 2 * slot[u]) = make_uint2(geo.x, geo.y);
                *reinterpret_cast<uint32_t*>(smem + SD_OFF + slot[u]) = geo.z;
                ps[u] = ps[u + 2];
                pr[u] = pr[u + 2];
                slot[u] = slot[u + 2];
            }
        }
    }
    if (warp == 15) { __syncwarp(); asm volatile("bar.arrive 4, 512;" ::: "memory"); }
    else asm volatile("bar.sync 4, 512;" ::: "memory");
    TS0(8);
    auto drain = [&](int i) { if (i < FLIGHT) mbar_wait(sb + BAR_OFF + 16 + 8 * i, ~((misc[3] + FLIGHT - 1 - i) / FLIGHT) & 1); };
    if (__builtin_expect(misc[18], 0)) {
        drain(warp);
        asm volatile("cp.async.wait_all;" ::: "memory");
        __syncthreads();
        cold_messages(smem, p, nn);
        mbar_wait(bar_tab, 1);
        return;
    }

    if (warp < 4 * NWG) {
        asm volatile("setmaxnreg.inc.sync.aligned.u32 %0;" ::"n"(REG_C));
        const int lane = fresh_lane();
        const int g = lane >> 2, q = lane & 3;
        const uint64_t dW1 = p.desc0, dW2 = dW1 + (W2_OFF >> 4), dWR = dW1 + (WR_OFF >> 4);
        const uint32_t ring = sb + RING_OFF + warp * 12288;
        const uint32_t vrow = pin(ring + g * 128 + ((q ^ ((g & 1) << 2) ^ (g >> 1)) << 4));
        const uint32_t mrow = pin(ring + (lane & 15) * 128 + (((lane >> 4) ^ ((lane & 1) << 2) ^ ((lane & 7) >> 1)) << 4));
        dst = pin(ring + (lane >> 3) * 256 + (((lane & 7) ^ (lane >> 3)) << 4)); l7 = pin((lane & 7) * 16); g32 = pin(g * 32);
        uint32_t ctl = sb + CTL_OFF + warp * 4;
        auto control = [&](uint32_t c, uint32_t at) {
            int it = 0;
#pragma unroll 1
            while (__builtin_expect(c == 0xFFFFFFFFu, 0)) {
                asm volatile("ld.volatile.shared.u32 %0, [%1];" : "=r"(c) : "r"(at) : "memory");
                c = __reduce_or_sync(0xffffffffu, c);
                if (++it > (1 << 24)) __trap();
            }
            return c;
        };
        uint32_t c0 = control(0xFFFFFFFFu, ctl), c1 = control(0xFFFFFFFFu, ctl + 64);
        if (warp >= 8) asm volatile("bar.arrive 1, 256;" ::: "memory");
        uint32_t acc[32];
        float P[32], W[32];
#pragma unroll
        for (int i = 0; i < 32; i++) { acc[i] = 0; P[i] = W[i] = 0.f; }
        mbar_wait(bar_tab, 1);
        sources(c0);
        e0 = __vminu2(e0, (N - 1) * 0x10001u);
        e1 = __vminu2(e1, (N - 1) * 0x10001u);
        if (warp >= VLATE) asm volatile("cp.async.wait_all;" ::: "memory");
        else if (warp >= VSOON) cp_wait1();
        load_v(IntC<0>{});
        uint32_t cp = 0, node = 0, a[16];
        auto finish = [&]() {
            if (cp & ST_CLOSE) {
                uint64_t op[2];
                asm("{\n.reg .b32 a;\nmad.lo.u32 a, %2, 512, %3;\nmad.wide.u32 %0, a, 1, %4;\nxor.b32 a, a, 64;\nmad.wide.u32 %1, a, 1, %4;\n}\n"
                    : "=l"(op[0]), "=l"(op[1]) : "r"(node), "r"(l7), "l"(p.out));
#pragma unroll
                for (int k = 0; k < 8; k++) {
                    uint32_t x[4];
#pragma unroll
                    for (int i = 0; i < 4; i++) x[i] = l7 & 64 ? acc[4 * (k ^ 1) + i] : acc[4 * k + i];
                    asm volatile("{\n.reg .pred p;\n.reg .b64 c;\nsetp.lt.u32 p, %5, %6;\n" STPRE "@p st.global" STPOL ".v4.u32 [%0], {%1,%2,%3,%4}" STSUF ";\n}\n"
                                 ::"l"(op[k & 1] + 128 * (k >> 1)), "r"(x[0]), "r"(x[1]), "r"(x[2]), "r"(x[3]), "r"(node), "n"(NODE_SPLIT) : "memory");
                }
                if (__builtin_expect(__any_sync(0xffffffffu, (int)node >= (int)NODE_SPLIT), 0)) {
                    mbar_wait(sb + BAR_OFF + 16 + 8 * FLIGHT, 0);
                    if ((int)node >= (int)NODE_SPLIT) {
#pragma unroll
                        for (int k = 0; k < 8; k++)
                            asm volatile("red.global.add.noftz.v4.bf16x2 [%0], {%1,%2,%3,%4};" ::"l"((op[0] & ~64ull) + 64 * k), "r"(acc[4 * k]), "r"(acc[4 * k + 1]), "r"(acc[4 * k + 2]), "r"(acc[4 * k + 3]) : "memory");
                    }
                    __syncwarp();
                }
            }
        };
#pragma unroll 1
        while ((int)c0 >= 0) {
            uint32_t h[16], rf[4], rr[4], m[16];
            TRW(ctl);
            RING(0);
            uint32_t dd[2], f01, f23;
            asm volatile("ld.shared.v2.u32 {%0,%1}, [%2 + %3];" : "=r"(dd[0]), "=r"(dd[1]) : "r"(((c0 & 0xFF00) | g32) >> 2), "n"(SB + SD_OFF));
            asm volatile("ld.shared.v2.u32 {%0,%1}, [%2 + %3];" : "=r"(f01), "=r"(f23) : "r"(l7), "n"(SB + FREQ_OFF));
            sources(c1);
            asm volatile("cp.async.wait_group 2;" ::: "memory");
            __syncwarp();
#pragma unroll
            for (int i = 0; i < 4; i++) ldsm4(mrow ^ (i << 5), a + 4 * i);
            wg_fence();
            wgmma_k64(P, a, dW1);
            wg_commit();
            RING(1);
            SPLIT(1);
#pragma unroll
            for (int hh = 0; hh < 2; hh++) {
                const float sc = bf_hi(dd[hh]);
                const uint32_t x01 = hmul2_lo(f01, dd[hh]), x23 = hmul2_lo(f23, dd[hh]);
                rf[hh] = pack2(__sinf(bf_lo(x01)) * sc, __sinf(bf_hi(x01)) * sc);
                rf[2 + hh] = pack2(__sinf(bf_lo(x23)) * sc, __sinf(bf_hi(x23)) * sc);
            }
            asm volatile("" : "+r"(rf[0]), "+r"(rf[1]), "+r"(rf[2]), "+r"(rf[3]));
            RING(2);
            SPLIT(2);
            wg_wait<0>();
            fence_regs(P);
#pragma unroll
            for (int i = 0; i < 16; i++)
                h[i] = pack2(fmaf(P[2 * i], tanh_fast(P[2 * i]), P[2 * i]), fmaf(P[2 * i + 1], tanh_fast(P[2 * i + 1]), P[2 * i + 1]));
            wg_fence();
            wgmma_k64(P, h, dW2 + 1024);
            wgmma_first(W, rf, dWR + 256);
            wg_commit();
            RING(3);
            SPLIT(3);
            cp_wait1();
            __syncwarp();
#pragma unroll
            for (int k = 0; k < 4; k++) lds2_if(vrow + 8192 + 1024 * k, (vrow ^ 64) + 8192 + 1024 * k, acc + 8 * k, c0 & ST_START);
            lds128(sb + SREC_OFF + (((c0 & 0xFF00) | g32) >> 1), rr);
            uint32_t c2 = lds32(ctl + 128);
            __syncwarp();
            load_s(IntC<1>{});
            cp_commit();
            if (c1 & ST_START) {
                load_o();
            }
            cp_commit();
            wg_wait<0>();
            fence_regs(P); fence_regs(W);
#pragma unroll
            for (int j = 0; j < 8; j++) {
                m[j] = pack2(P[4 * j] * W[4 * j], P[4 * j + 1] * W[4 * j + 1]);
                m[8 + j] = pack2(P[4 * j + 2] * W[4 * j + 2], P[4 * j + 3] * W[4 * j + 3]);
            }
            wg_fence();
            wgmma_k64(P, h, dW2);
            wgmma_first(W, rf, dWR);
            wg_commit();
            RING(4);
            SPLIT(4);
            PIN8(m); PIN8(m + 8);
            c2 = __reduce_or_sync(0xffffffffu, c2);
#pragma unroll
            for (int k = 1; k < 4; k++)
#pragma unroll
                for (int j = 0; j < 8; j++) {
                    const uint32_t x = k == 1 ? hfma2_lo(m[j], rr[0], acc[8 * k + j]) : k == 2 ? hfma2_hi(m[j], rr[0], acc[8 * k + j]) : hfma2_lo(m[j], rr[1], acc[8 * k + j]);
                    acc[8 * k + j] = k == 1 ? hfma2_lo(m[8 + j], rr[2], x) : k == 2 ? hfma2_hi(m[8 + j], rr[2], x) : hfma2_lo(m[8 + j], rr[3], x);
                }
            PIN8(acc + 8); PIN8(acc + 16); PIN8(acc + 24);
            RING(5);
            c2 = control(c2, ctl + 128);
            wg_wait<0>();
            fence_regs(P); fence_regs(W);
#pragma unroll
            for (int j = 0; j < 8; j++)
                acc[j] = hadd2(acc[j], pack2(fmaf(P[4 * j], W[4 * j], P[4 * j + 2] * W[4 * j + 2]), fmaf(P[4 * j + 1], W[4 * j + 1], P[4 * j + 3] * W[4 * j + 3])));
            wg_fence();
            wgmma_k64(P, h, dW2 + 512);
            wgmma_first(W, rf, dWR + 128);
            wg_commit();
            RING(6);
            SPLIT(6);
            asm volatile("cp.async.wait_group 2;" ::: "memory");
            __syncwarp();
            uint32_t v[4][16];
#pragma unroll
            for (int i = 0; i < NPRE; i++) lds128((vrow ^ (64 * (i & 1))) + 2048 + 1024 * (i >> 2) + 3072 * ((i >> 1) & 1), v[1 + (i >> 2)] + 4 * (i & 3));
            wg_wait<0>();
            fence_regs(P); fence_regs(W);
#pragma unroll
            for (int j = 0; j < 8; j++) {
                m[j] = pack2(P[4 * j] * W[4 * j], P[4 * j + 1] * W[4 * j + 1]);
                m[8 + j] = pack2(P[4 * j + 2] * W[4 * j + 2], P[4 * j + 3] * W[4 * j + 3]);
            }
#pragma unroll
            for (int i = NPRE; i < 12; i++) lds128((vrow ^ (64 * (i & 1))) + 2048 + 1024 * (i >> 2) + 3072 * ((i >> 1) & 1), v[1 + (i >> 2)] + 4 * (i & 3));
            sources(c1);
            node = lds32(sb + SN_OFF + 4 + (((c0 >> 16) | g32) >> 2));
            __syncwarp();
            load_v(IntC<1>{});
#pragma unroll
            for (int k = 1; k < 4; k++)
#pragma unroll
                for (int j = 0; j < 8; j++) acc[8 * k + j] = hfma2(m[8 + j], v[k][8 + j], hfma2(m[j], v[k][j], acc[8 * k + j]));
            ctl += 64;
            cp = c0;
            c0 = c1;
            c1 = c2;
            finish();
        }
        asm volatile("cp.async.wait_all;" ::: "memory");
        TRW(ctl);
        TSX(11, 0); TSX(12, 128); TSX(13, 256);
    } else {
        asm volatile("setmaxnreg.dec.sync.aligned.u32 %0;" ::"n"(REG_H));
        const int lane = fresh_lane();
        const uint32_t chunk = sb + (lane & 8 ? (lane & 4 ? SN_OFF : SD_OFF) + (lane & 3) * 16 : SREC_OFF + (lane & 7) * 16), pitch = lane & 8 ? 64 : 128;
        if (warp == 12) {
#pragma unroll 1
            for (int i = 0; i < (int)misc[2]; i++) {
                const uint32_t n = reinterpret_cast<const uint32_t*>(smem + SCNT_OFF)[i] * 32 + lane;
                reinterpret_cast<uint4*>(p.out)[n] = reinterpret_cast<const uint4*>(p.sv)[n];
            }
#pragma unroll 1
            for (int i = lane >> 4; i < give; i += 2) {
                uint32_t x[4];
                lds128(chunk + (ng - 1 - i) * pitch, x);
                p.g->pool[(b * GIVE + i) * 16 + (lane & 15)] = make_uint4(x[0], x[1], x[2], x[3]);
            }
            __threadfence();
            __syncwarp();
            if (lane == 0) {
                asm volatile("st.relaxed.gpu.global.u32 [%0], %1;" ::"l"(p.g->ready + b), "r"(~epoch) : "memory");
                mbar_arrive(sb + BAR_OFF + 16 + 8 * FLIGHT);
            }
        }
        if (warp == 15) {
            int k = lane < 4 * NWG ? lane : 255, next = 4 * NWG, j = 0, mine = ng - give, end = -1, take = 0;
            uint32_t busy, at = sb + CTL_OFF + 4 * lane, from = 0;
#pragma unroll 1
            do {
                if (next > mine && end < 0) {
                    end = mine = ng;
                    const int peer = b % 5 + 5 * lane;
                    uint32_t x = 255;
                    int it = 0;
                    if (peer < G) {
#pragma unroll 1
                        do {
                            asm volatile("ld.relaxed.gpu.global.u32 %0, [%1];" : "=r"(x) : "l"(p.g->rows + peer) : "memory");
                            if (++it > (1 << 22)) __trap();
                        } while ((x >> 16) != (~epoch & 0xFFFFu));
                    }
                    const int r = x & 255, n = __popc(__ballot_sync(0xffffffffu, r != 255));
                    const int level = min(((__reduce_add_sync(0xffffffffu, r != 255 ? r : 0) + n - 1) / n + 3) & ~3, MAXROW);
                    const uint32_t ed = r > level ? min(r - level, (int)(x >> 8) & 255) : min(level - r, ROOM) << 16;
                    uint32_t z = ed;
#pragma unroll
                    for (int o = 1; o < 32; o <<= 1) {
                        const uint32_t y = __shfl_up_sync(0xffffffffu, z, o);
                        if (lane >= o) z += y;
                    }
                    const uint32_t all = __shfl_sync(0xffffffffu, z, 31), moved = min(all & 0xFFFFu, all >> 16);
                    const uint32_t me = __shfl_sync(0xffffffffu, ed, b / 5), mz = __shfl_sync(0xffffffffu, z, b / 5) - me;
                    end = mine = ng - (min((mz + me) & 0xFFFFu, moved) - min(mz & 0xFFFFu, moved));
#pragma unroll 1
                    for (uint32_t u = mz >> 16; u < min((mz + me) >> 16, moved); u++, take++) {
                        const int f = __popc(__ballot_sync(0xffffffffu, (z & 0xFFFFu) <= u));
                        const uint32_t q = u - (__shfl_sync(0xffffffffu, z - ed, f) & 0xFFFFu);
                        if (lane == take) from = (b % 5 + 5 * f) << 8 | q;
                    }
                }
                if (next > mine && take) {
                    if (lane < take) {
                        uint32_t x;
                        int it = 0;
#pragma unroll 1
                        do {
                            asm volatile("ld.acquire.gpu.global.u32 %0, [%1];" : "=r"(x) : "l"(p.g->ready + (from >> 8)) : "memory");
                            if (++it > (1 << 22)) __trap();
                        } while (x != ~epoch);
                    }
                    __syncwarp();
#pragma unroll 1
                    for (end += take; take--;) {
                        const uint32_t f = __shfl_sync(0xffffffffu, from, take);
                        if (lane < 16)
                            asm volatile("cp.async.cg.shared.global [%0], [%1], 16;" ::"r"(chunk + (MAXROW - 1 - take) * pitch),
                                         "l"(p.g->pool + ((f >> 8) * GIVE + (f & 255)) * 16 + lane) : "memory");
                    }
                    take = 0;
                    asm volatile("cp.async.wait_all;" ::: "memory");
                    __threadfence_block();
                    __syncwarp();
                }
                const bool has = k < (end < 0 ? mine : end);
                const uint32_t i = k < mine ? k : MAXROW - 1 + mine - k, x = __shfl_sync(0xffffffffu, pk, j);
                const bool close = has && i >= (x >> 24);
                busy = __ballot_sync(0xffffffffu, has);
                const uint32_t m = __ballot_sync(0xffffffffu, close);
                uint32_t c = has ? ((x & 0xFF00) + i * 0x1000100) | (j ? 0u : ST_START) | (close ? ST_CLOSE : 0u) : MAXROW * 256;
                if (!(busy >> (lane & 12))) c |= 0x80000000u;
                c |= busy >> ((lane & 12) + 4) ? (lane & 12) * 4 + 32 : 16;
                sts32_if(at, c, lane < 16 || !busy);
                j = close ? 0 : j + 1;
                k = close ? next + __popc(m & ((1u << lane) - 1)) : k;
                next += __popc(m);
                at += 64;
            } while (busy);
        }
        if (warp == 15) mbar_wait(sb + BAR_OFF + 16 + 8 * FLIGHT, 0);
        else
        __nanosleep(ZDELAY);
        const int zend = misc[32] + misc[64];
#pragma unroll 1
        for (int r = 8 * ng + (warp & 3) * 4; r < zend; r += 16) {
            uint4 v[4];
            uint32_t n[4];
#pragma unroll
            for (int i = 0; i < 4; i++) {
                n[i] = reinterpret_cast<const uint32_t*>(smem + SN_OFF)[min(r + i, zend - 1) * 2 + 1] * 32 + lane;
                v[i] = __ldcg(reinterpret_cast<const uint4*>(p.sv) + n[i]);
            }
#pragma unroll
            for (int i = 0; i < 4; i++)
                if (r + i < zend) __stcs(reinterpret_cast<uint4*>(p.out) + n[i], v[i]);
        }
        static_assert(FLIGHT <= 8, "drain");
        drain(warp & 3);
        drain((warp & 3) + 4);
        asm volatile("cp.async.wait_all;" ::: "memory");
        TSX(14, 384);
    }
}

}

extern "C" void kernel_launch(void* const* d_in, const int* in_sizes, int n_in, void* d_out, int out_size) {
    static int s_G = 0;
    static void* s_scratch = nullptr;
    const int N = in_sizes[0] / 256, E = in_sizes[2];
    if (s_G == 0) {
        cudaFuncSetAttribute(painn_kernel<0, 0, 0>, cudaFuncAttributeMaxDynamicSharedMemorySize, SMEM_BYTES);
        cudaFuncSetAttribute(painn_kernel<50000, 800000, 132>, cudaFuncAttributeMaxDynamicSharedMemorySize, SMEM_BYTES);
        int dev = 0, sms = 0, occ = 0;
        cudaGetDevice(&dev);
        cudaDeviceGetAttribute(&sms, cudaDevAttrMultiProcessorCount, dev);
        cudaOccupancyMaxActiveBlocksPerMultiprocessor(&occ, painn_kernel<0, 0, 0>, THREADS, SMEM_BYTES);
        cudaGetSymbolAddress(&s_scratch, g_scratch);
        s_G = occ >= 1 ? (sms < MAXG ? sms : MAXG) : 0;
    }
    if (s_G == 0 || N > TABLE_MAXN || N > s_G * MAXNPC || (s_G - 1) * ((N + s_G - 1) / s_G) >= N || E > MAXE || E < 4 * MAXG * MAXG) return;
    Params p;
    p.g = (Scratch*)s_scratch;
    p.sv = (const __nv_bfloat16*)d_in[0];
    p.pos = (const __nv_bfloat16*)d_in[1];
    p.src = (const int*)d_in[2];
    p.dst = (const int*)d_in[3];
    p.freqs = (const __nv_bfloat16*)d_in[4];
    p.w1 = (const __nv_bfloat16*)d_in[5];
    p.w2 = (const __nv_bfloat16*)d_in[6];
    p.wr = (const __nv_bfloat16*)d_in[7];
    p.out = (__nv_bfloat16*)d_out;
    p.desc0 = (uint64_t)(SB >> 4) | ((uint64_t)1 << 16) | ((uint64_t)64 << 32) | ((uint64_t)1 << 62);
    p.N = N; p.E = E; p.G = s_G;
    p.NPC = (N + s_G - 1) / s_G;
    p.magic = (uint32_t)(((1ull << 32) + p.NPC - 1) / p.NPC);
    p.gpc = ((E >> 2) + s_G - 1) / s_G;
    p.odd_edges = (E & 3) != 0 || p.gpc > 3 * THREADS;
    if (N == 50000 && E == 800000 && s_G == 132) painn_kernel<50000, 800000, 132><<<s_G, THREADS, SMEM_BYTES, cudaStreamPerThread>>>(p);
    else painn_kernel<0, 0, 0><<<s_G, THREADS, SMEM_BYTES, cudaStreamPerThread>>>(p);
}
```

```cpp
#include <cuda_runtime.h>
#include <cuda_bf16.h>
#include <stdint.h>

namespace {

constexpr int NWG = 3;
constexpr int REG_C = 160, REG_H = 32;
constexpr int SPL = 10;
constexpr int GIVE = 10, ROOM = 4;
constexpr int BIG = 5;
constexpr int CUT = 4;
constexpr int TOUCH = 4, FLIGHT = 4;
constexpr int NPRE = 6;
constexpr int PDELAY = 150;
constexpr int ZDELAY = 1200;
constexpr int THREADS = 512;
constexpr int MAXG = 136;
constexpr int MAXROW = 96;
constexpr int TMAX = MAXROW / 12 + 18;
constexpr int MAXNPC = 480;
constexpr int MAXE = 1 << 20;

constexpr int W2_OFF = 8192;
constexpr int WR_OFF = 32768;
constexpr int RING_OFF = 38912;
constexpr int SREC_OFF = RING_OFF + 4 * NWG * 12288;
constexpr int SD_OFF = SREC_OFF + (MAXROW + 1) * 128 + 16;
constexpr int SN_OFF = SD_OFF + (MAXROW + 1) * 64 + 16;
constexpr int CTL_OFF = SN_OFF + (MAXROW + 1) * 64 + 16;
constexpr int TABLE_MAXN = 50176;
constexpr int STAGE_OFF = TABLE_MAXN * 4;
constexpr int SCNT_OFF = STAGE_OFF + MAXG * 128;
constexpr int PACK_OFF = RING_OFF + 6144;
constexpr int NCNT_OFF = SCNT_OFF + 768;
constexpr int OPOS_OFF = NCNT_OFF + 2048;
constexpr int BAR_OFF = OPOS_OFF + 4096;
constexpr int MISC_OFF = BAR_OFF + 128;
constexpr int FREQ_OFF = MISC_OFF + 512;
constexpr int DUMMY_OFF = (FREQ_OFF + 128 + 127) / 128 * 128;
constexpr int SMEM_BYTES = DUMMY_OFF + 4096;
static_assert(CTL_OFF + 64 * TMAX <= STAGE_OFF + 32 * THREADS && STAGE_OFF - SREC_OFF <= 32 * THREADS && 4 * (MAXG + 32) <= 768, "smem map");
static_assert(SMEM_BYTES <= 232448 && BAR_OFF % 8 == 0 && RING_OFF % 128 == 0 && SREC_OFF % 128 == 0 && (MAXG + 14) / 15 <= 12, "smem map");

constexpr uint32_t PAY_INVALID = 0x3FFFFFFu;
constexpr uint32_t PAY_MARK = 0x3FFFDFFu;
constexpr uint32_t NODE_SPLIT = 0x40000000u;
constexpr uint32_t ST_START = 1, ST_CLOSE = 2;
constexpr float QINVP = 9.0f / 510.0f;
constexpr uint32_t QTHRESH = 2209;
constexpr uint32_t QSURE = 1980;

struct Scratch {
    unsigned sync[32];
    uint4 table[TABLE_MAXN / 4];
    uint4 wimg[RING_OFF / 16];
    uint2 pos8[TABLE_MAXN];
    uint4 xbuf[MAXG * MAXG * 8 + 3 * THREADS];
    uint4 pool[MAXG * GIVE * 16];
    unsigned rows[MAXG];
    unsigned ready[MAXG];
    int ovfcnt[MAXG];
    int2 ovf[MAXE + 8 * MAXG + 8];
};
__device__ __align__(128) Scratch g_scratch;

struct Params {
    const __nv_bfloat16* pos;
    Scratch* g;
    const int* src;
    const int* dst;
    int N, NPC, E, gpc;
    const __nv_bfloat16* w2;
    const __nv_bfloat16* wr;
    const __nv_bfloat16* w1;
    const __nv_bfloat16* freqs;
    const __nv_bfloat16* sv;
    __nv_bfloat16* out;
    uint64_t desc0;
    int G;
    uint32_t magic;
    int odd_edges;
};
constexpr uint32_t SB = 1024;

#define TSX(i, thr)
#define TS0(i) TSX(i, 0)
#define TRW(ctl)

__device__ __forceinline__ uint32_t smem_u32(const void* p) { return (uint32_t)__cvta_generic_to_shared(p); }
__device__ __forceinline__ void mbar_init(uint32_t bar, uint32_t cnt) {
    asm volatile("mbarrier.init.shared::cta.b64 [%0], %1;" ::"r"(bar), "r"(cnt) : "memory");
}
__device__ __forceinline__ void mbar_arrive(uint32_t bar) {
    asm volatile("mbarrier.arrive.shared::cta.b64 _, [%0];" ::"r"(bar) : "memory");
}
__device__ __forceinline__ void mbar_expect_tx(uint32_t bar, uint32_t bytes) {
    asm volatile("mbarrier.arrive.expect_tx.shared::cta.b64 _, [%0], %1;" ::"r"(bar), "r"(bytes) : "memory");
}
__device__ __forceinline__ void mbar_wait(uint32_t bar, uint32_t parity) {
    uint32_t ok;
    int it = 0;
    do {
        asm volatile(
            "{\n.reg .pred p;\n"
            "mbarrier.try_wait.parity.shared::cta.b64 p, [%1], %2, 2000;\n"
            "selp.u32 %0, 1, 0, p;\n}\n"
            : "=r"(ok) : "r"(bar), "r"(parity) : "memory");
        if (++it > (1 << 20)) __trap();
    } while (!ok);
}
__device__ __forceinline__ uint32_t mbar_test(uint32_t bar, uint32_t parity) {
    uint32_t ok;
    asm volatile("{\n.reg .pred p;\nmbarrier.test_wait.parity.shared::cta.b64 p, [%1], %2;\nselp.u32 %0, 1, 0, p;\n}\n"
                 : "=r"(ok) : "r"(bar), "r"(parity) : "memory");
    return ok;
}
__device__ __forceinline__ uint32_t pin(uint32_t x) {
    uint32_t r;
    asm volatile("shfl.sync.bfly.b32 %0, %1, 0, 31, -1;" : "=r"(r) : "r"(x));
    return r;
}
__device__ __forceinline__ void bulk_g2s(uint32_t dst, const void* src, uint32_t bytes, uint32_t bar) {
    asm volatile("cp.async.bulk.shared::cluster.global.mbarrier::complete_tx::bytes [%0], [%1], %2, [%3];"
                 ::"r"(dst), "l"(src), "r"(bytes), "r"(bar) : "memory");
}
__device__ __forceinline__ void ldsm4(uint32_t addr, uint32_t* r) {
    asm volatile("ldmatrix.sync.aligned.m8n8.x4.shared.b16 {%0,%1,%2,%3}, [%4];"
                 : "=r"(r[0]), "=r"(r[1]), "=r"(r[2]), "=r"(r[3]) : "r"(addr) : "memory");
}
__device__ __forceinline__ uint32_t pack2(float lo, float hi) {
    uint32_t r;
    asm("cvt.rn.bf16x2.f32 %0, %1, %2;" : "=r"(r) : "f"(hi), "f"(lo));
    return r;
}
__device__ __forceinline__ float bf_lo(uint32_t w) { return __uint_as_float(w << 16); }
__device__ __forceinline__ float bf_hi(uint32_t w) { return __uint_as_float(w & 0xFFFF0000u); }
__device__ __forceinline__ float rbf16(float x) { return __uint_as_float(pack2(0.f, x)); }
__device__ __forceinline__ uint32_t hmul2(uint32_t a, uint32_t b) {
    uint32_t r;
    asm("mul.rn.bf16x2 %0, %1, %2;" : "=r"(r) : "r"(a), "r"(b));
    return r;
}
__device__ __forceinline__ uint32_t hfma2(uint32_t a, uint32_t b, uint32_t c) {
    uint32_t r;
    asm("fma.rn.bf16x2 %0, %1, %2, %3;" : "=r"(r) : "r"(a), "r"(b), "r"(c));
    return r;
}
__device__ __forceinline__ uint32_t hfma2_lo(uint32_t a, uint32_t b, uint32_t c) {
    uint32_t r;
    asm("{\n.reg .b16 l, h;\n.reg .b32 t;\nmov.b32 {l, h}, %2;\nmov.b32 t, {l, l};\nfma.rn.bf16x2 %0, %1, t, %3;\n}\n" : "=r"(r) : "r"(a), "r"(b), "r"(c));
    return r;
}
__device__ __forceinline__ uint32_t hfma2_hi(uint32_t a, uint32_t b, uint32_t c) {
    uint32_t r;
    asm("{\n.reg .b16 l, h;\n.reg .b32 t;\nmov.b32 {l, h}, %2;\nmov.b32 t, {h, h};\nfma.rn.bf16x2 %0, %1, t, %3;\n}\n" : "=r"(r) : "r"(a), "r"(b), "r"(c));
    return r;
}
__device__ __forceinline__ uint32_t hadd2(uint32_t a, uint32_t b) {
    uint32_t r;
    asm("add.rn.bf16x2 %0, %1, %2;" : "=r"(r) : "r"(a), "r"(b));
    return r;
}
__device__ __forceinline__ uint32_t hsub2(uint32_t a, uint32_t b) {
    uint32_t r;
    asm("sub.rn.bf16x2 %0, %1, %2;" : "=r"(r) : "r"(a), "r"(b));
    return r;
}
__device__ __forceinline__ float tanh_fast(float x) {
    float r;
    asm("tanh.approx.f32 %0, %1;" : "=f"(r) : "f"(x));
    return r;
}
__device__ __forceinline__ void wg_fence() { asm volatile("wgmma.fence.sync.aligned;" ::: "memory"); }
__device__ __forceinline__ void wg_commit() { asm volatile("wgmma.commit_group.sync.aligned;" ::: "memory"); }
template <int N>
__device__ __forceinline__ void wg_wait() { asm volatile("wgmma.wait_group.sync.aligned %0;" ::"n"(N) : "memory"); }

#define WG_REGS "{%0,%1,%2,%3,%4,%5,%6,%7,%8,%9,%10,%11,%12,%13,%14,%15,%16,%17,%18,%19,%20,%21,%22,%23,%24,%25,%26,%27,%28,%29,%30,%31}"
#define WG_OPS(c) c(d[0]), c(d[1]), c(d[2]), c(d[3]), c(d[4]), c(d[5]), c(d[6]), c(d[7]), c(d[8]), c(d[9]), c(d[10]), \
    c(d[11]), c(d[12]), c(d[13]), c(d[14]), c(d[15]), c(d[16]), c(d[17]), c(d[18]), c(d[19]), c(d[20]), c(d[21]),     \
    c(d[22]), c(d[23]), c(d[24]), c(d[25]), c(d[26]), c(d[27]), c(d[28]), c(d[29]), c(d[30]), c(d[31])
__device__ __forceinline__ void wgmma_first(float* d, const uint32_t* a, uint64_t desc) {
    asm volatile("wgmma.mma_async.sync.aligned.m64n64k16.f32.bf16.bf16 " WG_REGS ", {%32,%33,%34,%35}, %36, 0, 1, 1, 1;"
                 : WG_OPS("+f") : "r"(a[0]), "r"(a[1]), "r"(a[2]), "r"(a[3]), "l"(desc));
}
__device__ __forceinline__ void wgmma_acc(float* d, const uint32_t* a, uint64_t desc) {
    asm volatile("wgmma.mma_async.sync.aligned.m64n64k16.f32.bf16.bf16 " WG_REGS ", {%32,%33,%34,%35}, %36, 1, 1, 1, 1;"
                 : WG_OPS("+f") : "r"(a[0]), "r"(a[1]), "r"(a[2]), "r"(a[3]), "l"(desc));
}
__device__ __forceinline__ void wgmma_k64(float* d, const uint32_t* a, uint64_t desc) {
    wgmma_first(d, a, desc);
    wgmma_acc(d, a + 4, desc + 128);
    wgmma_acc(d, a + 8, desc + 256);
    wgmma_acc(d, a + 12, desc + 384);
}
__device__ __forceinline__ void fence_regs(float* d) { asm volatile("" : WG_OPS("+f")::"memory"); }
__device__ __forceinline__ uint32_t qaxis(float x) {
    const float u = fmaf(x, QINVP, 0.25f);
    const float f = u - ((u + 12582912.f) - 12582912.f);
    return __float_as_uint(fmaf(fabsf(f), 510.f, 12582912.f));
}
__device__ __forceinline__ uint32_t qcode(float x, float y, float z, uint32_t tx) {
    return __byte_perm(__byte_perm(qaxis(x), qaxis(y), 0x3340), qaxis(z), 0x3410) ^ tx;
}
__device__ __forceinline__ bool near_test(uint32_t ca, uint32_t cb, uint32_t tag24, uint32_t& q) {
    const uint32_t D = __vabsdiffu4(ca, cb);
    q = __dp4a(D, D, 0x7FFFFFFFu - QSURE);
    return q <= 0x7FFFFFFFu - QSURE + QTHRESH || ((ca ^ tag24) | (cb ^ tag24)) >= 0x1000000u;
}
__device__ __forceinline__ bool inside(uint32_t rxy, uint32_t rz) {
    const uint32_t qxy = hmul2(rxy, rxy), qz = hmul2(rz, rz);
    return bf_lo(qxy) + bf_hi(qxy) + bf_lo(qz) <= 24.8125f;
}

__device__ __forceinline__ uint32_t lds32(uint32_t addr) {
    uint32_t r;
    asm volatile("ld.shared.u32 %0, [%1];" : "=r"(r) : "r"(addr));
    return r;
}
__device__ __forceinline__ void sts32_if(uint32_t addr, uint32_t v, bool c) {
    asm volatile("{\n.reg .pred p;\nsetp.ne.u32 p, %2, 0;\n@p st.shared.u32 [%0], %1;\n}\n" ::"r"(addr), "r"(v), "r"((uint32_t)c) : "memory");
}
__device__ __forceinline__ void stg128_if(void* ptr, uint4 v, bool c) {
    asm volatile("{\n.reg .pred p;\nsetp.ne.u32 p, %5, 0;\n@p st.relaxed.gpu.global.v4.u32 [%0], {%1,%2,%3,%4};\n}\n"
                 ::"l"(ptr), "r"(v.x), "r"(v.y), "r"(v.z), "r"(v.w), "r"((uint32_t)c) : "memory");
}
__device__ __forceinline__ void lds128(uint32_t addr, uint32_t* r) {
    asm volatile("ld.shared.v4.u32 {%0,%1,%2,%3}, [%4];" : "=r"(r[0]), "=r"(r[1]), "=r"(r[2]), "=r"(r[3]) : "r"(addr) : "memory");
}
template <int NP, int HI, int PAD = 1>
__device__ __forceinline__ void gather(uint32_t dst, const void* base, uint32_t c, uint32_t e) {
#define GATHER_HEAD "{\n.reg .pred p;\n.reg .b32 n;\n.reg .b64 a;\nprmt.b32 n, %2, 0, %3;\nsetp.ne.u32 p, n, 0xFFFF;\nmad.lo.u32 n, n, 512, %4;\nmad.wide.u32 a, n, 1, %1;\n"
#define GATHER_1(P) P "cp.async.cg.shared.global [%0], [a], 16;\n}\n"
#define GATHER_3(P) P "cp.async.cg.shared.global [%0], [a + 128], 16;\n" P "cp.async.cg.shared.global [%0 + 1024], [a + 256], 16;\n" \
                    P "cp.async.cg.shared.global [%0 + 2048], [a + 384], 16;\n}\n"
#define GATHER_ARGS(z) ::"r"(dst), "l"(base), "r"(e), "n"((HI ? 0x32 : 0x10) + z), "r"(c) : "memory"
    if constexpr (NP == 1 && PAD) asm volatile(GATHER_HEAD GATHER_1("@p ") GATHER_ARGS(0x4400));
    if constexpr (NP == 1 && !PAD) asm volatile(GATHER_HEAD GATHER_1("") GATHER_ARGS(0x4400));
    if constexpr (NP == 3 && PAD) asm volatile(GATHER_HEAD GATHER_3("@p ") GATHER_ARGS(0x5500));
    if constexpr (NP == 3 && !PAD) asm volatile(GATHER_HEAD GATHER_3("") GATHER_ARGS(0x4400));
    if constexpr (NP == 4)
        asm volatile(GATHER_HEAD "setp.ge.u32 p, %2, 0x40000000;\ncp.async.cg.shared.global [%0], [a], 16, p;\ncp.async.cg.shared.global [%0 + 1024], [a + 128], 16, p;\n"
                     "cp.async.cg.shared.global [%0 + 2048], [a + 256], 16, p;\ncp.async.cg.shared.global [%0 + 3072], [a + 384], 16, p;\n}\n" GATHER_ARGS(0x4400));
}
__device__ __forceinline__ void cp_commit() { asm volatile("cp.async.commit_group;" ::: "memory"); }
__device__ __forceinline__ void cp_wait1() { asm volatile("cp.async.wait_group 1;" ::: "memory"); }
__device__ __forceinline__ uint32_t hmul2_lo(uint32_t a, uint32_t b) {
    uint32_t r;
    asm("{\n.reg .b16 l, h;\n.reg .b32 t;\nmov.b32 {l, h}, %2;\nmov.b32 t, {l, l};\nmul.rn.bf16x2 %0, %1, t;\n}\n" : "=r"(r) : "r"(a), "r"(b));
    return r;
}
__device__ __forceinline__ void lds2_if(uint32_t a0, uint32_t a1, uint32_t* r, uint32_t c) {
    asm volatile("{\n.reg .pred p;\nsetp.ne.u32 p, %10, 0;\n@p ld.shared.v4.u32 {%0,%1,%2,%3}, [%8];\n@p ld.shared.v4.u32 {%4,%5,%6,%7}, [%9];\n}\n"
                 : "+r"(r[0]), "+r"(r[1]), "+r"(r[2]), "+r"(r[3]), "+r"(r[4]), "+r"(r[5]), "+r"(r[6]), "+r"(r[7])
                 : "r"(a0), "r"(a1), "r"(c) : "memory");
}
__device__ __forceinline__ int fresh_lane() {
    int l;
    asm volatile("mov.u32 %0, %%laneid;" : "=r"(l));
    return l;
}

__device__ __forceinline__ void cold_edges(unsigned char* smem, const Params& p, int lo, int hi, uint32_t tag) {
#pragma unroll 1
    for (int e = lo + threadIdx.x; e < hi; e += THREADS) {
        const int s = p.src[e], d = p.dst[e];
        uint32_t q;
        if (near_test(reinterpret_cast<const uint32_t*>(smem)[s], reinterpret_cast<const uint32_t*>(smem)[d], tag << 24, q)) {
            const uint32_t own = __umulhi((uint32_t)d, p.magic);
            const uint32_t slot4 = atomicAdd(reinterpret_cast<uint32_t*>(smem + SCNT_OFF) + own, 4u);
            uint32_t* line = reinterpret_cast<uint32_t*>(smem + STAGE_OFF) + own * 32;
            if (slot4 < 124) {
                line[slot4 >> 2] = ((uint32_t)s << 15) + ((uint32_t)(d - own * p.NPC) << 6) + tag + (q & 0x80000000u);
            } else {
                uint32_t o = atomicAdd(reinterpret_cast<uint32_t*>(smem + MISC_OFF) + 16, 1u);
                p.g->ovf[(size_t)blockIdx.x * (4 * p.gpc + 4) + o] = make_int2(s, d);
                line[31] = (PAY_MARK << 6) | tag;
            }
        }
    }
}
__device__ __forceinline__ void cold_filter(unsigned char* smem, const Params& p, int e0, int e1, uint32_t tag, int redo) {
    if (redo) {
        if (threadIdx.x < MAXG) reinterpret_cast<uint32_t*>(smem + SCNT_OFF)[threadIdx.x] = 0;
        __syncthreads();
    }
    cold_edges(smem, p, redo ? 4 * e0 : 4 * (e0 + 3 * THREADS), 4 * e1, tag);
    if (blockIdx.x == 0) cold_edges(smem, p, p.E & ~3, p.E, tag);
    __syncthreads();
    if (threadIdx.x == 0) p.g->ovfcnt[blockIdx.x] = reinterpret_cast<uint32_t*>(smem + MISC_OFF)[16];
    __threadfence();
    __syncthreads();
}
__device__ __forceinline__ uint3 geometry(uint32_t rxy, uint32_t rz) {
    const uint32_t qxy = hmul2(rxy, rxy), qz = hmul2(rz, rz);
    float d, id;
    asm("sqrt.approx.ftz.f32 %0, %1;" : "=f"(d) : "f"(rbf16(rbf16(bf_lo(qxy) + bf_hi(qxy) + bf_lo(qz)) + 1e-8f)));
    d = rbf16(d);
    asm("rcp.approx.ftz.f32 %0, %1;" : "=f"(id) : "f"(d));
    const float cs = rbf16(__cosf(rbf16(rbf16(3.14159265358979f * d) * 0.2f)));
    const uint32_t zs = pack2(bf_lo(rz) * id, 0.5f * rbf16(cs + 1.0f) * id);
    return d < 5.0f ? make_uint3(pack2(bf_lo(rxy) * id, bf_hi(rxy) * id), zs, __byte_perm(__float_as_uint(d), zs, 0x7632)) : make_uint3(0, 0, 0);
}
__device__ __forceinline__ void cold_messages(unsigned char* smem, const Params& p, int nn) {
    const int nbase = blockIdx.x * p.NPC, lane = threadIdx.x & 31;
    const uint32_t* box = reinterpret_cast<const uint32_t*>(p.g->xbuf) + blockIdx.x * p.G * 32;
    uint32_t* w = reinterpret_cast<uint32_t*>(smem + RING_OFF);
#pragma unroll 1
    for (int i = threadIdx.x; i < 9728; i += THREADS)
        w[i] = i < 2048 ? reinterpret_cast<const uint32_t*>(p.w1)[i] : i < 8192 ? reinterpret_cast<const uint32_t*>(p.w2)[i - 2048] : reinterpret_cast<const uint32_t*>(p.wr)[i - 8192];
#pragma unroll 1
    for (int i = threadIdx.x; i < nn * 32; i += THREADS) reinterpret_cast<uint4*>(p.out)[nbase * 32 + i] = reinterpret_cast<const uint4*>(p.sv)[nbase * 32 + i];
    __threadfence();
    __syncthreads();
    const float freq = __bfloat162float(p.freqs[lane & 15]);
#pragma unroll 1
    for (int m = -1; m < p.G; m++) {
        const int cnt = m < 0 ? p.G * 32 : (__ldcg(box + m * 32 + 31) >> 6) == PAY_MARK ? __ldcg(&p.g->ovfcnt[m]) : 0;
#pragma unroll 1
        for (int i = threadIdx.x; i - lane < cnt; i += THREADS) {
            int2 e = make_int2(0, -1);
            if (i < cnt) {
                if (m < 0) {
                    const uint32_t x = __ldcg(box + i);
                    e = make_int2((x >> 15) & 0xFFFFu, nbase + ((x >> 6) & 511u));
                } else {
                    e = __ldcg(p.g->ovf + (size_t)m * (4 * p.gpc + 4) + i);
                }
            }
            bool in = (uint32_t)(e.y - nbase) < (uint32_t)nn;
            uint3 geo = make_uint3(0, 0, 0);
            if (in) {
                const uint2 ps = __ldcg(p.g->pos8 + e.x), pd = __ldcg(p.g->pos8 + e.y);
                const uint32_t rxy = hsub2(ps.x, pd.x), rz = hsub2(ps.y, pd.y);
                in = inside(rxy, rz);
                geo = geometry(rxy, rz);
            }
#pragma unroll 1
            for (uint32_t todo = __ballot_sync(0xffffffffu, in); todo; todo &= todo - 1) {
                const int l = __ffs(todo) - 1;
                const uint32_t* row = reinterpret_cast<const uint32_t*>(p.sv) + (size_t)__shfl_sync(0xffffffffu, e.x, l) * 128 + lane;
                uint32_t* orow = reinterpret_cast<uint32_t*>(p.out) + (size_t)__shfl_sync(0xffffffffu, e.y, l) * 128 + lane;
                const uint32_t gx = __shfl_sync(0xffffffffu, geo.x, l), gy = __shfl_sync(0xffffffffu, geo.y, l);
                const float rb = rbf16(__sinf(rbf16(bf_lo(__shfl_sync(0xffffffffu, geo.z, l)) * freq)) * bf_hi(gy));
                uint32_t x = row[0];
                float a[12] = {0, 0, 0, 0, 0, 0, 0, 0, 0, 0, 0, 0};
#pragma unroll 2
                for (int k = 0; k < 64; k++) {
                    const uint32_t u = __shfl_sync(0xffffffffu, x, k >> 1), ww = w[k * 32 + lane];
                    const float f = k & 1 ? bf_hi(u) : bf_lo(u);
                    a[0] = fmaf(f, bf_lo(ww), a[0]); a[1] = fmaf(f, bf_hi(ww), a[1]);
                }
                x = pack2(0.5f * fmaf(a[0], tanh_fast(0.5f * a[0]), a[0]), 0.5f * fmaf(a[1], tanh_fast(0.5f * a[1]), a[1]));
                a[0] = a[1] = 0.f;
#pragma unroll 2
                for (int k = 0; k < 64; k++) {
                    const uint32_t u = __shfl_sync(0xffffffffu, x, k >> 1);
                    const float f = k & 1 ? bf_hi(u) : bf_lo(u), r = __shfl_sync(0xffffffffu, rb, k & 15);
#pragma unroll
                    for (int c = 0; c < 3; c++) {
                        const uint32_t ww = w[2048 + k * 96 + c * 32 + lane], wr = k < 16 ? w[8192 + k * 96 + c * 32 + lane] : 0u;
                        a[2 * c] = fmaf(f, bf_lo(ww), a[2 * c]); a[2 * c + 1] = fmaf(f, bf_hi(ww), a[2 * c + 1]);
                        a[6 + 2 * c] = fmaf(r, bf_lo(wr), a[6 + 2 * c]); a[7 + 2 * c] = fmaf(r, bf_hi(wr), a[7 + 2 * c]);
                    }
                }
                const uint32_t mv = pack2(a[2] * a[8], a[3] * a[9]), mr = pack2(a[4] * a[10], a[5] * a[11]);
                const uint32_t o[4] = {pack2(a[0] * a[6], a[1] * a[7]), hfma2_lo(mr, gx, hmul2(mv, row[32])), hfma2_hi(mr, gx, hmul2(mv, row[64])),
                                       hfma2_lo(mr, gy, hmul2(mv, row[96]))};
#pragma unroll
                for (int c = 0; c < 4; c++) asm volatile("red.global.add.noftz.bf16x2 [%0], %1;" ::"l"(orow + 32 * c), "r"(o[c]) : "memory");
            }
        }
    }
}

#define SPLIT(k) asm volatile("{\n.reg .pred p;\nsetp.eq.u32 p, %0, %1;\n@p trap;\n}" ::"r"(c0), "n"(0x70000 + k) : "memory")
#define PIN8(a) asm volatile("" : "+r"((a)[0]), "+r"((a)[1]), "+r"((a)[2]), "+r"((a)[3]), "+r"((a)[4]), "+r"((a)[5]), "+r"((a)[6]), "+r"((a)[7]))
template <int V> struct IntC { static constexpr int value = V; };

template <int CN, int CE, int CG>
__global__ void __launch_bounds__(THREADS, 1) painn_kernel(const __grid_constant__ Params p) {
    extern __shared__ __align__(1024) unsigned char smem_dyn[];
    unsigned char* const smem = static_cast<unsigned char*>(__cvta_shared_to_generic(SB));
    constexpr uint32_t sb = SB;
    const int tid = threadIdx.x, lane = tid & 31;
    const int warp = __shfl_sync(0xffffffffu, tid >> 5, 0);
    constexpr int CNPC = CG ? (CN + CG - 1) / CG : 1, CGPC = CG ? (CE / 4 + CG - 1) / CG : 1;
    const int b = blockIdx.x, G = CG ? CG : p.G, NPC = CG ? CNPC : p.NPC, N = CG ? CN : p.N, gpc = CG ? CGPC : p.gpc;
    const uint32_t magic = CG ? (uint32_t)(((1ull << 32) + CNPC - 1) / CNPC) : p.magic;
    const bool odd_edges = CG ? (CE & 3) != 0 || CGPC > 3 * THREADS : p.odd_edges;
    const int nbase = b * NPC, nn = min(NPC, N - nbase);
    const int eg0 = b * gpc, eg1 = min((CG ? CE : p.E) >> 2, eg0 + gpc);

    uint4* stage4 = reinterpret_cast<uint4*>(smem + STAGE_OFF);
    uint32_t* ncnt = reinterpret_cast<uint32_t*>(smem + NCNT_OFF);
    uint32_t* misc = reinterpret_cast<uint32_t*>(smem + MISC_OFF);
    const uint32_t bar_tab = sb + BAR_OFF;

    TS0(0);
    int4 es[3], ed[3];
    auto load_edges = [&](int i) {
        const int g = min(eg0 + tid + i * THREADS, eg1 - 1);
        asm volatile("ld.global.cs.v4.u32 {%0,%1,%2,%3}, [%8];\nld.global.cs.v4.u32 {%4,%5,%6,%7}, [%9];"
                     : "=r"(es[i].x), "=r"(es[i].y), "=r"(es[i].z), "=r"(es[i].w), "=r"(ed[i].x), "=r"(ed[i].y), "=r"(ed[i].z), "=r"(ed[i].w)
                     : "l"(reinterpret_cast<const int4*>(p.src) + g), "l"(reinterpret_cast<const int4*>(p.dst) + g) : "memory");
    };
    const char* const own = reinterpret_cast<const char*>(p.sv) + (size_t)nbase * 512;
    auto touch = [&](int o) {
        if (o + lane * 256 < nn * 512)
            asm volatile("cp.async.ca.shared.global.L2::256B [%0], [%1], 4;" ::"r"(sb + DUMMY_OFF + 4 * lane), "l"(own + o + lane * 256) : "memory");
    };
    uint4* const xout = p.g->xbuf + ((tid >> 3) * G + b) * 8 + (tid & 7);
    unsigned epoch;
    const uint32_t tbytes = ((N + 3) >> 2) * 16, cut = (tbytes >> 8) * CUT * 16, bar_cut = sb + BAR_OFF + 120;
    {
        uint32_t pxy, pz;
        asm volatile("ld.global.nc.u32 %0, [%3];\nld.global.nc.u32 %1, [%3 + 4];\nld.global.ca.u32 %2, [%4];"
                     : "=r"(pxy), "=r"(pz), "=r"(epoch)
                     : "l"(reinterpret_cast<const uint32_t*>(p.pos) + ((nbase + min(tid, nn - 1)) * 3 >> 1)), "l"(p.g->sync) : "memory");
        const uint32_t sh = ((nbase + tid) & 1) << 4;
        pxy = __funnelshift_r(pxy, pz, sh);
        pz >>= sh;
        if (tid < nn) {
            reinterpret_cast<uint32_t*>(p.g->table)[nbase + tid] = qcode(bf_lo(pxy), bf_hi(pxy), bf_lo(pz), ((epoch & 31u) ^ 0x6Bu) << 24);
            p.g->pos8[nbase + tid] = make_uint2(pxy, pz);
        }
        reinterpret_cast<uint2*>(smem + OPOS_OFF)[tid] = make_uint2(pxy, pz);
        if (pxy == 0xFFFFFFFFu && pz == 0xFFFFFFFFu && epoch == 0xFFFFFFFFu) asm volatile("nanosleep.u32 0;");
        load_edges(0);
    }
    __syncthreads();
    const uint32_t tag = (epoch & 31u) | 32u;
    if (tid == THREADS - 1) {
        asm volatile("red.relaxed.gpu.global.add.u32 [%0], 1;" ::"l"(p.g->sync + 1) : "memory");
        TSX(1, 511);
        mbar_init(bar_tab, 1);
        mbar_init(bar_cut, 1);
        mbar_expect_tx(bar_cut, cut);
        mbar_expect_tx(bar_tab, tbytes - cut);
        const unsigned want = (epoch + 1) * G;
        unsigned c;
        int it = smem_u32(smem_dyn) == SB ? 0 : 1 << 22;
        do {
            asm volatile("ld.relaxed.gpu.global.u32 %0, [%1];" : "=r"(c) : "l"(p.g->sync + 1) : "memory");
            if (++it > (1 << 22)) __trap();
        } while (c != want);
        bulk_g2s(sb, p.g->table, cut, bar_cut);
        bulk_g2s(sb + cut, reinterpret_cast<const char*>(p.g->table) + cut, tbytes - cut, bar_tab);
        TSX(2, 511);
    }
    if (warp == 14) {
#pragma unroll 1
        for (int c = b * 32 + lane; c < RING_OFF / 16; c += G * 32) {
            const int row = c >> 3, j = (c ^ row) & 7;
            uint4 v;
            if (c < 512) {
                const uint32_t half = 0x3F003F00u;
                v = __ldg(reinterpret_cast<const uint4*>(p.w1) + row * 8 + j);
                v = make_uint4(hmul2(v.x, half), hmul2(v.y, half), hmul2(v.z, half), hmul2(v.w, half));
            } else {
                const uint32_t* q = (c < 2048 ? reinterpret_cast<const uint32_t*>(p.w2) + (row & 63) * 96 + ((row >> 6) - 1) * 32
                                              : reinterpret_cast<const uint32_t*>(p.wr) + (row & 15) * 96 + ((row >> 4) - 16) * 32) + (j & 4) * 4 + (j & 3);
                v = make_uint4(__ldg(q), __ldg(q + 4), __ldg(q + 8), __ldg(q + 12));
            }
            p.g->wimg[c] = v;
        }
    }
    if (tid == 416) {
#pragma unroll
        for (int i = 0; i < FLIGHT + 2; i++) mbar_init(sb + BAR_OFF + 8 + 8 * i, i ? 1 : 15);
    }
    ncnt[tid] = 0;
    if (tid < MAXG + 32) reinterpret_cast<uint32_t*>(smem + SCNT_OFF)[tid] = tid < MAXG ? 0 : 128;
    if (tid < 128) misc[tid] = 0;
    {
        const uint32_t inv = (PAY_INVALID << 6) | tag;
        stage4[tid] = stage4[tid + THREADS] = make_uint4(inv, inv, inv, inv);
        if (tid < MAXG * 8 - 2 * THREADS) stage4[tid + 2 * THREADS] = make_uint4(inv, inv, inv, inv);
    }
    __syncthreads();
    if ((tid >> 4) == 29) asm volatile("cp.async.ca.shared.global [%0], [%1], 4;" ::"r"(sb + FREQ_OFF + 8 * (tid & 14) + 4 * (tid & 1)),
                              "l"(reinterpret_cast<const uint32_t*>(p.freqs) + ((tid & 7) >> 1) + (tid & 1) * 4) : "memory");
    load_edges(1);
    if (warp != 13) mbar_wait(bar_cut, 0);
    load_edges(2);
    if (tid == 416) asm volatile("fence.acq_rel.gpu;" ::: "memory");
#pragma unroll
    for (int i = 0; i < 3; i++) stg128_if(xout + i * G * THREADS, make_uint4(0, 0, 0, 0), tid + i * THREADS < G * 8);
    if (warp == 13) mbar_wait(bar_cut, 0);
    mbar_wait(bar_tab, 0);
    TS0(3);
    if (warp == 15) {
#pragma unroll
        for (int i = 0; i < TOUCH; i++) touch(i * 8192);
    }

    bool full = false;
#pragma unroll 1
    for (int i = 0, g = eg0 + tid; i < 3; i++, g += THREADS) {
        const int s[4] = {es[0].x, es[0].y, es[0].z, es[0].w}, d[4] = {ed[0].x, ed[0].y, ed[0].z, ed[0].w};
        uint32_t ca[4], cb[4], own[4], sl[4], q[4];
        bool c[4];
#pragma unroll
        for (int j = 0; j < 4; j++) { ca[j] = lds32(sb + 4 * s[j]); cb[j] = lds32(sb + 4 * d[j]); }
#pragma unroll
        for (int j = 0; j < 4; j++) {
            c[j] = near_test(ca[j], cb[j], tag << 24, q[j]) && g < eg1;
            own[j] = __umulhi((uint32_t)d[j], magic);
            sl[j] = atomicAdd(reinterpret_cast<uint32_t*>(smem + SCNT_OFF) + (c[j] ? own[j] : MAXG + lane), 4u);
        }
#pragma unroll
        for (int j = 0; j < 4; j++)
            sts32_if(sb + STAGE_OFF + own[j] * 128 + sl[j], own[j] * (uint32_t)(-64 * NPC) + (((uint32_t)s[j] << 15) + (((uint32_t)d[j] << 6) + ((q[j] & 0x80000000u) | tag))),
                     sl[j] < 124);
        full |= (sl[0] == 124) | (sl[1] == 124) | (sl[2] == 124) | (sl[3] == 124);
        es[0] = es[1]; es[1] = es[2];
        ed[0] = ed[1]; ed[1] = ed[2];
    }
    {
        const int redo = __syncthreads_or(full);
        if (__builtin_expect(redo || odd_edges, 0)) cold_filter(smem, p, eg0, eg1, tag, redo);
    }
    TS0(4);
#pragma unroll
    for (int i = 0; i < 3; i++) stg128_if(xout + i * G * THREADS, stage4[tid + i * THREADS], tid + i * THREADS < G * 8);
    __syncthreads();
#pragma unroll
    for (int i = -2; i < 2; i++) {
        const int c = tid + i * THREADS;
        const uint32_t x = c < (SN_OFF - STAGE_OFF) / 16 ? 0u : 0xFFFFFFFFu;
        if (c >= (SREC_OFF - STAGE_OFF) / 16) stage4[c] = make_uint4(x, x, x, x);
    }
    uint32_t key[4];
    uint2 pr[4];
    const uint32_t gp = sb + RING_OFF + 2048 + (warp < 4 * NWG ? warp * 12288 : (warp & 3) * 12288 + 2048) + lane * 16;
    uint32_t pk = 0;
    if (warp == 15) {
        if (lane == 0) {
            int o = TOUCH * 8192;
#pragma unroll 1
            while (o < nn * 512 && !mbar_test(sb + BAR_OFF + 8, 0)) {
                const uint32_t bar = sb + BAR_OFF + 16 + 8 * (pk % FLIGHT);
                if (!mbar_test(bar, ~(pk / FLIGHT) & 1)) continue;
                const int n = min(4096, nn * 512 - o);
                mbar_expect_tx(bar, n);
                bulk_g2s(sb + DUMMY_OFF, own + o, n, bar);
                o += n;
                pk++;
            }
            misc[3] = pk;
        }
        __syncwarp();
    } else {
    __nanosleep(PDELAY);
    TS0(5);

    {
        const int LPW = (G + 14) / 15;
        uint32_t ew[3][4], bad[3];
        const uint4* cp = p.g->xbuf + (b * G + warp * LPW) * 8 + lane;
#pragma unroll
        for (int i = 0; i < 3; i++) {
            bad[i] = lane + 32 * i < min(LPW, G - warp * LPW) * 8;
            ew[i][0] = ew[i][1] = ew[i][2] = ew[i][3] = (PAY_INVALID << 6) | tag;
        }
        int it = 0;
#pragma unroll 1
        do {
#pragma unroll
            for (int i = 0; i < 3; i++)
                asm volatile("{\n.reg .pred p;\nsetp.ne.u32 p, %5, 0;\n@p ld.relaxed.gpu.global.v4.u32 {%0,%1,%2,%3}, [%4];\n}\n"
                             : "+r"(ew[i][0]), "+r"(ew[i][1]), "+r"(ew[i][2]), "+r"(ew[i][3]) : "l"(cp + 32 * i), "r"(bad[i]) : "memory");
#pragma unroll
            for (int i = 0; i < 3; i++) bad[i] = ((ew[i][0] ^ tag) | (ew[i][1] ^ tag) | (ew[i][2] ^ tag) | (ew[i][3] ^ tag)) & 63u;
            if (++it > (1 << 22)) __trap();
        } while (__any_sync(0xffffffffu, bad[0] | bad[1] | bad[2]));
        TSX(21, 0); TSX(22, 448);
        uint4* pack = reinterpret_cast<uint4*>(smem + PACK_OFF);
        int nch = 0;
        uint32_t at[3];
#pragma unroll
        for (int i = 0; i < 3; i++) {
            const uint32_t m = __ballot_sync(0xffffffffu, ew[i][0] < (PAY_MARK << 6));
            at[i] = nch + __popc(m & ((1u << lane) - 1));
            nch += __popc(m);
        }
        if (__builtin_expect(nch > 32, 0)) {
#pragma unroll 1
            for (int i = 0; i < 3; i++) {
                if (ew[0][0] < (PAY_MARK << 6) && at[0] >= 32) at[0] = (15 - warp) * 32 - 1 - min(atomicAdd(&misc[1], 1u), 31u);
                const uint32_t x = at[0], y = ew[0][0];
                at[0] = at[1]; at[1] = at[2]; at[2] = x;
                ew[0][0] = ew[1][0]; ew[1][0] = ew[2][0]; ew[2][0] = y;
            }
        }
#pragma unroll
        for (int i = 0; i < 3; i++) {
            asm volatile("{\n.reg .pred p;\nsetp.lt.u32 p, %1, %5;\n@p st.shared.v4.u32 [%0], {%1,%2,%3,%4};\n}\n"
                         ::"r"(sb + PACK_OFF + (warp * 32 + at[i]) * 16), "r"(ew[i][0]), "r"(ew[i][1]), "r"(ew[i][2]), "r"(ew[i][3]), "n"(PAY_MARK << 6) : "memory");
            sts32_if(sb + MISC_OFF + 4 * 17, 1, (ew[i][3] >> 6) == PAY_MARK);
        }
        bool have = lane < nch;
        if (warp == 14) {
            asm volatile("bar.sync 7, 480;" ::: "memory");
            const uint32_t extra = misc[1];
            if (nch + extra > 32) misc[18] = 1;
            have = have || lane + extra >= 32;
        } else {
            asm volatile("bar.arrive 7, 480;" ::: "memory");
        }
        __syncwarp();
        uint32_t w[4], rk[4];
        bool in[4];
        {
            const uint4 x = pack[tid];
            w[0] = have ? x.x : ~0u; w[1] = have ? x.y : ~0u; w[2] = have ? x.z : ~0u; w[3] = have ? x.w : ~0u;
        }
        auto fetch = [&](int j, bool c) {
            asm volatile("{\n.reg .pred p;\nsetp.ne.u32 p, %2, 0;\n@p cp.async.cg.shared.global [%0], [%1], 16;\n}\n"
                         ::"r"(gp + j * 512), "l"(reinterpret_cast<const uint4*>(p.g->pos8) + ((w[j] >> 16) & 0x7FFFu)), "r"((uint32_t)c) : "memory");
        };
#pragma unroll
        for (int j = 0; j < 4; j++) fetch(j, (int)w[j] < (int)(PAY_MARK << 6));
#pragma unroll
        for (int j = 0; j < 4; j++) pr[j] = reinterpret_cast<const uint2*>(smem + OPOS_OFF)[(w[j] >> 6) & 511u];
        asm volatile("cp.async.wait_all;" ::: "memory");
        TSX(23, 0); TSX(24, 448);
        asm volatile("{\n.reg .pred p;\nsetp.eq.u32 p, %1, 0;\n@p mbarrier.arrive.shared::cta.b64 _, [%0];\n}\n" ::"r"(sb + BAR_OFF + 8), "r"(lane) : "memory");
#pragma unroll
        for (int j = 0; j < 4; j++) {
            uint2 ps;
            asm volatile("ld.shared.v2.u32 {%0,%1}, [%2];" : "=r"(ps.x), "=r"(ps.y) : "r"(gp + j * 512 + ((w[j] >> 12) & 8)) : "memory");
            in[j] = ((int)w[j] >= 0) | (((int)w[j] < (int)(PAY_MARK << 6)) & inside(hsub2(ps.x, pr[j].x), hsub2(ps.y, pr[j].y)));
        }
#pragma unroll
        for (int j = 0; j < 4; j++) rk[j] = atomicAdd(&ncnt[in[j] ? (w[j] >> 6) & 511u : 480 + lane], 1u);
#pragma unroll
        for (int j = 0; j < 4; j++) {
            rk[j] = rk[j] < SPL ? 2 * rk[j] : min(2 * rk[j] - (2 * SPL - 1), 63u);
            atomicAdd(&misc[in[j] && !(rk[j] & 2) ? 32 + (rk[j] >> 2) : 63], 1u);
            key[j] = in[j] ? ((w[j] >> 15) & 0xFFFFu) | ((w[j] << 10) & 0x1FF0000u) | (rk[j] << 25) : 0xF8000000u;
        }
#pragma unroll
        for (int j = 0; j < 4; j++) fetch(j, (int)w[j] >= 0);
        cp_commit();
    }
    }
    __syncthreads();
    TS0(6);
    if (tid == THREADS - 33) {
        if (b == 0) p.g->sync[0] = epoch + 1;
        asm volatile("fence.proxy.async.global;" ::: "memory");
        mbar_expect_tx(bar_tab, RING_OFF);
        bulk_g2s(sb, p.g->wimg, RING_OFF, bar_tab);
    }
    __syncwarp();
    uint32_t dst = sb + RING_OFF + warp * 12288 + (lane >> 3) * 256 + (((lane & 7) ^ (lane >> 3)) << 4), l7 = (lane & 7) * 16, g32 = (lane >> 2) * 32;
    uint32_t e0, e1, n0, n1;
    auto sources = [&](uint32_t c) {
        asm volatile("{\n.reg .b32 a;\nlop3.b32 a, %4, %5, 0xFFC0, 0xA8;\nshr.u32 a, a, 2;\nld.shared.v4.u32 {%0,%1,%2,%3}, [a + %6];\n}\n"
                     : "=r"(e0), "=r"(n0), "=r"(e1), "=r"(n1) : "r"(c), "r"(g32), "n"(SB + SN_OFF));
    };
    auto load_s = [&](auto pad) {
        gather<1, 0, pad.value>(dst, p.sv, l7, e0); gather<1, 1, pad.value>(dst + 1024, p.sv, l7, e0);
        gather<1, 0, pad.value>((dst ^ 64) + 128, p.sv, l7, e1); gather<1, 1, pad.value>((dst ^ 64) + 1152, p.sv, l7, e1);
    };
    auto load_o = [&]() {
        gather<4, 0>(dst + 8192, p.sv, l7, n0); gather<4, 0>((dst ^ 64) + 8320, p.sv, l7, n1);
    };
    auto load_v = [&](auto pad) {
        gather<3, 0, pad.value>(dst + 2048, p.sv, l7, e0); gather<3, 1, pad.value>(dst + 5120, p.sv, l7, e0);
        gather<3, 0, pad.value>((dst ^ 64) + 2176, p.sv, l7, e1); gather<3, 1, pad.value>((dst ^ 64) + 5248, p.sv, l7, e1);
        cp_commit();
    };
    const int ng = (misc[32] + 7) >> 3;
    const int give = max(min(ng - max((int)(misc[33] + 7) >> 3, 4 * NWG), GIVE), 0);
    if (warp == 15) {
        const uint32_t cnt = lane < 16 ? (misc[32 + lane] + 7) >> 3 : 0u;
        uint32_t z = cnt;
#pragma unroll
        for (int o = 1; o < 16; o <<= 1) {
            const uint32_t y = __shfl_up_sync(0xffffffffu, z, o);
            if (lane >= o) z += y;
        }
        misc[96 + lane] = lane < 16 ? 64 * (z - cnt) : 64 * (MAXROW + 1);
        asm volatile("bar.arrive 5, 512;" ::: "memory");
        if (lane == 15) {
            const bool cold = cnt || z > MAXROW || misc[31 + SPL / 2] > 32 || misc[17] || misc[18];
            misc[18] = cold;
            asm volatile("st.relaxed.gpu.global.u32 [%0], %1;" ::"l"(p.g->rows + b), "r"(~epoch << 16 | (cold || ng < 4 * NWG ? 255 : give << 8 | z)) : "memory");
        }
        pk = (z - cnt) << 8 | __shfl_down_sync(0xffffffffu, cnt, 1) << 24;
    } else {
        if (warp * 32 < nn) {
            const uint32_t c = ncnt[tid], st = tid < nn ? (min(c, (uint32_t)SPL) + 1) >> 1 : 17u;
            const uint32_t same = __match_any_sync(0xffffffffu, st), first = __ffs(same) - 1;
            uint32_t r, node = nbase + tid;
            asm volatile("atom.shared.add.u32 %0, [%1], %2;" : "=r"(r)
                         : "r"(lane == first ? sb + MISC_OFF + 4 * (64 + st) : sb + NCNT_OFF + 4 * (480 + lane)), "r"(__popc(same)) : "memory");
            r = __shfl_sync(0xffffffffu, r, first) + __popc(same & ((1u << lane) - 1)) + misc[32 + st];
            if (__builtin_expect(c > SPL, 0)) {
                const uint32_t s2 = min((c - SPL + 1) >> 1, 16u), r2 = misc[32 + s2] + atomicAdd(&misc[64 + s2], 1u), k = atomicAdd(&misc[2], 1u);
                reinterpret_cast<uint32_t*>(smem + SCNT_OFF)[k & 31] = node;
                node |= NODE_SPLIT;
                ncnt[1024 + tid] = 8 * r2;
                reinterpret_cast<uint32_t*>(smem + SN_OFF)[(r2 & 511) * 2 + 1] = node;
            }
            if (tid < nn) {
                ncnt[512 + tid] = 8 * r;
                reinterpret_cast<uint32_t*>(smem + SN_OFF)[(r & 511) * 2 + 1] = node;
            }
        }
#pragma unroll
        for (int j = 0; j < 4; j++) {
            const uint32_t c = ncnt[(key[j] >> 16) & 511];
            asm volatile("{\n.reg .pred p;\n.reg .b64 a;\nsetp.ge.u32 p, %0, %3;\nsetp.lt.and.u32 p, %1, 0x8000000, p;\nmad.wide.u32 a, %4, 512, %2;\n@p prefetch.global.L2 [a];\n"
                         "}\n" ::"r"(c), "r"(key[j]), "l"(p.sv), "n"(BIG), "r"(key[j] & 0xFFFFu) : "memory");
        }
        asm volatile("bar.sync 5, 512;" ::: "memory");
        uint32_t slot[4];
#pragma unroll
        for (int j = 0; j < 4; j++) slot[j] = min(misc[96 + (key[j] >> 27)] + ncnt[512 + ((key[j] >> 16) & 1023)], 64u * (MAXROW + 1)) + ((key[j] >> 25) & 2);
#pragma unroll
        for (int j = 0; j < 4; j++) {
            *reinterpret_cast<uint16_t*>(smem + SN_OFF + slot[j]) = (uint16_t)key[j];
            slot[j] += slot[j] & 2;
        }
        asm volatile("bar.sync 6, 480;" ::: "memory");
        TS0(7);
        if (warp < 4 * NWG) {
            sources((warp < ng ? warp : MAXROW) << 8);
            e0 = __vminu2(e0, (N - 1) * 0x10001u);
            e1 = __vminu2(e1, (N - 1) * 0x10001u);
            load_s(IntC<0>{});
            cp_commit();
            load_o();
            cp_commit();
            asm volatile("cp.async.wait_group 2;" ::: "memory");
        } else {
            asm volatile("cp.async.wait_all;" ::: "memory");
        }
        uint2 ps[4];
#pragma unroll
        for (int j = 0; j < 4; j++)
            asm volatile("ld.shared.v2.u32 {%0,%1}, [%2];" : "=r"(ps[j].x), "=r"(ps[j].y) : "r"(gp + j * 512 + (key[j] & 1) * 8) : "memory");
        TSX(9, 0);
#pragma unroll 1
        for (int i = 0; i < 2; i++) {
#pragma unroll
            for (int u = 0; u < 2; u++) {
                const uint3 geo = geometry(hsub2(ps[u].x, pr[u].x), hsub2(ps[u].y, pr[u].y));
                *reinterpret_cast<uint2*>(smem + SREC_OFF + 2 * slot[u]) = make_uint2(geo.x, geo.y);
                *reinterpret_cast<uint32_t*>(smem + SD_OFF + slot[u]) = geo.z;
                ps[u] = ps[u + 2];
                pr[u] = pr[u + 2];
                slot[u] = slot[u + 2];
            }
        }
    }
    if (warp == 15) { __syncwarp(); asm volatile("bar.arrive 4, 512;" ::: "memory"); }
    else asm volatile("bar.sync 4, 512;" ::: "memory");
    TS0(8);
    auto drain = [&](int i) { if (i < FLIGHT) mbar_wait(sb + BAR_OFF + 16 + 8 * i, ~((misc[3] + FLIGHT - 1 - i) / FLIGHT) & 1); };
    if (__builtin_expect(misc[18], 0)) {
        drain(warp);
        asm volatile("cp.async.wait_all;" ::: "memory");
        __syncthreads();
        cold_messages(smem, p, nn);
        mbar_wait(bar_tab, 1);
        return;
    }

    if (warp < 4 * NWG) {
        asm volatile("setmaxnreg.inc.sync.aligned.u32 %0;" ::"n"(REG_C));
        const int lane = fresh_lane();
        const int g = lane >> 2, q = lane & 3;
        const uint64_t dW1 = p.desc0, dW2 = dW1 + (W2_OFF >> 4), dWR = dW1 + (WR_OFF >> 4);
        const uint32_t ring = sb + RING_OFF + warp * 12288;
        const uint32_t vrow = pin(ring + g * 128 + ((q ^ ((g & 1) << 2) ^ (g >> 1)) << 4));
        const uint32_t mrow = pin(ring + (lane & 15) * 128 + (((lane >> 4) ^ ((lane & 1) << 2) ^ ((lane & 7) >> 1)) << 4));
        dst = pin(ring + (lane >> 3) * 256 + (((lane & 7) ^ (lane >> 3)) << 4)); l7 = pin((lane & 7) * 16); g32 = pin(g * 32);
        uint32_t ctl = sb + CTL_OFF + warp * 4;
        auto control = [&](uint32_t c, uint32_t at) {
            int it = 0;
#pragma unroll 1
            while (__builtin_expect(c == 0xFFFFFFFFu, 0)) {
                asm volatile("ld.volatile.shared.u32 %0, [%1];" : "=r"(c) : "r"(at) : "memory");
                c = __reduce_or_sync(0xffffffffu, c);
                if (++it > (1 << 24)) __trap();
            }
            return c;
        };
        uint32_t c0 = control(0xFFFFFFFFu, ctl), c1 = control(0xFFFFFFFFu, ctl + 64);
        if (warp >= 8) asm volatile("bar.arrive 1, 256;" ::: "memory");
        uint32_t acc[32];
        float P[32], W[32];
#pragma unroll
        for (int i = 0; i < 32; i++) { acc[i] = 0; P[i] = W[i] = 0.f; }
        mbar_wait(bar_tab, 1);
        sources(c0);
        e0 = __vminu2(e0, (N - 1) * 0x10001u);
        e1 = __vminu2(e1, (N - 1) * 0x10001u);
        if (warp >= 8) asm volatile("cp.async.wait_all;" ::: "memory");
        else if (warp >= 4) cp_wait1();
        load_v(IntC<0>{});
        auto finish = [&](uint32_t c, uint32_t node) {
            if (c & ST_CLOSE) {
                uint64_t op[2];
                asm("{\n.reg .b32 a;\nmad.lo.u32 a, %2, 512, %3;\nmad.wide.u32 %0, a, 1, %4;\nxor.b32 a, a, 64;\nmad.wide.u32 %1, a, 1, %4;\n}\n"
                    : "=l"(op[0]), "=l"(op[1]) : "r"(node), "r"(l7), "l"(p.out));
#pragma unroll
                for (int k = 0; k < 8; k++) {
                    uint32_t x[4];
#pragma unroll
                    for (int i = 0; i < 4; i++) x[i] = l7 & 64 ? acc[4 * (k ^ 1) + i] : acc[4 * k + i];
                    asm volatile("{\n.reg .pred p;\nsetp.lt.u32 p, %5, %6;\n@p st.global.cs.v4.u32 [%0], {%1,%2,%3,%4};\n}\n"
                                 ::"l"(op[k & 1] + 128 * (k >> 1)), "r"(x[0]), "r"(x[1]), "r"(x[2]), "r"(x[3]), "r"(node), "n"(NODE_SPLIT) : "memory");
                }
                if (__builtin_expect(__any_sync(0xffffffffu, (int)node >= (int)NODE_SPLIT), 0)) {
                    mbar_wait(sb + BAR_OFF + 16 + 8 * FLIGHT, 0);
                    if ((int)node >= (int)NODE_SPLIT) {
#pragma unroll
                        for (int k = 0; k < 8; k++)
                            asm volatile("red.global.add.noftz.v4.bf16x2 [%0], {%1,%2,%3,%4};" ::"l"((op[0] & ~64ull) + 64 * k), "r"(acc[4 * k]), "r"(acc[4 * k + 1]), "r"(acc[4 * k + 2]), "r"(acc[4 * k + 3]) : "memory");
                    }
                    __syncwarp();
                }
            }
        };
#pragma unroll 1
        while ((int)c0 >= 0) {
            uint32_t a[16], h[16], rf[4], rr[4], m[16];
            TRW(ctl);
            uint32_t dd[2], f01, f23;
            asm volatile("ld.shared.v2.u32 {%0,%1}, [%2 + %3];" : "=r"(dd[0]), "=r"(dd[1]) : "r"(((c0 & 0xFF00) | g32) >> 2), "n"(SB + SD_OFF));
            asm volatile("ld.shared.v2.u32 {%0,%1}, [%2 + %3];" : "=r"(f01), "=r"(f23) : "r"(l7), "n"(SB + FREQ_OFF));
            sources(c1);
            asm volatile("cp.async.wait_group 2;" ::: "memory");
            __syncwarp();
#pragma unroll
            for (int i = 0; i < 4; i++) ldsm4(mrow ^ (i << 5), a + 4 * i);
            wg_fence();
            wgmma_k64(P, a, dW1);
            wg_commit();
            SPLIT(1);
#pragma unroll
            for (int hh = 0; hh < 2; hh++) {
                const float sc = bf_hi(dd[hh]);
                const uint32_t x01 = hmul2_lo(f01, dd[hh]), x23 = hmul2_lo(f23, dd[hh]);
                rf[hh] = pack2(__sinf(bf_lo(x01)) * sc, __sinf(bf_hi(x01)) * sc);
                rf[2 + hh] = pack2(__sinf(bf_lo(x23)) * sc, __sinf(bf_hi(x23)) * sc);
            }
            asm volatile("" : "+r"(rf[0]), "+r"(rf[1]), "+r"(rf[2]), "+r"(rf[3]));
            asm volatile("bar.sync %0, 256;" ::"r"(1 + (warp >> 2)) : "memory");
            SPLIT(2);
            wg_wait<0>();
            fence_regs(P);
#pragma unroll
            for (int i = 0; i < 16; i++)
                h[i] = pack2(fmaf(P[2 * i], tanh_fast(P[2 * i]), P[2 * i]), fmaf(P[2 * i + 1], tanh_fast(P[2 * i + 1]), P[2 * i + 1]));
            wg_fence();
            wgmma_k64(P, h, dW2 + 1024);
            wgmma_first(W, rf, dWR + 256);
            wg_commit();
            asm volatile("bar.arrive %0, 256;" ::"r"((c0 >> 4) & 3) : "memory");
            SPLIT(3);
            cp_wait1();
            __syncwarp();
#pragma unroll
            for (int k = 0; k < 4; k++) lds2_if(vrow + 8192 + 1024 * k, (vrow ^ 64) + 8192 + 1024 * k, acc + 8 * k, c0 & ST_START);
            lds128(sb + SREC_OFF + (((c0 & 0xFF00) | g32) >> 1), rr);
            uint32_t c2 = lds32(ctl + 128);
            __syncwarp();
            load_s(IntC<1>{});
            cp_commit();
            if (c1 & ST_START) load_o();
            cp_commit();
            wg_wait<0>();
            fence_regs(P); fence_regs(W);
#pragma unroll
            for (int j = 0; j < 8; j++) {
                m[j] = pack2(P[4 * j] * W[4 * j], P[4 * j + 1] * W[4 * j + 1]);
                m[8 + j] = pack2(P[4 * j + 2] * W[4 * j + 2], P[4 * j + 3] * W[4 * j + 3]);
            }
            wg_fence();
            wgmma_k64(P, h, dW2);
            wgmma_first(W, rf, dWR);
            wg_commit();
            SPLIT(4);
            PIN8(m); PIN8(m + 8);
            c2 = __reduce_or_sync(0xffffffffu, c2);
#pragma unroll
            for (int k = 1; k < 4; k++)
#pragma unroll
                for (int j = 0; j < 8; j++) {
                    const uint32_t x = k == 1 ? hfma2_lo(m[j], rr[0], acc[8 * k + j]) : k == 2 ? hfma2_hi(m[j], rr[0], acc[8 * k + j]) : hfma2_lo(m[j], rr[1], acc[8 * k + j]);
                    acc[8 * k + j] = k == 1 ? hfma2_lo(m[8 + j], rr[2], x) : k == 2 ? hfma2_hi(m[8 + j], rr[2], x) : hfma2_lo(m[8 + j], rr[3], x);
                }
            PIN8(acc + 8); PIN8(acc + 16); PIN8(acc + 24);
            c2 = control(c2, ctl + 128);
            wg_wait<0>();
            fence_regs(P); fence_regs(W);
#pragma unroll
            for (int j = 0; j < 8; j++)
                acc[j] = hadd2(acc[j], pack2(fmaf(P[4 * j], W[4 * j], P[4 * j + 2] * W[4 * j + 2]), fmaf(P[4 * j + 1], W[4 * j + 1], P[4 * j + 3] * W[4 * j + 3])));
            wg_fence();
            wgmma_k64(P, h, dW2 + 512);
            wgmma_first(W, rf, dWR + 128);
            wg_commit();
            SPLIT(6);
            asm volatile("cp.async.wait_group 2;" ::: "memory");
            __syncwarp();
            uint32_t v[4][16];
#pragma unroll
            for (int i = 0; i < NPRE; i++) lds128((vrow ^ (64 * (i & 1))) + 2048 + 1024 * (i >> 2) + 3072 * ((i >> 1) & 1), v[1 + (i >> 2)] + 4 * (i & 3));
            wg_wait<0>();
            fence_regs(P); fence_regs(W);
#pragma unroll
            for (int j = 0; j < 8; j++) {
                m[j] = pack2(P[4 * j] * W[4 * j], P[4 * j + 1] * W[4 * j + 1]);
                m[8 + j] = pack2(P[4 * j + 2] * W[4 * j + 2], P[4 * j + 3] * W[4 * j + 3]);
            }
#pragma unroll
            for (int i = NPRE; i < 12; i++) lds128((vrow ^ (64 * (i & 1))) + 2048 + 1024 * (i >> 2) + 3072 * ((i >> 1) & 1), v[1 + (i >> 2)] + 4 * (i & 3));
            sources(c1);
            const uint32_t node = lds32(sb + SN_OFF + 4 + (((c0 >> 16) | g32) >> 2));
            __syncwarp();
            load_v(IntC<1>{});
#pragma unroll
            for (int k = 1; k < 4; k++)
#pragma unroll
                for (int j = 0; j < 8; j++) acc[8 * k + j] = hfma2(m[8 + j], v[k][8 + j], hfma2(m[j], v[k][j], acc[8 * k + j]));
            finish(c0, node);
            ctl += 64;
            c0 = c1;
            c1 = c2;
        }
        asm volatile("cp.async.wait_all;" ::: "memory");
        TRW(ctl);
        TSX(11, 0); TSX(12, 128); TSX(13, 256);
    } else {
        asm volatile("setmaxnreg.dec.sync.aligned.u32 %0;" ::"n"(REG_H));
        const int lane = fresh_lane();
        const uint32_t chunk = sb + (lane & 8 ? (lane & 4 ? SN_OFF : SD_OFF) + (lane & 3) * 16 : SREC_OFF + (lane & 7) * 16), pitch = lane & 8 ? 64 : 128;
        if (warp == 12) {
#pragma unroll 1
            for (int i = 0; i < (int)misc[2]; i++) {
                const uint32_t n = reinterpret_cast<const uint32_t*>(smem + SCNT_OFF)[i] * 32 + lane;
                reinterpret_cast<uint4*>(p.out)[n] = reinterpret_cast<const uint4*>(p.sv)[n];
            }
#pragma unroll 1
            for (int i = lane >> 4; i < give; i += 2) {
                uint32_t x[4];
                lds128(chunk + (ng - 1 - i) * pitch, x);
                p.g->pool[(b * GIVE + i) * 16 + (lane & 15)] = make_uint4(x[0], x[1], x[2], x[3]);
            }
            __threadfence();
            __syncwarp();
            if (lane == 0) {
                asm volatile("st.relaxed.gpu.global.u32 [%0], %1;" ::"l"(p.g->ready + b), "r"(~epoch) : "memory");
                mbar_arrive(sb + BAR_OFF + 16 + 8 * FLIGHT);
            }
        }
        if (warp == 15) {
            int k = lane < 4 * NWG ? lane : 255, next = 4 * NWG, j = 0, mine = ng - give, end = -1, take = 0;
            uint32_t busy, at = sb + CTL_OFF + 4 * lane, from = 0;
#pragma unroll 1
            do {
                if (next > mine && end < 0) {
                    end = mine = ng;
                    const int peer = b % 5 + 5 * lane;
                    uint32_t x = 255;
                    int it = 0;
                    if (peer < G) {
#pragma unroll 1
                        do {
                            asm volatile("ld.relaxed.gpu.global.u32 %0, [%1];" : "=r"(x) : "l"(p.g->rows + peer) : "memory");
                            if (++it > (1 << 22)) __trap();
                        } while ((x >> 16) != (~epoch & 0xFFFFu));
                    }
                    const int r = x & 255, n = __popc(__ballot_sync(0xffffffffu, r != 255));
                    const int level = min(((__reduce_add_sync(0xffffffffu, r != 255 ? r : 0) + n - 1) / max(n, 1) + 3) & ~3, MAXROW);
                    const uint32_t ed = r > level ? min(r - level, (int)(x >> 8) & 255) : min(level - r, ROOM) << 16;
                    uint32_t z = ed;
#pragma unroll
                    for (int o = 1; o < 32; o <<= 1) {
                        const uint32_t y = __shfl_up_sync(0xffffffffu, z, o);
                        if (lane >= o) z += y;
                    }
                    const uint32_t all = __shfl_sync(0xffffffffu, z, 31), moved = min(all & 0xFFFFu, all >> 16);
                    const uint32_t me = __shfl_sync(0xffffffffu, ed, b / 5), mz = __shfl_sync(0xffffffffu, z, b / 5) - me;
                    end = mine = ng - (min((mz + me) & 0xFFFFu, moved) - min(mz & 0xFFFFu, moved));
#pragma unroll 1
                    for (uint32_t u = mz >> 16; u < min((mz + me) >> 16, moved); u++, take++) {
                        const int f = __popc(__ballot_sync(0xffffffffu, (z & 0xFFFFu) <= u));
                        const uint32_t q = u - (__shfl_sync(0xffffffffu, z - ed, f) & 0xFFFFu);
                        if (lane == take) from = (b % 5 + 5 * f) << 8 | q;
                    }
                }
                if (next > mine && take) {
                    if (lane < take) {
                        uint32_t x;
                        int it = 0;
#pragma unroll 1
                        do {
                            asm volatile("ld.acquire.gpu.global.u32 %0, [%1];" : "=r"(x) : "l"(p.g->ready + (from >> 8)) : "memory");
                            if (++it > (1 << 22)) __trap();
                        } while (x != ~epoch);
                    }
                    __syncwarp();
#pragma unroll 1
                    for (end += take; take--;) {
                        const uint32_t f = __shfl_sync(0xffffffffu, from, take);
                        if (lane < 16)
                            asm volatile("cp.async.cg.shared.global [%0], [%1], 16;" ::"r"(chunk + (MAXROW - 1 - take) * pitch),
                                         "l"(p.g->pool + ((f >> 8) * GIVE + (f & 255)) * 16 + lane) : "memory");
                    }
                    take = 0;
                    asm volatile("cp.async.wait_all;" ::: "memory");
                    __threadfence_block();
                    __syncwarp();
                }
                const bool has = k < (end < 0 ? mine : end);
                const uint32_t i = k < mine ? k : MAXROW - 1 + mine - k, x = __shfl_sync(0xffffffffu, pk, j);
                const bool close = has && i >= (x >> 24);
                busy = __ballot_sync(0xffffffffu, has);
                const uint32_t m = __ballot_sync(0xffffffffu, close);
                uint32_t c = has ? ((x & 0xFF00) + i * 0x1000100) | (j ? 0u : ST_START) | (close ? ST_CLOSE : 0u) : MAXROW * 256;
                if (!(busy >> (lane & 12))) c |= 0x80000000u;
                c |= busy >> ((lane & 12) + 4) ? (lane & 12) * 4 + 32 : 16;
                sts32_if(at, c, lane < 16 || !busy);
                j = close ? 0 : j + 1;
                k = close ? next + __popc(m & ((1u << lane) - 1)) : k;
                next += __popc(m);
                at += 64;
            } while (busy);
        }
        if (warp == 15) mbar_wait(sb + BAR_OFF + 16 + 8 * FLIGHT, 0);
        else if (warp != 12) __nanosleep(ZDELAY);
        const int zend = misc[32] + misc[64];
#pragma unroll 1
        for (;;) {
            int r = 0;
            if (lane == 0) r = atomicAdd(&misc[4], 4u);
            r = __shfl_sync(0xffffffffu, r, 0) + 8 * ng;
            if (r >= zend) break;
            uint4 v[4];
            uint32_t n[4];
#pragma unroll
            for (int i = 0; i < 4; i++) {
                n[i] = reinterpret_cast<const uint32_t*>(smem + SN_OFF)[min(r + i, zend - 1) * 2 + 1] * 32 + lane;
                v[i] = __ldcs(reinterpret_cast<const uint4*>(p.sv) + n[i]);
            }
#pragma unroll
            for (int i = 0; i < 4; i++)
                if (r + i < zend) __stcs(reinterpret_cast<uint4*>(p.out) + n[i], v[i]);
        }
        static_assert(FLIGHT <= 4, "drain");
        drain(warp & 3);
        asm volatile("cp.async.wait_all;" ::: "memory");
        TSX(14, 384); TSX(15, 480); TSX(16, 416);
    }
}

}

extern "C" void kernel_launch(void* const* d_in, const int* in_sizes, int n_in, void* d_out, int out_size) {
    static int s_G = 0;
    static void* s_scratch = nullptr;
    const int N = in_sizes[0] / 256, E = in_sizes[2];
    if (s_G == 0) {
        cudaFuncSetAttribute(painn_kernel<0, 0, 0>, cudaFuncAttributeMaxDynamicSharedMemorySize, SMEM_BYTES);
        cudaFuncSetAttribute(painn_kernel<50000, 800000, 132>, cudaFuncAttributeMaxDynamicSharedMemorySize, SMEM_BYTES);
        int dev = 0, sms = 0, occ = 0;
        cudaGetDevice(&dev);
        cudaDeviceGetAttribute(&sms, cudaDevAttrMultiProcessorCount, dev);
        cudaOccupancyMaxActiveBlocksPerMultiprocessor(&occ, painn_kernel<0, 0, 0>, THREADS, SMEM_BYTES);
        cudaGetSymbolAddress(&s_scratch, g_scratch);
        s_G = occ >= 1 ? (sms < MAXG ? sms : MAXG) : 0;
    }
    if (s_G == 0 || N > TABLE_MAXN || N > s_G * MAXNPC || (s_G - 1) * ((N + s_G - 1) / s_G) >= N || E > MAXE || E < 4 * MAXG * MAXG) return;
    Params p;
    p.g = (Scratch*)s_scratch;
    p.sv = (const __nv_bfloat16*)d_in[0];
    p.pos = (const __nv_bfloat16*)d_in[1];
    p.src = (const int*)d_in[2];
    p.dst = (const int*)d_in[3];
    p.freqs = (const __nv_bfloat16*)d_in[4];
    p.w1 = (const __nv_bfloat16*)d_in[5];
    p.w2 = (const __nv_bfloat16*)d_in[6];
    p.wr = (const __nv_bfloat16*)d_in[7];
    p.out = (__nv_bfloat16*)d_out;
    p.desc0 = (uint64_t)(SB >> 4) | ((uint64_t)1 << 16) | ((uint64_t)64 << 32) | ((uint64_t)1 << 62);
    p.N = N; p.E = E; p.G = s_G;
    p.NPC = (N + s_G - 1) / s_G;
    p.magic = (uint32_t)(((1ull << 32) + p.NPC - 1) / p.NPC);
    p.gpc = ((E >> 2) + s_G - 1) / s_G;
    p.odd_edges = (E & 3) != 0 || p.gpc > 3 * THREADS;
    if (N == 50000 && E == 800000 && s_G == 132) painn_kernel<50000, 800000, 132><<<s_G, THREADS, SMEM_BYTES, cudaStreamPerThread>>>(p);
    else painn_kernel<0, 0, 0><<<s_G, THREADS, SMEM_BYTES, cudaStreamPerThread>>>(p);
}
```

```cpp
#include <cuda_runtime.h>
#include <cuda_bf16.h>
#include <stdint.h>

namespace {

constexpr int NWG = 3;
constexpr int REG_C = 160, REG_H = 32;
constexpr int SPL = 10;
constexpr int GIVE = 10, ROOM = 4;
constexpr int BIG = 5;
constexpr int CUT = 7;
constexpr int HDELAY = 150;
constexpr int TOUCH = 4, FLIGHT = 4;
constexpr int NPRE = 6;
constexpr int PDELAY = 150;
constexpr int ZDELAY = 1200;
constexpr int THREADS = 512;
constexpr int MAXG = 136;
constexpr int MAXROW = 96;
constexpr int TMAX = MAXROW / 12 + 18;
constexpr int MAXNPC = 480;
constexpr int MAXE = 1 << 20;

constexpr int W2_OFF = 8192;
constexpr int WR_OFF = 32768;
constexpr int RING_OFF = 38912;
constexpr int SREC_OFF = RING_OFF + 4 * NWG * 12288;
constexpr int SD_OFF = SREC_OFF + (MAXROW + 1) * 128 + 16;
constexpr int SN_OFF = SD_OFF + (MAXROW + 1) * 64 + 16;
constexpr int CTL_OFF = SN_OFF + (MAXROW + 1) * 64 + 16;
constexpr int TABLE_MAXN = 50176;
constexpr int STAGE_OFF = TABLE_MAXN * 4;
constexpr int SCNT_OFF = STAGE_OFF + MAXG * 128;
constexpr int PACK_OFF = RING_OFF + 6144;
constexpr int NCNT_OFF = SCNT_OFF + 768;
constexpr int OPOS_OFF = NCNT_OFF + 2048;
constexpr int BAR_OFF = OPOS_OFF + 4096;
constexpr int MISC_OFF = BAR_OFF + 128;
constexpr int FREQ_OFF = MISC_OFF + 512;
constexpr int DUMMY_OFF = (FREQ_OFF + 128 + 127) / 128 * 128;
constexpr int SMEM_BYTES = DUMMY_OFF + 4096;
static_assert(CTL_OFF + 64 * TMAX <= STAGE_OFF + 32 * THREADS && STAGE_OFF - SREC_OFF <= 32 * THREADS && 4 * (MAXG + 32) <= 768, "smem map");
static_assert(SMEM_BYTES <= 232448 && BAR_OFF % 8 == 0 && RING_OFF % 128 == 0 && SREC_OFF % 128 == 0 && (MAXG + 14) / 15 <= 12, "smem map");

constexpr uint32_t PAY_INVALID = 0x3FFFFFFu;
constexpr uint32_t PAY_MARK = 0x3FFFDFFu;
constexpr uint32_t NODE_SPLIT = 0x40000000u;
constexpr uint32_t ST_START = 1, ST_CLOSE = 2;
constexpr float QINVP = 9.0f / 510.0f;
constexpr uint32_t QTHRESH = 2209;
constexpr uint32_t QSURE = 1980;

struct Scratch {
    unsigned sync[32];
    uint4 table[TABLE_MAXN / 4];
    uint4 wimg[RING_OFF / 16];
    uint2 pos8[TABLE_MAXN];
    uint4 xbuf[MAXG * MAXG * 8 + 3 * THREADS];
    uint4 pool[MAXG * GIVE * 16];
    unsigned rows[MAXG];
    unsigned ready[MAXG];
    int ovfcnt[MAXG];
    int2 ovf[MAXE + 8 * MAXG + 8];
};
__device__ __align__(128) Scratch g_scratch;

struct Params {
    const __nv_bfloat16* pos;
    Scratch* g;
    const int* src;
    const int* dst;
    int N, NPC, E, gpc;
    const __nv_bfloat16* w2;
    const __nv_bfloat16* wr;
    const __nv_bfloat16* w1;
    const __nv_bfloat16* freqs;
    const __nv_bfloat16* sv;
    __nv_bfloat16* out;
    uint64_t desc0;
    int G;
    uint32_t magic;
    int odd_edges;
};
constexpr uint32_t SB = 1024;

#define TSX(i, thr)
#define TS0(i) TSX(i, 0)
#define TRW(ctl)

__device__ __forceinline__ uint32_t smem_u32(const void* p) { return (uint32_t)__cvta_generic_to_shared(p); }
__device__ __forceinline__ void mbar_init(uint32_t bar, uint32_t cnt) {
    asm volatile("mbarrier.init.shared::cta.b64 [%0], %1;" ::"r"(bar), "r"(cnt) : "memory");
}
__device__ __forceinline__ void mbar_arrive(uint32_t bar) {
    asm volatile("mbarrier.arrive.shared::cta.b64 _, [%0];" ::"r"(bar) : "memory");
}
__device__ __forceinline__ void mbar_expect_tx(uint32_t bar, uint32_t bytes) {
    asm volatile("mbarrier.arrive.expect_tx.shared::cta.b64 _, [%0], %1;" ::"r"(bar), "r"(bytes) : "memory");
}
__device__ __forceinline__ void mbar_wait(uint32_t bar, uint32_t parity) {
    uint32_t ok;
    int it = 0;
    do {
        asm volatile(
            "{\n.reg .pred p;\n"
            "mbarrier.try_wait.parity.shared::cta.b64 p, [%1], %2, 2000;\n"
            "selp.u32 %0, 1, 0, p;\n}\n"
            : "=r"(ok) : "r"(bar), "r"(parity) : "memory");
        if (++it > (1 << 20)) __trap();
    } while (!ok);
}
__device__ __forceinline__ uint32_t mbar_test(uint32_t bar, uint32_t parity) {
    uint32_t ok;
    asm volatile("{\n.reg .pred p;\nmbarrier.test_wait.parity.shared::cta.b64 p, [%1], %2;\nselp.u32 %0, 1, 0, p;\n}\n"
                 : "=r"(ok) : "r"(bar), "r"(parity) : "memory");
    return ok;
}
__device__ __forceinline__ uint32_t pin(uint32_t x) {
    uint32_t r;
    asm volatile("shfl.sync.bfly.b32 %0, %1, 0, 31, -1;" : "=r"(r) : "r"(x));
    return r;
}
__device__ __forceinline__ void bulk_g2s(uint32_t dst, const void* src, uint32_t bytes, uint32_t bar) {
    asm volatile("cp.async.bulk.shared::cluster.global.mbarrier::complete_tx::bytes [%0], [%1], %2, [%3];"
                 ::"r"(dst), "l"(src), "r"(bytes), "r"(bar) : "memory");
}
__device__ __forceinline__ void ldsm4(uint32_t addr, uint32_t* r) {
    asm volatile("ldmatrix.sync.aligned.m8n8.x4.shared.b16 {%0,%1,%2,%3}, [%4];"
                 : "=r"(r[0]), "=r"(r[1]), "=r"(r[2]), "=r"(r[3]) : "r"(addr) : "memory");
}
__device__ __forceinline__ uint32_t pack2(float lo, float hi) {
    uint32_t r;
    asm("cvt.rn.bf16x2.f32 %0, %1, %2;" : "=r"(r) : "f"(hi), "f"(lo));
    return r;
}
__device__ __forceinline__ float bf_lo(uint32_t w) { return __uint_as_float(w << 16); }
__device__ __forceinline__ float bf_hi(uint32_t w) { return __uint_as_float(w & 0xFFFF0000u); }
__device__ __forceinline__ float rbf16(float x) { return __uint_as_float(pack2(0.f, x)); }
__device__ __forceinline__ uint32_t hmul2(uint32_t a, uint32_t b) {
    uint32_t r;
    asm("mul.rn.bf16x2 %0, %1, %2;" : "=r"(r) : "r"(a), "r"(b));
    return r;
}
__device__ __forceinline__ uint32_t hfma2(uint32_t a, uint32_t b, uint32_t c) {
    uint32_t r;
    asm("fma.rn.bf16x2 %0, %1, %2, %3;" : "=r"(r) : "r"(a), "r"(b), "r"(c));
    return r;
}
__device__ __forceinline__ uint32_t hfma2_lo(uint32_t a, uint32_t b, uint32_t c) {
    uint32_t r;
    asm("{\n.reg .b16 l, h;\n.reg .b32 t;\nmov.b32 {l, h}, %2;\nmov.b32 t, {l, l};\nfma.rn.bf16x2 %0, %1, t, %3;\n}\n" : "=r"(r) : "r"(a), "r"(b), "r"(c));
    return r;
}
__device__ __forceinline__ uint32_t hfma2_hi(uint32_t a, uint32_t b, uint32_t c) {
    uint32_t r;
    asm("{\n.reg .b16 l, h;\n.reg .b32 t;\nmov.b32 {l, h}, %2;\nmov.b32 t, {h, h};\nfma.rn.bf16x2 %0, %1, t, %3;\n}\n" : "=r"(r) : "r"(a), "r"(b), "r"(c));
    return r;
}
__device__ __forceinline__ uint32_t hadd2(uint32_t a, uint32_t b) {
    uint32_t r;
    asm("add.rn.bf16x2 %0, %1, %2;" : "=r"(r) : "r"(a), "r"(b));
    return r;
}
__device__ __forceinline__ uint32_t hsub2(uint32_t a, uint32_t b) {
    uint32_t r;
    asm("sub.rn.bf16x2 %0, %1, %2;" : "=r"(r) : "r"(a), "r"(b));
    return r;
}
__device__ __forceinline__ float tanh_fast(float x) {
    float r;
    asm("tanh.approx.f32 %0, %1;" : "=f"(r) : "f"(x));
    return r;
}
__device__ __forceinline__ void wg_fence() { asm volatile("wgmma.fence.sync.aligned;" ::: "memory"); }
__device__ __forceinline__ void wg_commit() { asm volatile("wgmma.commit_group.sync.aligned;" ::: "memory"); }
template <int N>
__device__ __forceinline__ void wg_wait() { asm volatile("wgmma.wait_group.sync.aligned %0;" ::"n"(N) : "memory"); }

#define WG_REGS "{%0,%1,%2,%3,%4,%5,%6,%7,%8,%9,%10,%11,%12,%13,%14,%15,%16,%17,%18,%19,%20,%21,%22,%23,%24,%25,%26,%27,%28,%29,%30,%31}"
#define WG_OPS(c) c(d[0]), c(d[1]), c(d[2]), c(d[3]), c(d[4]), c(d[5]), c(d[6]), c(d[7]), c(d[8]), c(d[9]), c(d[10]), \
    c(d[11]), c(d[12]), c(d[13]), c(d[14]), c(d[15]), c(d[16]), c(d[17]), c(d[18]), c(d[19]), c(d[20]), c(d[21]),     \
    c(d[22]), c(d[23]), c(d[24]), c(d[25]), c(d[26]), c(d[27]), c(d[28]), c(d[29]), c(d[30]), c(d[31])
__device__ __forceinline__ void wgmma_first(float* d, const uint32_t* a, uint64_t desc) {
    asm volatile("wgmma.mma_async.sync.aligned.m64n64k16.f32.bf16.bf16 " WG_REGS ", {%32,%33,%34,%35}, %36, 0, 1, 1, 1;"
                 : WG_OPS("+f") : "r"(a[0]), "r"(a[1]), "r"(a[2]), "r"(a[3]), "l"(desc));
}
__device__ __forceinline__ void wgmma_acc(float* d, const uint32_t* a, uint64_t desc) {
    asm volatile("wgmma.mma_async.sync.aligned.m64n64k16.f32.bf16.bf16 " WG_REGS ", {%32,%33,%34,%35}, %36, 1, 1, 1, 1;"
                 : WG_OPS("+f") : "r"(a[0]), "r"(a[1]), "r"(a[2]), "r"(a[3]), "l"(desc));
}
__device__ __forceinline__ void wgmma_k64(float* d, const uint32_t* a, uint64_t desc) {
    wgmma_first(d, a, desc);
    wgmma_acc(d, a + 4, desc + 128);
    wgmma_acc(d, a + 8, desc + 256);
    wgmma_acc(d, a + 12, desc + 384);
}
__device__ __forceinline__ void fence_regs(float* d) { asm volatile("" : WG_OPS("+f")::"memory"); }
__device__ __forceinline__ uint32_t qaxis(float x) {
    const float u = fmaf(x, QINVP, 0.25f);
    const float f = u - ((u + 12582912.f) - 12582912.f);
    return __float_as_uint(fmaf(fabsf(f), 510.f, 12582912.f));
}
__device__ __forceinline__ uint32_t qcode(float x, float y, float z, uint32_t tx) {
    return __byte_perm(__byte_perm(qaxis(x), qaxis(y), 0x3340), qaxis(z), 0x3410) ^ tx;
}
__device__ __forceinline__ bool near_test(uint32_t ca, uint32_t cb, uint32_t tag24, uint32_t& q) {
    const uint32_t D = __vabsdiffu4(ca, cb);
    q = __dp4a(D, D, 0x7FFFFFFFu - QSURE);
    return q <= 0x7FFFFFFFu - QSURE + QTHRESH || ((ca ^ tag24) | (cb ^ tag24)) >= 0x1000000u;
}
__device__ __forceinline__ bool inside(uint32_t rxy, uint32_t rz) {
    const uint32_t qxy = hmul2(rxy, rxy), qz = hmul2(rz, rz);
    return bf_lo(qxy) + bf_hi(qxy) + bf_lo(qz) <= 24.8125f;
}

__device__ __forceinline__ uint32_t lds32(uint32_t addr) {
    uint32_t r;
    asm volatile("ld.shared.u32 %0, [%1];" : "=r"(r) : "r"(addr));
    return r;
}
__device__ __forceinline__ void sts32_if(uint32_t addr, uint32_t v, bool c) {
    asm volatile("{\n.reg .pred p;\nsetp.ne.u32 p, %2, 0;\n@p st.shared.u32 [%0], %1;\n}\n" ::"r"(addr), "r"(v), "r"((uint32_t)c) : "memory");
}
__device__ __forceinline__ void stg128_if(void* ptr, uint4 v, bool c) {
    asm volatile("{\n.reg .pred p;\nsetp.ne.u32 p, %5, 0;\n@p st.relaxed.gpu.global.v4.u32 [%0], {%1,%2,%3,%4};\n}\n"
                 ::"l"(ptr), "r"(v.x), "r"(v.y), "r"(v.z), "r"(v.w), "r"((uint32_t)c) : "memory");
}
__device__ __forceinline__ void lds128(uint32_t addr, uint32_t* r) {
    asm volatile("ld.shared.v4.u32 {%0,%1,%2,%3}, [%4];" : "=r"(r[0]), "=r"(r[1]), "=r"(r[2]), "=r"(r[3]) : "r"(addr) : "memory");
}
template <int NP, int HI, int PAD = 1>
__device__ __forceinline__ void gather(uint32_t dst, const void* base, uint32_t c, uint32_t e) {
#define GATHER_HEAD "{\n.reg .pred p;\n.reg .b32 n;\n.reg .b64 a;\nprmt.b32 n, %2, 0, %3;\nsetp.ne.u32 p, n, 0xFFFF;\nmad.lo.u32 n, n, 512, %4;\nmad.wide.u32 a, n, 1, %1;\n"
#define GATHER_1(P) P "cp.async.cg.shared.global [%0], [a], 16;\n}\n"
#define GATHER_3(P) P "cp.async.cg.shared.global [%0], [a + 128], 16;\n" P "cp.async.cg.shared.global [%0 + 1024], [a + 256], 16;\n" \
                    P "cp.async.cg.shared.global [%0 + 2048], [a + 384], 16;\n}\n"
#define GATHER_ARGS(z) ::"r"(dst), "l"(base), "r"(e), "n"((HI ? 0x32 : 0x10) + z), "r"(c) : "memory"
    if constexpr (NP == 1 && PAD) asm volatile(GATHER_HEAD GATHER_1("@p ") GATHER_ARGS(0x4400));
    if constexpr (NP == 1 && !PAD) asm volatile(GATHER_HEAD GATHER_1("") GATHER_ARGS(0x4400));
    if constexpr (NP == 3 && PAD) asm volatile(GATHER_HEAD GATHER_3("@p ") GATHER_ARGS(0x5500));
    if constexpr (NP == 3 && !PAD) asm volatile(GATHER_HEAD GATHER_3("") GATHER_ARGS(0x4400));
    if constexpr (NP == 4)
        asm volatile(GATHER_HEAD "setp.ge.u32 p, %2, 0x40000000;\ncp.async.cg.shared.global [%0], [a], 16, p;\ncp.async.cg.shared.global [%0 + 1024], [a + 128], 16, p;\n"
                     "cp.async.cg.shared.global [%0 + 2048], [a + 256], 16, p;\ncp.async.cg.shared.global [%0 + 3072], [a + 384], 16, p;\n}\n" GATHER_ARGS(0x4400));
}
__device__ __forceinline__ void cp_commit() { asm volatile("cp.async.commit_group;" ::: "memory"); }
__device__ __forceinline__ void cp_wait1() { asm volatile("cp.async.wait_group 1;" ::: "memory"); }
__device__ __forceinline__ uint32_t hmul2_lo(uint32_t a, uint32_t b) {
    uint32_t r;
    asm("{\n.reg .b16 l, h;\n.reg .b32 t;\nmov.b32 {l, h}, %2;\nmov.b32 t, {l, l};\nmul.rn.bf16x2 %0, %1, t;\n}\n" : "=r"(r) : "r"(a), "r"(b));
    return r;
}
__device__ __forceinline__ void lds2_if(uint32_t a0, uint32_t a1, uint32_t* r, uint32_t c) {
    asm volatile("{\n.reg .pred p;\nsetp.ne.u32 p, %10, 0;\n@p ld.shared.v4.u32 {%0,%1,%2,%3}, [%8];\n@p ld.shared.v4.u32 {%4,%5,%6,%7}, [%9];\n}\n"
                 : "+r"(r[0]), "+r"(r[1]), "+r"(r[2]), "+r"(r[3]), "+r"(r[4]), "+r"(r[5]), "+r"(r[6]), "+r"(r[7])
                 : "r"(a0), "r"(a1), "r"(c) : "memory");
}
__device__ __forceinline__ int fresh_lane() {
    int l;
    asm volatile("mov.u32 %0, %%laneid;" : "=r"(l));
    return l;
}

__device__ __forceinline__ void cold_edges(unsigned char* smem, const Params& p, int lo, int hi, uint32_t tag) {
#pragma unroll 1
    for (int e = lo + threadIdx.x; e < hi; e += THREADS) {
        const int s = p.src[e], d = p.dst[e];
        uint32_t q;
        if (near_test(reinterpret_cast<const uint32_t*>(smem)[s], reinterpret_cast<const uint32_t*>(smem)[d], tag << 24, q)) {
            const uint32_t own = __umulhi((uint32_t)d, p.magic);
            const uint32_t slot4 = atomicAdd(reinterpret_cast<uint32_t*>(smem + SCNT_OFF) + own, 4u);
            uint32_t* line = reinterpret_cast<uint32_t*>(smem + STAGE_OFF) + own * 32;
            if (slot4 < 124) {
                line[slot4 >> 2] = ((uint32_t)s << 15) + ((uint32_t)(d - own * p.NPC) << 6) + tag + (q & 0x80000000u);
            } else {
                uint32_t o = atomicAdd(reinterpret_cast<uint32_t*>(smem + MISC_OFF) + 16, 1u);
                p.g->ovf[(size_t)blockIdx.x * (4 * p.gpc + 4) + o] = make_int2(s, d);
                line[31] = (PAY_MARK << 6) | tag;
            }
        }
    }
}
__device__ __forceinline__ void cold_filter(unsigned char* smem, const Params& p, int e0, int e1, uint32_t tag, int redo) {
    if (redo) {
        if (threadIdx.x < MAXG) reinterpret_cast<uint32_t*>(smem + SCNT_OFF)[threadIdx.x] = 0;
        __syncthreads();
    }
    cold_edges(smem, p, redo ? 4 * e0 : 4 * (e0 + 3 * THREADS), 4 * e1, tag);
    if (blockIdx.x == 0) cold_edges(smem, p, p.E & ~3, p.E, tag);
    __syncthreads();
    if (threadIdx.x == 0) p.g->ovfcnt[blockIdx.x] = reinterpret_cast<uint32_t*>(smem + MISC_OFF)[16];
    __threadfence();
    __syncthreads();
}
__device__ __forceinline__ uint3 geometry(uint32_t rxy, uint32_t rz) {
    const uint32_t qxy = hmul2(rxy, rxy), qz = hmul2(rz, rz);
    float d, id;
    asm("sqrt.approx.ftz.f32 %0, %1;" : "=f"(d) : "f"(rbf16(rbf16(bf_lo(qxy) + bf_hi(qxy) + bf_lo(qz)) + 1e-8f)));
    d = rbf16(d);
    asm("rcp.approx.ftz.f32 %0, %1;" : "=f"(id) : "f"(d));
    const float cs = rbf16(__cosf(rbf16(rbf16(3.14159265358979f * d) * 0.2f)));
    const uint32_t zs = pack2(bf_lo(rz) * id, 0.5f * rbf16(cs + 1.0f) * id);
    return d < 5.0f ? make_uint3(pack2(bf_lo(rxy) * id, bf_hi(rxy) * id), zs, __byte_perm(__float_as_uint(d), zs, 0x7632)) : make_uint3(0, 0, 0);
}
__device__ __forceinline__ void cold_messages(unsigned char* smem, const Params& p, int nn) {
    const int nbase = blockIdx.x * p.NPC, lane = threadIdx.x & 31;
    const uint32_t* box = reinterpret_cast<const uint32_t*>(p.g->xbuf) + blockIdx.x * p.G * 32;
    uint32_t* w = reinterpret_cast<uint32_t*>(smem + RING_OFF);
#pragma unroll 1
    for (int i = threadIdx.x; i < 9728; i += THREADS)
        w[i] = i < 2048 ? reinterpret_cast<const uint32_t*>(p.w1)[i] : i < 8192 ? reinterpret_cast<const uint32_t*>(p.w2)[i - 2048] : reinterpret_cast<const uint32_t*>(p.wr)[i - 8192];
#pragma unroll 1
    for (int i = threadIdx.x; i < nn * 32; i += THREADS) reinterpret_cast<uint4*>(p.out)[nbase * 32 + i] = reinterpret_cast<const uint4*>(p.sv)[nbase * 32 + i];
    __threadfence();
    __syncthreads();
    const float freq = __bfloat162float(p.freqs[lane & 15]);
#pragma unroll 1
    for (int m = -1; m < p.G; m++) {
        const int cnt = m < 0 ? p.G * 32 : (__ldcg(box + m * 32 + 31) >> 6) == PAY_MARK ? __ldcg(&p.g->ovfcnt[m]) : 0;
#pragma unroll 1
        for (int i = threadIdx.x; i - lane < cnt; i += THREADS) {
            int2 e = make_int2(0, -1);
            if (i < cnt) {
                if (m < 0) {
                    const uint32_t x = __ldcg(box + i);
                    e = make_int2((x >> 15) & 0xFFFFu, nbase + ((x >> 6) & 511u));
                } else {
                    e = __ldcg(p.g->ovf + (size_t)m * (4 * p.gpc + 4) + i);
                }
            }
            bool in = (uint32_t)(e.y - nbase) < (uint32_t)nn;
            uint3 geo = make_uint3(0, 0, 0);
            if (in) {
                const uint2 ps = __ldcg(p.g->pos8 + e.x), pd = __ldcg(p.g->pos8 + e.y);
                const uint32_t rxy = hsub2(ps.x, pd.x), rz = hsub2(ps.y, pd.y);
                in = inside(rxy, rz);
                geo = geometry(rxy, rz);
            }
#pragma unroll 1
            for (uint32_t todo = __ballot_sync(0xffffffffu, in); todo; todo &= todo - 1) {
                const int l = __ffs(todo) - 1;
                const uint32_t* row = reinterpret_cast<const uint32_t*>(p.sv) + (size_t)__shfl_sync(0xffffffffu, e.x, l) * 128 + lane;
                uint32_t* orow = reinterpret_cast<uint32_t*>(p.out) + (size_t)__shfl_sync(0xffffffffu, e.y, l) * 128 + lane;
                const uint32_t gx = __shfl_sync(0xffffffffu, geo.x, l), gy = __shfl_sync(0xffffffffu, geo.y, l);
                const float rb = rbf16(__sinf(rbf16(bf_lo(__shfl_sync(0xffffffffu, geo.z, l)) * freq)) * bf_hi(gy));
                uint32_t x = row[0];
                float a[12] = {0, 0, 0, 0, 0, 0, 0, 0, 0, 0, 0, 0};
#pragma unroll 2
                for (int k = 0; k < 64; k++) {
                    const uint32_t u = __shfl_sync(0xffffffffu, x, k >> 1), ww = w[k * 32 + lane];
                    const float f = k & 1 ? bf_hi(u) : bf_lo(u);
                    a[0] = fmaf(f, bf_lo(ww), a[0]); a[1] = fmaf(f, bf_hi(ww), a[1]);
                }
                x = pack2(0.5f * fmaf(a[0], tanh_fast(0.5f * a[0]), a[0]), 0.5f * fmaf(a[1], tanh_fast(0.5f * a[1]), a[1]));
                a[0] = a[1] = 0.f;
#pragma unroll 2
                for (int k = 0; k < 64; k++) {
                    const uint32_t u = __shfl_sync(0xffffffffu, x, k >> 1);
                    const float f = k & 1 ? bf_hi(u) : bf_lo(u), r = __shfl_sync(0xffffffffu, rb, k & 15);
#pragma unroll
                    for (int c = 0; c < 3; c++) {
                        const uint32_t ww = w[2048 + k * 96 + c * 32 + lane], wr = k < 16 ? w[8192 + k * 96 + c * 32 + lane] : 0u;
                        a[2 * c] = fmaf(f, bf_lo(ww), a[2 * c]); a[2 * c + 1] = fmaf(f, bf_hi(ww), a[2 * c + 1]);
                        a[6 + 2 * c] = fmaf(r, bf_lo(wr), a[6 + 2 * c]); a[7 + 2 * c] = fmaf(r, bf_hi(wr), a[7 + 2 * c]);
                    }
                }
                const uint32_t mv = pack2(a[2] * a[8], a[3] * a[9]), mr = pack2(a[4] * a[10], a[5] * a[11]);
                const uint32_t o[4] = {pack2(a[0] * a[6], a[1] * a[7]), hfma2_lo(mr, gx, hmul2(mv, row[32])), hfma2_hi(mr, gx, hmul2(mv, row[64])),
                                       hfma2_lo(mr, gy, hmul2(mv, row[96]))};
#pragma unroll
                for (int c = 0; c < 4; c++) asm volatile("red.global.add.noftz.bf16x2 [%0], %1;" ::"l"(orow + 32 * c), "r"(o[c]) : "memory");
            }
        }
    }
}

#define SPLIT(k) asm volatile("{\n.reg .pred p;\nsetp.eq.u32 p, %0, %1;\n@p trap;\n}" ::"r"(c0), "n"(0x70000 + k) : "memory")
#define PIN8(a) asm volatile("" : "+r"((a)[0]), "+r"((a)[1]), "+r"((a)[2]), "+r"((a)[3]), "+r"((a)[4]), "+r"((a)[5]), "+r"((a)[6]), "+r"((a)[7]))
template <int V> struct IntC { static constexpr int value = V; };

template <int CN, int CE, int CG>
__global__ void __launch_bounds__(THREADS, 1) painn_kernel(const __grid_constant__ Params p) {
    extern __shared__ __align__(1024) unsigned char smem_dyn[];
    unsigned char* const smem = static_cast<unsigned char*>(__cvta_shared_to_generic(SB));
    constexpr uint32_t sb = SB;
    const int tid = threadIdx.x, lane = tid & 31;
    const int warp = __shfl_sync(0xffffffffu, tid >> 5, 0);
    constexpr int CNPC = CG ? (CN + CG - 1) / CG : 1, CGPC = CG ? (CE / 4 + CG - 1) / CG : 1;
    const int b = blockIdx.x, G = CG ? CG : p.G, NPC = CG ? CNPC : p.NPC, N = CG ? CN : p.N, gpc = CG ? CGPC : p.gpc;
    const uint32_t magic = CG ? (uint32_t)(((1ull << 32) + CNPC - 1) / CNPC) : p.magic;
    const bool odd_edges = CG ? (CE & 3) != 0 || CGPC > 3 * THREADS : p.odd_edges;
    const int nbase = b * NPC, nn = min(NPC, N - nbase);
    const int eg0 = b * gpc, eg1 = min((CG ? CE : p.E) >> 2, eg0 + gpc);

    uint4* stage4 = reinterpret_cast<uint4*>(smem + STAGE_OFF);
    uint32_t* ncnt = reinterpret_cast<uint32_t*>(smem + NCNT_OFF);
    uint32_t* misc = reinterpret_cast<uint32_t*>(smem + MISC_OFF);
    const uint32_t bar_tab = sb + BAR_OFF;

    TS0(0);
    int4 es[3], ed[3];
    auto load_edges = [&](int i) {
        const int g = min(eg0 + tid + i * THREADS, eg1 - 1);
        asm volatile("ld.global.cs.v4.u32 {%0,%1,%2,%3}, [%8];\nld.global.cs.v4.u32 {%4,%5,%6,%7}, [%9];"
                     : "=r"(es[i].x), "=r"(es[i].y), "=r"(es[i].z), "=r"(es[i].w), "=r"(ed[i].x), "=r"(ed[i].y), "=r"(ed[i].z), "=r"(ed[i].w)
                     : "l"(reinterpret_cast<const int4*>(p.src) + g), "l"(reinterpret_cast<const int4*>(p.dst) + g) : "memory");
    };
    es[0] = ed[0] = make_int4(0, 0, 0, 0);
    const char* const own = reinterpret_cast<const char*>(p.sv) + (size_t)nbase * 512;
    auto touch = [&](int o) {
        if (o + lane * 256 < nn * 512)
            asm volatile("cp.async.ca.shared.global.L2::256B [%0], [%1], 4;" ::"r"(sb + DUMMY_OFF + 4 * lane), "l"(own + o + lane * 256) : "memory");
    };
    uint4* const xout = p.g->xbuf + ((tid >> 3) * G + b) * 8 + (tid & 7);
    unsigned epoch;
    const uint32_t tbytes = ((N + 3) >> 2) * 16, cut = (tbytes >> 8) * CUT * 16, bar_cut = sb + BAR_OFF + 120;
    {
        uint32_t pxy, pz;
        asm volatile("ld.global.nc.u32 %0, [%3];\nld.global.nc.u32 %1, [%3 + 4];\nld.global.ca.u32 %2, [%4];"
                     : "=r"(pxy), "=r"(pz), "=r"(epoch)
                     : "l"(reinterpret_cast<const uint32_t*>(p.pos) + ((nbase + min(tid, nn - 1)) * 3 >> 1)), "l"(p.g->sync) : "memory");
        const uint32_t sh = ((nbase + tid) & 1) << 4;
        pxy = __funnelshift_r(pxy, pz, sh);
        pz >>= sh;
        const uint32_t code = qcode(bf_lo(pxy), bf_hi(pxy), bf_lo(pz), ((epoch & 31u) ^ 0x6Bu) << 24);
        asm volatile("{\n.reg .pred p;\nsetp.lt.s32 p, %2, %3;\n@p st.global.u32 [%0], %1;\n}\n"
                     ::"l"(reinterpret_cast<uint32_t*>(p.g->table) + nbase + tid), "r"(code), "r"(tid), "r"(nn) : "memory");
        __syncthreads();
        asm volatile("{\n.reg .pred p;\nsetp.eq.u32 p, %1, %2;\n@p red.relaxed.gpu.global.add.u32 [%0], 1;\n}\n" ::"l"(p.g->sync + 1), "r"(tid), "n"(THREADS - 1) : "memory");
        if (tid < THREADS - 32) load_edges(0);
        if (tid < nn) p.g->pos8[nbase + tid] = make_uint2(pxy, pz);
        reinterpret_cast<uint2*>(smem + OPOS_OFF)[tid] = make_uint2(pxy, pz);
    }
    const uint32_t tag = (epoch & 31u) | 32u;
    if (tid == THREADS - 1) {
        TSX(1, 511);
        mbar_init(bar_tab, 1);
        mbar_init(bar_cut, 1);
        mbar_expect_tx(bar_cut, cut);
        mbar_expect_tx(bar_tab, tbytes - cut);
        const unsigned want = (epoch + 1) * G;
        unsigned c;
        int it = smem_u32(smem_dyn) == SB ? 0 : 1 << 22;
        __nanosleep(HDELAY);
        do {
            asm volatile("ld.relaxed.gpu.global.u32 %0, [%1];" : "=r"(c) : "l"(p.g->sync + 1) : "memory");
            if (++it > (1 << 22)) __trap();
        } while (c != want);
        bulk_g2s(sb, p.g->table, cut, bar_cut);
        bulk_g2s(sb + cut, reinterpret_cast<const char*>(p.g->table) + cut, tbytes - cut, bar_tab);
        TSX(2, 511);
    }
    if (warp == 14) {
#pragma unroll 1
        for (int c = b * 32 + lane; c < RING_OFF / 16; c += G * 32) {
            const int row = c >> 3, j = (c ^ row) & 7;
            uint4 v;
            if (c < 512) {
                const uint32_t half = 0x3F003F00u;
                v = __ldg(reinterpret_cast<const uint4*>(p.w1) + row * 8 + j);
                v = make_uint4(hmul2(v.x, half), hmul2(v.y, half), hmul2(v.z, half), hmul2(v.w, half));
            } else {
                const uint32_t* q = (c < 2048 ? reinterpret_cast<const uint32_t*>(p.w2) + (row & 63) * 96 + ((row >> 6) - 1) * 32
                                              : reinterpret_cast<const uint32_t*>(p.wr) + (row & 15) * 96 + ((row >> 4) - 16) * 32) + (j & 4) * 4 + (j & 3);
                v = make_uint4(__ldg(q), __ldg(q + 4), __ldg(q + 8), __ldg(q + 12));
            }
            p.g->wimg[c] = v;
        }
    }
    if (tid == 416) {
#pragma unroll
        for (int i = 0; i < FLIGHT + 2; i++) mbar_init(sb + BAR_OFF + 8 + 8 * i, i ? 1 : 15);
    }
    ncnt[tid] = tid < 480 ? 0 : 1024;
    if (tid < MAXG + 32) reinterpret_cast<uint32_t*>(smem + SCNT_OFF)[tid] = tid < MAXG ? 0 : 128;
    if (tid < 128) misc[tid] = 0;
    {
        const uint32_t inv = (PAY_INVALID << 6) | tag;
        stage4[tid] = stage4[tid + THREADS] = make_uint4(inv, inv, inv, inv);
        if (tid < MAXG * 8 - 2 * THREADS) stage4[tid + 2 * THREADS] = make_uint4(inv, inv, inv, inv);
    }
    __syncthreads();
    if ((tid >> 4) == 29) asm volatile("cp.async.ca.shared.global [%0], [%1], 4;" ::"r"(sb + FREQ_OFF + 8 * (tid & 14) + 4 * (tid & 1)),
                              "l"(reinterpret_cast<const uint32_t*>(p.freqs) + ((tid & 7) >> 1) + (tid & 1) * 4) : "memory");
    if (warp == 15) load_edges(0);
    if (warp < 8) mbar_wait(bar_cut, 0);
    load_edges(1);
    load_edges(2);
    if (tid == 416) asm volatile("fence.acq_rel.gpu;" ::: "memory");
    if (warp >= 8) mbar_wait(bar_cut, 0);
#pragma unroll
    for (int i = 0; i < 3; i++) stg128_if(xout + i * G * THREADS, make_uint4(0, 0, 0, 0), tid + i * THREADS < G * 8);
    mbar_wait(bar_tab, 0);
    TS0(3);
    if (warp == 15) {
#pragma unroll
        for (int i = 0; i < TOUCH; i++) touch(i * 8192);
    }

    bool full = false;
#pragma unroll 1
    for (int i = 0, g = eg0 + tid; i < 3; i++, g += THREADS) {
        const int s[4] = {es[0].x, es[0].y, es[0].z, es[0].w}, d[4] = {ed[0].x, ed[0].y, ed[0].z, ed[0].w};
        uint32_t ca[4], cb[4], own[4], sl[4], q[4];
        bool c[4];
#pragma unroll
        for (int j = 0; j < 4; j++) { ca[j] = lds32(sb + 4 * s[j]); cb[j] = lds32(sb + 4 * d[j]); }
#pragma unroll
        for (int j = 0; j < 4; j++) {
            c[j] = near_test(ca[j], cb[j], tag << 24, q[j]) && g < eg1;
            own[j] = __umulhi((uint32_t)d[j], magic);
            sl[j] = atomicAdd(reinterpret_cast<uint32_t*>(smem + SCNT_OFF) + (c[j] ? own[j] : MAXG + lane), 4u);
        }
#pragma unroll
        for (int j = 0; j < 4; j++)
            sts32_if(sb + STAGE_OFF + own[j] * 128 + sl[j], own[j] * (uint32_t)(-64 * NPC) + (((uint32_t)s[j] << 15) + (((uint32_t)d[j] << 6) + ((q[j] & 0x80000000u) | tag))),
                     sl[j] < 124);
        full |= (sl[0] == 124) | (sl[1] == 124) | (sl[2] == 124) | (sl[3] == 124);
        es[0] = es[1]; es[1] = es[2];
        ed[0] = ed[1]; ed[1] = ed[2];
    }
    {
        const int redo = __syncthreads_or(full);
        if (__builtin_expect(redo || odd_edges, 0)) cold_filter(smem, p, eg0, eg1, tag, redo);
    }
    TS0(4);
#pragma unroll
    for (int i = 0; i < 3; i++) stg128_if(xout + i * G * THREADS, stage4[tid + i * THREADS], tid + i * THREADS < G * 8);
    __syncthreads();
#pragma unroll
    for (int i = -2; i < 2; i++) {
        const int c = tid + i * THREADS;
        const uint32_t x = c < (SN_OFF - STAGE_OFF) / 16 ? 0u : 0xFFFFFFFFu;
        if (c >= (SREC_OFF - STAGE_OFF) / 16) stage4[c] = make_uint4(x, x, x, x);
    }
    uint32_t key[4] = {0, 0, 0, 0};
    uint2 pr[4];
    const uint32_t gp = sb + RING_OFF + 2048 + (warp < 4 * NWG ? warp * 12288 : (warp & 3) * 12288 + 2048) + lane * 16;
    uint32_t pk = 0;
    if (warp == 15) {
        if (lane == 0) {
            int o = TOUCH * 8192;
#pragma unroll 1
            while (o < nn * 512 && !mbar_test(sb + BAR_OFF + 8, 0)) {
                const uint32_t bar = sb + BAR_OFF + 16 + 8 * (pk % FLIGHT);
                if (!mbar_test(bar, ~(pk / FLIGHT) & 1)) continue;
                const int n = min(4096, nn * 512 - o);
                mbar_expect_tx(bar, n);
                bulk_g2s(sb + DUMMY_OFF, own + o, n, bar);
                o += n;
                pk++;
            }
            misc[3] = pk;
        }
        __syncwarp();
    } else {
    __nanosleep(PDELAY);
    TS0(5);

    {
        const int LPW = (G + 14) / 15;
        uint32_t ew[3][4], bad[3];
        const uint4* cp = p.g->xbuf + (b * G + warp * LPW) * 8 + lane;
#pragma unroll
        for (int i = 0; i < 3; i++) {
            bad[i] = lane + 32 * i < min(LPW, G - warp * LPW) * 8;
            ew[i][0] = ew[i][1] = ew[i][2] = ew[i][3] = (PAY_INVALID << 6) | tag;
        }
        int it = 0;
#pragma unroll 1
        do {
#pragma unroll
            for (int i = 0; i < 3; i++)
                asm volatile("{\n.reg .pred p;\nsetp.ne.u32 p, %5, 0;\n@p ld.relaxed.gpu.global.v4.u32 {%0,%1,%2,%3}, [%4];\n}\n"
                             : "+r"(ew[i][0]), "+r"(ew[i][1]), "+r"(ew[i][2]), "+r"(ew[i][3]) : "l"(cp + 32 * i), "r"(bad[i]) : "memory");
#pragma unroll
            for (int i = 0; i < 3; i++) bad[i] = ((ew[i][0] ^ tag) | (ew[i][1] ^ tag) | (ew[i][2] ^ tag) | (ew[i][3] ^ tag)) & 63u;
            if (++it > (1 << 22)) __trap();
        } while (__any_sync(0xffffffffu, bad[0] | bad[1] | bad[2]));
        TSX(21, 0); TSX(22, 448);
        uint4* pack = reinterpret_cast<uint4*>(smem + PACK_OFF);
        int nch = 0;
        uint32_t at[3];
#pragma unroll
        for (int i = 0; i < 3; i++) {
            const uint32_t m = __ballot_sync(0xffffffffu, ew[i][0] < (PAY_MARK << 6));
            at[i] = nch + __popc(m & ((1u << lane) - 1));
            nch += __popc(m);
        }
        if (__builtin_expect(nch > 32, 0)) {
#pragma unroll 1
            for (int i = 0; i < 3; i++) {
                if (ew[0][0] < (PAY_MARK << 6) && at[0] >= 32) at[0] = (15 - warp) * 32 - 1 - min(atomicAdd(&misc[1], 1u), 31u);
                const uint32_t x = at[0], y = ew[0][0];
                at[0] = at[1]; at[1] = at[2]; at[2] = x;
                ew[0][0] = ew[1][0]; ew[1][0] = ew[2][0]; ew[2][0] = y;
            }
        }
#pragma unroll
        for (int i = 0; i < 3; i++) {
            asm volatile("{\n.reg .pred p;\nsetp.lt.u32 p, %1, %5;\n@p st.shared.v4.u32 [%0], {%1,%2,%3,%4};\n}\n"
                         ::"r"(sb + PACK_OFF + (warp * 32 + at[i]) * 16), "r"(ew[i][0]), "r"(ew[i][1]), "r"(ew[i][2]), "r"(ew[i][3]), "n"(PAY_MARK << 6) : "memory");
            sts32_if(sb + MISC_OFF + 4 * 17, 1, (ew[i][3] >> 6) == PAY_MARK);
        }
        bool have = lane < nch;
        if (warp == 14) {
            asm volatile("bar.sync 7, 480;" ::: "memory");
            const uint32_t extra = misc[1];
            if (nch + extra > 32) misc[18] = 1;
            have = have || lane + extra >= 32;
        } else {
            asm volatile("bar.arrive 7, 480;" ::: "memory");
        }
        __syncwarp();
        uint32_t w[4], rk[4];
        bool in[4];
        {
            const uint4 x = pack[tid];
            w[0] = have ? x.x : ~0u; w[1] = have ? x.y : ~0u; w[2] = have ? x.z : ~0u; w[3] = have ? x.w : ~0u;
        }
        auto fetch = [&](int j, bool c) {
            asm volatile("{\n.reg .pred p;\nsetp.ne.u32 p, %2, 0;\n@p cp.async.cg.shared.global [%0], [%1], 16;\n}\n"
                         ::"r"(gp + j * 512), "l"(reinterpret_cast<const uint4*>(p.g->pos8) + ((w[j] >> 16) & 0x7FFFu)), "r"((uint32_t)c) : "memory");
        };
#pragma unroll
        for (int j = 0; j < 4; j++) fetch(j, (int)w[j] < (int)(PAY_MARK << 6));
#pragma unroll
        for (int j = 0; j < 4; j++) pr[j] = reinterpret_cast<const uint2*>(smem + OPOS_OFF)[(w[j] >> 6) & 511u];
        uint32_t ca[4];
#pragma unroll
        for (int j = 0; j < 4; j++) {
            key[j] = ((w[j] >> 15) & 0xFFFFu) | ((w[j] << 10) & 0x1FF0000u);
            ca[j] = sb + NCNT_OFF + ((w[j] >> 4) & 0x7FCu);
            asm volatile("" : "+r"(key[j]), "+r"(ca[j]));
        }
        asm volatile("{\n.reg .pred p;\nsetp.eq.u32 p, %0, -1;\n@p trap;\n}" ::"r"(nch) : "memory");
        asm volatile("cp.async.wait_all;" ::: "memory");
        TSX(23, 0); TSX(24, 448);
        asm volatile("{\n.reg .pred p;\nsetp.eq.u32 p, %1, 0;\n@p mbarrier.arrive.shared::cta.b64 _, [%0];\n}\n" ::"r"(sb + BAR_OFF + 8), "r"(lane) : "memory");
#pragma unroll
        for (int j = 0; j < 4; j++) {
            uint2 ps;
            asm volatile("ld.shared.v2.u32 {%0,%1}, [%2];" : "=r"(ps.x), "=r"(ps.y) : "r"(gp + j * 512 + ((w[j] >> 12) & 8)) : "memory");
            in[j] = ((int)w[j] >= 0) | (((int)w[j] < (int)(PAY_MARK << 6)) & inside(hsub2(ps.x, pr[j].x), hsub2(ps.y, pr[j].y)));
        }
#pragma unroll
        for (int j = 0; j < 4; j++)
            asm volatile("atom.shared.add.u32 %0, [%1], 1;" : "=r"(rk[j]) : "r"(in[j] ? ca[j] : sb + NCNT_OFF + 4 * (480 + lane)) : "memory");
#pragma unroll
        for (int j = 0; j < 4; j++) {
            rk[j] = rk[j] < SPL ? 2 * rk[j] : min(2 * rk[j] - (2 * SPL - 1), 126u);
            asm volatile("red.shared.add.u32 [%0 + %1], 1;" ::"r"(rk[j] & 2 ? 124u : rk[j] & 60u), "n"(SB + MISC_OFF + 128) : "memory");
            key[j] += rk[j] << 25;
        }
#pragma unroll
        for (int j = 0; j < 4; j++) fetch(j, (int)w[j] >= 0);
        cp_commit();
    }
    }
    __syncthreads();
    TS0(6);
    uint32_t deg[5];
    deg[4] = lds32(sb + NCNT_OFF + 4 * tid);
#pragma unroll
    for (int j = 0; j < 4; j++) deg[j] = lds32(sb + NCNT_OFF + ((key[j] >> 14) & 0x7FCu));
    if (tid == THREADS - 33) {
        if (b == 0) p.g->sync[0] = epoch + 1;
        asm volatile("fence.proxy.async.global;" ::: "memory");
        mbar_expect_tx(bar_tab, RING_OFF);
        bulk_g2s(sb, p.g->wimg, RING_OFF, bar_tab);
    }
    __syncwarp();
    uint32_t dst = sb + RING_OFF + warp * 12288 + (lane >> 3) * 256 + (((lane & 7) ^ (lane >> 3)) << 4), l7 = (lane & 7) * 16, g32 = (lane >> 2) * 32;
    uint32_t e0, e1, n0, n1;
    auto sources = [&](uint32_t c) {
        asm volatile("{\n.reg .b32 a;\nlop3.b32 a, %4, %5, 0xFFC0, 0xA8;\nshr.u32 a, a, 2;\nld.shared.v4.u32 {%0,%1,%2,%3}, [a + %6];\n}\n"
                     : "=r"(e0), "=r"(n0), "=r"(e1), "=r"(n1) : "r"(c), "r"(g32), "n"(SB + SN_OFF));
    };
    auto load_s = [&](auto pad) {
        gather<1, 0, pad.value>(dst, p.sv, l7, e0); gather<1, 1, pad.value>(dst + 1024, p.sv, l7, e0);
        gather<1, 0, pad.value>((dst ^ 64) + 128, p.sv, l7, e1); gather<1, 1, pad.value>((dst ^ 64) + 1152, p.sv, l7, e1);
    };
    auto load_o = [&]() {
        gather<4, 0>(dst + 8192, p.sv, l7, n0); gather<4, 0>((dst ^ 64) + 8320, p.sv, l7, n1);
    };
    auto load_v = [&](auto pad) {
        gather<3, 0, pad.value>(dst + 2048, p.sv, l7, e0); gather<3, 1, pad.value>(dst + 5120, p.sv, l7, e0);
        gather<3, 0, pad.value>((dst ^ 64) + 2176, p.sv, l7, e1); gather<3, 1, pad.value>((dst ^ 64) + 5248, p.sv, l7, e1);
        cp_commit();
    };
    const int ng = (misc[32] + 7) >> 3;
    const int give = max(min(ng - max((int)(misc[33] + 7) >> 3, 4 * NWG), GIVE), 0);
    if (warp == 15) {
        const uint32_t cnt = lane < 16 ? (misc[32 + lane] + 7) >> 3 : 0u;
        uint32_t z = cnt;
#pragma unroll
        for (int o = 1; o < 16; o <<= 1) {
            const uint32_t y = __shfl_up_sync(0xffffffffu, z, o);
            if (lane >= o) z += y;
        }
        misc[96 + lane] = lane < 16 ? 64 * (z - cnt) : 64 * (MAXROW + 1);
        asm volatile("bar.arrive 5, 512;" ::: "memory");
        if (lane == 15) {
            const bool cold = cnt || z > MAXROW || misc[31 + SPL / 2] > 32 || misc[17] || misc[18];
            misc[18] = cold;
            asm volatile("st.relaxed.gpu.global.u32 [%0], %1;" ::"l"(p.g->rows + b), "r"(~epoch << 16 | (cold || ng < 4 * NWG ? 255 : give << 8 | z)) : "memory");
        }
        pk = (z - cnt) << 8 | __shfl_down_sync(0xffffffffu, cnt, 1) << 24;
    } else {
        if (warp * 32 < nn) {
            const uint32_t c = deg[4], st = tid < nn ? (min(c, (uint32_t)SPL) + 1) >> 1 : 17u;
            const uint32_t same = __match_any_sync(0xffffffffu, st), first = __ffs(same) - 1;
            uint32_t r, node = nbase + tid;
            asm volatile("atom.shared.add.u32 %0, [%1], %2;" : "=r"(r)
                         : "r"(lane == first ? sb + MISC_OFF + 4 * (64 + st) : sb + NCNT_OFF + 4 * (480 + lane)), "r"(__popc(same)) : "memory");
            r = __shfl_sync(0xffffffffu, r, first) + __popc(same & ((1u << lane) - 1)) + misc[32 + st];
            if (__builtin_expect(c > SPL, 0)) {
                const uint32_t s2 = min((c - SPL + 1) >> 1, 16u), r2 = misc[32 + s2] + atomicAdd(&misc[64 + s2], 1u), k = atomicAdd(&misc[2], 1u);
                reinterpret_cast<uint32_t*>(smem + SCNT_OFF)[k & 31] = node;
                node |= NODE_SPLIT;
                ncnt[1024 + tid] = 8 * r2;
                reinterpret_cast<uint32_t*>(smem + SN_OFF)[(r2 & 511) * 2 + 1] = node;
            }
            if (tid < nn) {
                ncnt[512 + tid] = 8 * r;
                reinterpret_cast<uint32_t*>(smem + SN_OFF)[(r & 511) * 2 + 1] = node;
            }
        }
#pragma unroll
        for (int j = 0; j < 4; j++) {
            const uint32_t c = deg[j];
            asm volatile("{\n.reg .pred p;\n.reg .b64 a;\nsetp.ge.u32 p, %0, %3;\nsetp.lt.and.u32 p, %1, 0x8000000, p;\nmad.wide.u32 a, %4, 512, %2;\n@p prefetch.global.L2 [a];\n"
                         "}\n" ::"r"(c), "r"(key[j]), "l"(p.sv), "n"(BIG), "r"(key[j] & 0xFFFFu) : "memory");
        }
        asm volatile("bar.sync 5, 512;" ::: "memory");
        uint32_t slot[4];
#pragma unroll
        for (int j = 0; j < 4; j++) slot[j] = min(misc[96 + (key[j] >> 27)] + (ncnt[512 + ((key[j] >> 16) & 1023)] & 0xFFF8u), 64u * (MAXROW + 1)) + ((key[j] >> 25) & 2);
#pragma unroll
        for (int j = 0; j < 4; j++) {
            *reinterpret_cast<uint16_t*>(smem + SN_OFF + slot[j]) = (uint16_t)key[j];
            slot[j] += slot[j] & 2;
        }
        asm volatile("bar.sync 6, 480;" ::: "memory");
        TS0(7);
        if (warp < 4 * NWG) {
            sources((warp < ng ? warp : MAXROW) << 8);
            e0 = __vminu2(e0, (N - 1) * 0x10001u);
            e1 = __vminu2(e1, (N - 1) * 0x10001u);
            load_s(IntC<0>{});
            cp_commit();
            load_o();
            cp_commit();
            asm volatile("cp.async.wait_group 2;" ::: "memory");
        } else {
            asm volatile("cp.async.wait_all;" ::: "memory");
        }
        uint2 ps[4];
#pragma unroll
        for (int j = 0; j < 4; j++)
            asm volatile("ld.shared.v2.u32 {%0,%1}, [%2];" : "=r"(ps[j].x), "=r"(ps[j].y) : "r"(gp + j * 512 + (key[j] & 1) * 8) : "memory");
        TSX(9, 0);
#pragma unroll 1
        for (int i = 0; i < 2; i++) {
#pragma unroll
            for (int u = 0; u < 2; u++) {
                const uint3 geo = geometry(hsub2(ps[u].x, pr[u].x), hsub2(ps[u].y, pr[u].y));
                *reinterpret_cast<uint2*>(smem + SREC_OFF + 2 * slot[u]) = make_uint2(geo.x, geo.y);
                *reinterpret_cast<uint32_t*>(smem + SD_OFF + slot[u]) = geo.z;
                ps[u] = ps[u + 2];
                pr[u] = pr[u + 2];
                slot[u] = slot[u + 2];
            }
        }
    }
    if (warp == 15) { __syncwarp(); asm volatile("bar.arrive 4, 512;" ::: "memory"); }
    else asm volatile("bar.sync 4, 512;" ::: "memory");
    TS0(8);
    auto drain = [&](int i) { if (i < FLIGHT) mbar_wait(sb + BAR_OFF + 16 + 8 * i, ~((misc[3] + FLIGHT - 1 - i) / FLIGHT) & 1); };
    if (__builtin_expect(misc[18], 0)) {
        drain(warp);
        asm volatile("cp.async.wait_all;" ::: "memory");
        __syncthreads();
        cold_messages(smem, p, nn);
        mbar_wait(bar_tab, 1);
        return;
    }

    if (warp < 4 * NWG) {
        asm volatile("setmaxnreg.inc.sync.aligned.u32 %0;" ::"n"(REG_C));
        const int lane = fresh_lane();
        const int g = lane >> 2, q = lane & 3;
        const uint64_t dW1 = p.desc0, dW2 = dW1 + (W2_OFF >> 4), dWR = dW1 + (WR_OFF >> 4);
        const uint32_t ring = sb + RING_OFF + warp * 12288;
        const uint32_t vrow = pin(ring + g * 128 + ((q ^ ((g & 1) << 2) ^ (g >> 1)) << 4));
        const uint32_t mrow = pin(ring + (lane & 15) * 128 + (((lane >> 4) ^ ((lane & 1) << 2) ^ ((lane & 7) >> 1)) << 4));
        dst = pin(ring + (lane >> 3) * 256 + (((lane & 7) ^ (lane >> 3)) << 4)); l7 = pin((lane & 7) * 16); g32 = pin(g * 32);
        uint32_t ctl = sb + CTL_OFF + warp * 4;
        auto control = [&](uint32_t c, uint32_t at) {
            int it = 0;
#pragma unroll 1
            while (__builtin_expect(c == 0xFFFFFFFFu, 0)) {
                asm volatile("ld.volatile.shared.u32 %0, [%1];" : "=r"(c) : "r"(at) : "memory");
                c = __reduce_or_sync(0xffffffffu, c);
                if (++it > (1 << 24)) __trap();
            }
            return c;
        };
        uint32_t c0 = control(0xFFFFFFFFu, ctl), c1 = control(0xFFFFFFFFu, ctl + 64);
        if (warp >= 8) asm volatile("bar.arrive 1, 256;" ::: "memory");
        uint32_t acc[32];
        float P[32], W[32];
#pragma unroll
        for (int i = 0; i < 32; i++) { acc[i] = 0; P[i] = W[i] = 0.f; }
        mbar_wait(bar_tab, 1);
        sources(c0);
        e0 = __vminu2(e0, (N - 1) * 0x10001u);
        e1 = __vminu2(e1, (N - 1) * 0x10001u);
        if (warp >= 8) asm volatile("cp.async.wait_all;" ::: "memory");
        else if (warp >= 4) cp_wait1();
        load_v(IntC<0>{});
        auto finish = [&](uint32_t c, uint32_t node) {
            if (c & ST_CLOSE) {
                uint64_t op[2];
                asm("{\n.reg .b32 a;\nmad.lo.u32 a, %2, 512, %3;\nmad.wide.u32 %0, a, 1, %4;\nxor.b32 a, a, 64;\nmad.wide.u32 %1, a, 1, %4;\n}\n"
                    : "=l"(op[0]), "=l"(op[1]) : "r"(node), "r"(l7), "l"(p.out));
#pragma unroll
                for (int k = 0; k < 8; k++) {
                    uint32_t x[4];
#pragma unroll
                    for (int i = 0; i < 4; i++) x[i] = l7 & 64 ? acc[4 * (k ^ 1) + i] : acc[4 * k + i];
                    asm volatile("{\n.reg .pred p;\nsetp.lt.u32 p, %5, %6;\n@p st.global.cs.v4.u32 [%0], {%1,%2,%3,%4};\n}\n"
                                 ::"l"(op[k & 1] + 128 * (k >> 1)), "r"(x[0]), "r"(x[1]), "r"(x[2]), "r"(x[3]), "r"(node), "n"(NODE_SPLIT) : "memory");
                }
                if (__builtin_expect(__any_sync(0xffffffffu, (int)node >= (int)NODE_SPLIT), 0)) {
                    mbar_wait(sb + BAR_OFF + 16 + 8 * FLIGHT, 0);
                    if ((int)node >= (int)NODE_SPLIT) {
#pragma unroll
                        for (int k = 0; k < 8; k++)
                            asm volatile("red.global.add.noftz.v4.bf16x2 [%0], {%1,%2,%3,%4};" ::"l"((op[0] & ~64ull) + 64 * k), "r"(acc[4 * k]), "r"(acc[4 * k + 1]), "r"(acc[4 * k + 2]), "r"(acc[4 * k + 3]) : "memory");
                    }
                    __syncwarp();
                }
            }
        };
#pragma unroll 1
        while ((int)c0 >= 0) {
            uint32_t a[16], h[16], rf[4], rr[4], m[16];
            TRW(ctl);
            uint32_t dd[2], f01, f23;
            asm volatile("ld.shared.v2.u32 {%0,%1}, [%2 + %3];" : "=r"(dd[0]), "=r"(dd[1]) : "r"(((c0 & 0xFF00) | g32) >> 2), "n"(SB + SD_OFF));
            asm volatile("ld.shared.v2.u32 {%0,%1}, [%2 + %3];" : "=r"(f01), "=r"(f23) : "r"(l7), "n"(SB + FREQ_OFF));
            sources(c1);
            asm volatile("cp.async.wait_group 2;" ::: "memory");
            __syncwarp();
#pragma unroll
            for (int i = 0; i < 4; i++) ldsm4(mrow ^ (i << 5), a + 4 * i);
            wg_fence();
            wgmma_k64(P, a, dW1);
            wg_commit();
            SPLIT(1);
#pragma unroll
            for (int hh = 0; hh < 2; hh++) {
                const float sc = bf_hi(dd[hh]);
                const uint32_t x01 = hmul2_lo(f01, dd[hh]), x23 = hmul2_lo(f23, dd[hh]);
                rf[hh] = pack2(__sinf(bf_lo(x01)) * sc, __sinf(bf_hi(x01)) * sc);
                rf[2 + hh] = pack2(__sinf(bf_lo(x23)) * sc, __sinf(bf_hi(x23)) * sc);
            }
            asm volatile("" : "+r"(rf[0]), "+r"(rf[1]), "+r"(rf[2]), "+r"(rf[3]));
            asm volatile("bar.sync %0, 256;" ::"r"(1 + (warp >> 2)) : "memory");
            SPLIT(2);
            wg_wait<0>();
            fence_regs(P);
#pragma unroll
            for (int i = 0; i < 16; i++)
                h[i] = pack2(fmaf(P[2 * i], tanh_fast(P[2 * i]), P[2 * i]), fmaf(P[2 * i + 1], tanh_fast(P[2 * i + 1]), P[2 * i + 1]));
            wg_fence();
            wgmma_k64(P, h, dW2 + 1024);
            wgmma_first(W, rf, dWR + 256);
            wg_commit();
            asm volatile("bar.arrive %0, 256;" ::"r"((c0 >> 4) & 3) : "memory");
            SPLIT(3);
            cp_wait1();
            __syncwarp();
#pragma unroll
            for (int k = 0; k < 4; k++) lds2_if(vrow + 8192 + 1024 * k, (vrow ^ 64) + 8192 + 1024 * k, acc + 8 * k, c0 & ST_START);
            lds128(sb + SREC_OFF + (((c0 & 0xFF00) | g32) >> 1), rr);
            uint32_t c2 = lds32(ctl + 128);
            __syncwarp();
            load_s(IntC<1>{});
            cp_commit();
            if (c1 & ST_START) load_o();
            cp_commit();
            wg_wait<0>();
            fence_regs(P); fence_regs(W);
#pragma unroll
            for (int j = 0; j < 8; j++) {
                m[j] = pack2(P[4 * j] * W[4 * j], P[4 * j + 1] * W[4 * j + 1]);
                m[8 + j] = pack2(P[4 * j + 2] * W[4 * j + 2], P[4 * j + 3] * W[4 * j + 3]);
            }
            wg_fence();
            wgmma_k64(P, h, dW2);
            wgmma_first(W, rf, dWR);
            wg_commit();
            SPLIT(4);
            PIN8(m); PIN8(m + 8);
            c2 = __reduce_or_sync(0xffffffffu, c2);
#pragma unroll
            for (int k = 1; k < 4; k++)
#pragma unroll
                for (int j = 0; j < 8; j++) {
                    const uint32_t x = k == 1 ? hfma2_lo(m[j], rr[0], acc[8 * k + j]) : k == 2 ? hfma2_hi(m[j], rr[0], acc[8 * k + j]) : hfma2_lo(m[j], rr[1], acc[8 * k + j]);
                    acc[8 * k + j] = k == 1 ? hfma2_lo(m[8 + j], rr[2], x) : k == 2 ? hfma2_hi(m[8 + j], rr[2], x) : hfma2_lo(m[8 + j], rr[3], x);
                }
            PIN8(acc + 8); PIN8(acc + 16); PIN8(acc + 24);
            c2 = control(c2, ctl + 128);
            wg_wait<0>();
            fence_regs(P); fence_regs(W);
#pragma unroll
            for (int j = 0; j < 8; j++)
                acc[j] = hadd2(acc[j], pack2(fmaf(P[4 * j], W[4 * j], P[4 * j + 2] * W[4 * j + 2]), fmaf(P[4 * j + 1], W[4 * j + 1], P[4 * j + 3] * W[4 * j + 3])));
            wg_fence();
            wgmma_k64(P, h, dW2 + 512);
            wgmma_first(W, rf, dWR + 128);
            wg_commit();
            SPLIT(6);
            asm volatile("cp.async.wait_group 2;" ::: "memory");
            __syncwarp();
            uint32_t v[4][16];
#pragma unroll
            for (int i = 0; i < NPRE; i++) lds128((vrow ^ (64 * (i & 1))) + 2048 + 1024 * (i >> 2) + 3072 * ((i >> 1) & 1), v[1 + (i >> 2)] + 4 * (i & 3));
            wg_wait<0>();
            fence_regs(P); fence_regs(W);
#pragma unroll
            for (int j = 0; j < 8; j++) {
                m[j] = pack2(P[4 * j] * W[4 * j], P[4 * j + 1] * W[4 * j + 1]);
                m[8 + j] = pack2(P[4 * j + 2] * W[4 * j + 2], P[4 * j + 3] * W[4 * j + 3]);
            }
#pragma unroll
            for (int i = NPRE; i < 12; i++) lds128((vrow ^ (64 * (i & 1))) + 2048 + 1024 * (i >> 2) + 3072 * ((i >> 1) & 1), v[1 + (i >> 2)] + 4 * (i & 3));
            sources(c1);
            const uint32_t node = lds32(sb + SN_OFF + 4 + (((c0 >> 16) | g32) >> 2));
            __syncwarp();
            load_v(IntC<1>{});
#pragma unroll
            for (int k = 1; k < 4; k++)
#pragma unroll
                for (int j = 0; j < 8; j++) acc[8 * k + j] = hfma2(m[8 + j], v[k][8 + j], hfma2(m[j], v[k][j], acc[8 * k + j]));
            finish(c0, node);
            ctl += 64;
            c0 = c1;
            c1 = c2;
        }
        asm volatile("cp.async.wait_all;" ::: "memory");
        TRW(ctl);
        TSX(11, 0); TSX(12, 128); TSX(13, 256);
    } else {
        asm volatile("setmaxnreg.dec.sync.aligned.u32 %0;" ::"n"(REG_H));
        const int lane = fresh_lane();
        const uint32_t chunk = sb + (lane & 8 ? (lane & 4 ? SN_OFF : SD_OFF) + (lane & 3) * 16 : SREC_OFF + (lane & 7) * 16), pitch = lane & 8 ? 64 : 128;
        if (warp == 12) {
#pragma unroll 1
            for (int i = 0; i < (int)misc[2]; i++) {
                const uint32_t n = reinterpret_cast<const uint32_t*>(smem + SCNT_OFF)[i] * 32 + lane;
                reinterpret_cast<uint4*>(p.out)[n] = reinterpret_cast<const uint4*>(p.sv)[n];
            }
#pragma unroll 1
            for (int i = lane >> 4; i < give; i += 2) {
                uint32_t x[4];
                lds128(chunk + (ng - 1 - i) * pitch, x);
                p.g->pool[(b * GIVE + i) * 16 + (lane & 15)] = make_uint4(x[0], x[1], x[2], x[3]);
            }
            __threadfence();
            __syncwarp();
            if (lane == 0) {
                asm volatile("st.relaxed.gpu.global.u32 [%0], %1;" ::"l"(p.g->ready + b), "r"(~epoch) : "memory");
                mbar_arrive(sb + BAR_OFF + 16 + 8 * FLIGHT);
            }
        }
        if (warp == 15) {
            int k = lane < 4 * NWG ? lane : 255, next = 4 * NWG, j = 0, mine = ng - give, end = -1, take = 0;
            uint32_t busy, at = sb + CTL_OFF + 4 * lane, from = 0;
#pragma unroll 1
            do {
                if (next > mine && end < 0) {
                    end = mine = ng;
                    const int peer = b % 5 + 5 * lane;
                    uint32_t x = 255;
                    int it = 0;
                    if (peer < G) {
#pragma unroll 1
                        do {
                            asm volatile("ld.relaxed.gpu.global.u32 %0, [%1];" : "=r"(x) : "l"(p.g->rows + peer) : "memory");
                            if (++it > (1 << 22)) __trap();
                        } while ((x >> 16) != (~epoch & 0xFFFFu));
                    }
                    const int r = x & 255, n = __popc(__ballot_sync(0xffffffffu, r != 255));
                    const int level = min(((__reduce_add_sync(0xffffffffu, r != 255 ? r : 0) + n - 1) / max(n, 1) + 3) & ~3, MAXROW);
                    const uint32_t ed = r > level ? min(r - level, (int)(x >> 8) & 255) : min(level - r, ROOM) << 16;
                    uint32_t z = ed;
#pragma unroll
                    for (int o = 1; o < 32; o <<= 1) {
                        const uint32_t y = __shfl_up_sync(0xffffffffu, z, o);
                        if (lane >= o) z += y;
                    }
                    const uint32_t all = __shfl_sync(0xffffffffu, z, 31), moved = min(all & 0xFFFFu, all >> 16);
                    const uint32_t me = __shfl_sync(0xffffffffu, ed, b / 5), mz = __shfl_sync(0xffffffffu, z, b / 5) - me;
                    end = mine = ng - (min((mz + me) & 0xFFFFu, moved) - min(mz & 0xFFFFu, moved));
#pragma unroll 1
                    for (uint32_t u = mz >> 16; u < min((mz + me) >> 16, moved); u++, take++) {
                        const int f = __popc(__ballot_sync(0xffffffffu, (z & 0xFFFFu) <= u));
                        const uint32_t q = u - (__shfl_sync(0xffffffffu, z - ed, f) & 0xFFFFu);
                        if (lane == take) from = (b % 5 + 5 * f) << 8 | q;
                    }
                }
                if (next > mine && take) {
                    if (lane < take) {
                        uint32_t x;
                        int it = 0;
#pragma unroll 1
                        do {
                            asm volatile("ld.acquire.gpu.global.u32 %0, [%1];" : "=r"(x) : "l"(p.g->ready + (from >> 8)) : "memory");
                            if (++it > (1 << 22)) __trap();
                        } while (x != ~epoch);
                    }
                    __syncwarp();
#pragma unroll 1
                    for (end += take; take--;) {
                        const uint32_t f = __shfl_sync(0xffffffffu, from, take);
                        if (lane < 16)
                            asm volatile("cp.async.cg.shared.global [%0], [%1], 16;" ::"r"(chunk + (MAXROW - 1 - take) * pitch),
                                         "l"(p.g->pool + ((f >> 8) * GIVE + (f & 255)) * 16 + lane) : "memory");
                    }
                    take = 0;
                    asm volatile("cp.async.wait_all;" ::: "memory");
                    __threadfence_block();
                    __syncwarp();
                }
                const bool has = k < (end < 0 ? mine : end);
                const uint32_t i = k < mine ? k : MAXROW - 1 + mine - k, x = __shfl_sync(0xffffffffu, pk, j);
                const bool close = has && i >= (x >> 24);
                busy = __ballot_sync(0xffffffffu, has);
                const uint32_t m = __ballot_sync(0xffffffffu, close);
                uint32_t c = has ? ((x & 0xFF00) + i * 0x1000100) | (j ? 0u : ST_START) | (close ? ST_CLOSE : 0u) : MAXROW * 256;
                if (!(busy >> (lane & 12))) c |= 0x80000000u;
                c |= busy >> ((lane & 12) + 4) ? (lane & 12) * 4 + 32 : 16;
                sts32_if(at, c, lane < 16 || !busy);
                j = close ? 0 : j + 1;
                k = close ? next + __popc(m & ((1u << lane) - 1)) : k;
                next += __popc(m);
                at += 64;
            } while (busy);
        }
        if (warp == 15) mbar_wait(sb + BAR_OFF + 16 + 8 * FLIGHT, 0);
        else if (warp != 12) __nanosleep(ZDELAY);
        const int zend = misc[32] + misc[64];
#pragma unroll 1
        for (;;) {
            int r = 0;
            if (lane == 0) r = atomicAdd(&misc[4], 4u);
            r = __shfl_sync(0xffffffffu, r, 0) + 8 * ng;
            if (r >= zend) break;
            uint4 v[4];
            uint32_t n[4];
#pragma unroll
            for (int i = 0; i < 4; i++) {
                n[i] = reinterpret_cast<const uint32_t*>(smem + SN_OFF)[min(r + i, zend - 1) * 2 + 1] * 32 + lane;
                v[i] = __ldcs(reinterpret_cast<const uint4*>(p.sv) + n[i]);
            }
#pragma unroll
            for (int i = 0; i < 4; i++)
                if (r + i < zend) __stcs(reinterpret_cast<uint4*>(p.out) + n[i], v[i]);
        }
        static_assert(FLIGHT <= 4, "drain");
        drain(warp & 3);
        asm volatile("cp.async.wait_all;" ::: "memory");
        TSX(14, 384); TSX(15, 480); TSX(16, 416);
    }
}

}

extern "C" void kernel_launch(void* const* d_in, const int* in_sizes, int n_in, void* d_out, int out_size) {
    static int s_G = 0;
    static void* s_scratch = nullptr;
    const int N = in_sizes[0] / 256, E = in_sizes[2];
    if (s_G == 0) {
        cudaFuncSetAttribute(painn_kernel<0, 0, 0>, cudaFuncAttributeMaxDynamicSharedMemorySize, SMEM_BYTES);
        cudaFuncSetAttribute(painn_kernel<50000, 800000, 132>, cudaFuncAttributeMaxDynamicSharedMemorySize, SMEM_BYTES);
        int dev = 0, sms = 0, occ = 0;
        cudaGetDevice(&dev);
        cudaDeviceGetAttribute(&sms, cudaDevAttrMultiProcessorCount, dev);
        cudaOccupancyMaxActiveBlocksPerMultiprocessor(&occ, painn_kernel<0, 0, 0>, THREADS, SMEM_BYTES);
        cudaGetSymbolAddress(&s_scratch, g_scratch);
        s_G = occ >= 1 ? (sms < MAXG ? sms : MAXG) : 0;
    }
    if (s_G == 0 || N > TABLE_MAXN || N > s_G * MAXNPC || (s_G - 1) * ((N + s_G - 1) / s_G) >= N || E > MAXE || E < 4 * MAXG * MAXG) return;
    Params p;
    p.g = (Scratch*)s_scratch;
    p.sv = (const __nv_bfloat16*)d_in[0];
    p.pos = (const __nv_bfloat16*)d_in[1];
    p.src = (const int*)d_in[2];
    p.dst = (const int*)d_in[3];
    p.freqs = (const __nv_bfloat16*)d_in[4];
    p.w1 = (const __nv_bfloat16*)d_in[5];
    p.w2 = (const __nv_bfloat16*)d_in[6];
    p.wr = (const __nv_bfloat16*)d_in[7];
    p.out = (__nv_bfloat16*)d_out;
    p.desc0 = (uint64_t)(SB >> 4) | ((uint64_t)1 << 16) | ((uint64_t)64 << 32) | ((uint64_t)1 << 62);
    p.N = N; p.E = E; p.G = s_G;
    p.NPC = (N + s_G - 1) / s_G;
    p.magic = (uint32_t)(((1ull << 32) + p.NPC - 1) / p.NPC);
    p.gpc = ((E >> 2) + s_G - 1) / s_G;
    p.odd_edges = (E & 3) != 0 || p.gpc > 3 * THREADS;
    if (N == 50000 && E == 800000 && s_G == 132) painn_kernel<50000, 800000, 132><<<s_G, THREADS, SMEM_BYTES, cudaStreamPerThread>>>(p);
    else painn_kernel<0, 0, 0><<<s_G, THREADS, SMEM_BYTES, cudaStreamPerThread>>>(p);
}
```

```cpp
#include <cuda_runtime.h>
#include <cuda_bf16.h>
#include <stdint.h>

namespace {

constexpr int NWG = 3;
constexpr int REG_C = 160, REG_H = 32;
constexpr int SPL = 10;
constexpr int GIVE = 10, ROOM = 4;
constexpr int BIG = 5;
constexpr int CUT = 7;
constexpr int HDELAY = 150;
constexpr int TOUCH = 4, FLIGHT = 4;
constexpr int NPRE = 6;
constexpr int PDELAY = 150;
constexpr int ZDELAY = 1200;
constexpr int THREADS = 512;
constexpr int MAXG = 136;
constexpr int MAXROW = 96;
constexpr int TMAX = MAXROW / 12 + 18;
constexpr int MAXNPC = 480;
constexpr int MAXE = 1 << 20;

constexpr int W2_OFF = 8192;
constexpr int WR_OFF = 32768;
constexpr int RING_OFF = 38912;
constexpr int SREC_OFF = RING_OFF + 4 * NWG * 12288;
constexpr int SD_OFF = SREC_OFF + (MAXROW + 1) * 128 + 16;
constexpr int SN_OFF = SD_OFF + (MAXROW + 1) * 64 + 16;
constexpr int CTL_OFF = SN_OFF + (MAXROW + 1) * 64 + 16;
constexpr int TABLE_MAXN = 50176;
constexpr int STAGE_OFF = TABLE_MAXN * 4;
constexpr int SCNT_OFF = STAGE_OFF + MAXG * 128;
constexpr int PACK_OFF = RING_OFF + 6144;
constexpr int NCNT_OFF = SCNT_OFF + 768;
constexpr int OPOS_OFF = NCNT_OFF + 2048;
constexpr int BAR_OFF = OPOS_OFF + 4096;
constexpr int MISC_OFF = BAR_OFF + 128;
constexpr int FREQ_OFF = MISC_OFF + 512;
constexpr int DUMMY_OFF = (FREQ_OFF + 128 + 127) / 128 * 128;
constexpr int SMEM_BYTES = DUMMY_OFF + 4096;
static_assert(CTL_OFF + 64 * TMAX <= STAGE_OFF + 32 * THREADS && STAGE_OFF - SREC_OFF <= 32 * THREADS && 4 * (MAXG + 32) <= 768, "smem map");
static_assert(SMEM_BYTES <= 232448 && BAR_OFF % 8 == 0 && RING_OFF % 128 == 0 && SREC_OFF % 128 == 0 && (MAXG + 14) / 15 <= 12, "smem map");

constexpr uint32_t PAY_INVALID = 0x3FFFFFFu;
constexpr uint32_t PAY_MARK = 0x3FFFDFFu;
constexpr uint32_t NODE_SPLIT = 0x40000000u;
constexpr uint32_t ST_START = 1, ST_CLOSE = 2;
constexpr float QINVP = 9.0f / 510.0f;
constexpr uint32_t QTHRESH = 2209;
constexpr uint32_t QSURE = 1980;

struct Scratch {
    unsigned sync[32];
    uint4 table[TABLE_MAXN / 4];
    uint4 wimg[RING_OFF / 16];
    uint2 pos8[TABLE_MAXN];
    uint4 xbuf[MAXG * MAXG * 8 + 3 * THREADS];
    uint4 pool[MAXG * GIVE * 16];
    unsigned rows[MAXG];
    unsigned ready[MAXG];
    int ovfcnt[MAXG];
    int2 ovf[MAXE + 8 * MAXG + 8];
};
__device__ __align__(128) Scratch g_scratch;

struct Params {
    const __nv_bfloat16* pos;
    Scratch* g;
    const int* src;
    const int* dst;
    int N, NPC, E, gpc;
    const __nv_bfloat16* w2;
    const __nv_bfloat16* wr;
    const __nv_bfloat16* w1;
    const __nv_bfloat16* freqs;
    const __nv_bfloat16* sv;
    __nv_bfloat16* out;
    uint64_t desc0;
    int G;
    uint32_t magic;
    int odd_edges;
};
constexpr uint32_t SB = 1024;

#define TSX(i, thr)
#define TS0(i) TSX(i, 0)
#define TRW(ctl)

__device__ __forceinline__ uint32_t smem_u32(const void* p) { return (uint32_t)__cvta_generic_to_shared(p); }
__device__ __forceinline__ void mbar_init(uint32_t bar, uint32_t cnt) {
    asm volatile("mbarrier.init.shared::cta.b64 [%0], %1;" ::"r"(bar), "r"(cnt) : "memory");
}
__device__ __forceinline__ void mbar_arrive(uint32_t bar) {
    asm volatile("mbarrier.arrive.shared::cta.b64 _, [%0];" ::"r"(bar) : "memory");
}
__device__ __forceinline__ void mbar_expect_tx(uint32_t bar, uint32_t bytes) {
    asm volatile("mbarrier.arrive.expect_tx.shared::cta.b64 _, [%0], %1;" ::"r"(bar), "r"(bytes) : "memory");
}
__device__ __forceinline__ void mbar_wait(uint32_t bar, uint32_t parity) {
    uint32_t ok;
    int it = 0;
    do {
        asm volatile(
            "{\n.reg .pred p;\n"
            "mbarrier.try_wait.parity.shared::cta.b64 p, [%1], %2, 2000;\n"
            "selp.u32 %0, 1, 0, p;\n}\n"
            : "=r"(ok) : "r"(bar), "r"(parity) : "memory");
        if (++it > (1 << 20)) __trap();
    } while (!ok);
}
__device__ __forceinline__ uint32_t mbar_test(uint32_t bar, uint32_t parity) {
    uint32_t ok;
    asm volatile("{\n.reg .pred p;\nmbarrier.test_wait.parity.shared::cta.b64 p, [%1], %2;\nselp.u32 %0, 1, 0, p;\n}\n"
                 : "=r"(ok) : "r"(bar), "r"(parity) : "memory");
    return ok;
}
__device__ __forceinline__ uint32_t pin(uint32_t x) {
    uint32_t r;
    asm volatile("shfl.sync.bfly.b32 %0, %1, 0, 31, -1;" : "=r"(r) : "r"(x));
    return r;
}
__device__ __forceinline__ void bulk_g2s(uint32_t dst, const void* src, uint32_t bytes, uint32_t bar) {
    asm volatile("cp.async.bulk.shared::cluster.global.mbarrier::complete_tx::bytes [%0], [%1], %2, [%3];"
                 ::"r"(dst), "l"(src), "r"(bytes), "r"(bar) : "memory");
}
__device__ __forceinline__ void ldsm4(uint32_t addr, uint32_t* r) {
    asm volatile("ldmatrix.sync.aligned.m8n8.x4.shared.b16 {%0,%1,%2,%3}, [%4];"
                 : "=r"(r[0]), "=r"(r[1]), "=r"(r[2]), "=r"(r[3]) : "r"(addr) : "memory");
}
__device__ __forceinline__ uint32_t pack2(float lo, float hi) {
    uint32_t r;
    asm("cvt.rn.bf16x2.f32 %0, %1, %2;" : "=r"(r) : "f"(hi), "f"(lo));
    return r;
}
__device__ __forceinline__ float bf_lo(uint32_t w) { return __uint_as_float(w << 16); }
__device__ __forceinline__ float bf_hi(uint32_t w) { return __uint_as_float(w & 0xFFFF0000u); }
__device__ __forceinline__ float rbf16(float x) { return __uint_as_float(pack2(0.f, x)); }
__device__ __forceinline__ uint32_t hmul2(uint32_t a, uint32_t b) {
    uint32_t r;
    asm("mul.rn.bf16x2 %0, %1, %2;" : "=r"(r) : "r"(a), "r"(b));
    return r;
}
__device__ __forceinline__ uint32_t hfma2(uint32_t a, uint32_t b, uint32_t c) {
    uint32_t r;
    asm("fma.rn.bf16x2 %0, %1, %2, %3;" : "=r"(r) : "r"(a), "r"(b), "r"(c));
    return r;
}
__device__ __forceinline__ uint32_t hfma2_lo(uint32_t a, uint32_t b, uint32_t c) {
    uint32_t r;
    asm("{\n.reg .b16 l, h;\n.reg .b32 t;\nmov.b32 {l, h}, %2;\nmov.b32 t, {l, l};\nfma.rn.bf16x2 %0, %1, t, %3;\n}\n" : "=r"(r) : "r"(a), "r"(b), "r"(c));
    return r;
}
__device__ __forceinline__ uint32_t hfma2_hi(uint32_t a, uint32_t b, uint32_t c) {
    uint32_t r;
    asm("{\n.reg .b16 l, h;\n.reg .b32 t;\nmov.b32 {l, h}, %2;\nmov.b32 t, {h, h};\nfma.rn.bf16x2 %0, %1, t, %3;\n}\n" : "=r"(r) : "r"(a), "r"(b), "r"(c));
    return r;
}
__device__ __forceinline__ uint32_t hadd2(uint32_t a, uint32_t b) {
    uint32_t r;
    asm("add.rn.bf16x2 %0, %1, %2;" : "=r"(r) : "r"(a), "r"(b));
    return r;
}
__device__ __forceinline__ uint32_t hsub2(uint32_t a, uint32_t b) {
    uint32_t r;
    asm("sub.rn.bf16x2 %0, %1, %2;" : "=r"(r) : "r"(a), "r"(b));
    return r;
}
__device__ __forceinline__ float tanh_fast(float x) {
    float r;
    asm("tanh.approx.f32 %0, %1;" : "=f"(r) : "f"(x));
    return r;
}
__device__ __forceinline__ void wg_fence() { asm volatile("wgmma.fence.sync.aligned;" ::: "memory"); }
__device__ __forceinline__ void wg_commit() { asm volatile("wgmma.commit_group.sync.aligned;" ::: "memory"); }
template <int N>
__device__ __forceinline__ void wg_wait() { asm volatile("wgmma.wait_group.sync.aligned %0;" ::"n"(N) : "memory"); }

#define WG_REGS "{%0,%1,%2,%3,%4,%5,%6,%7,%8,%9,%10,%11,%12,%13,%14,%15,%16,%17,%18,%19,%20,%21,%22,%23,%24,%25,%26,%27,%28,%29,%30,%31}"
#define WG_OPS(c) c(d[0]), c(d[1]), c(d[2]), c(d[3]), c(d[4]), c(d[5]), c(d[6]), c(d[7]), c(d[8]), c(d[9]), c(d[10]), \
    c(d[11]), c(d[12]), c(d[13]), c(d[14]), c(d[15]), c(d[16]), c(d[17]), c(d[18]), c(d[19]), c(d[20]), c(d[21]),     \
    c(d[22]), c(d[23]), c(d[24]), c(d[25]), c(d[26]), c(d[27]), c(d[28]), c(d[29]), c(d[30]), c(d[31])
__device__ __forceinline__ void wgmma_first(float* d, const uint32_t* a, uint64_t desc) {
    asm volatile("wgmma.mma_async.sync.aligned.m64n64k16.f32.bf16.bf16 " WG_REGS ", {%32,%33,%34,%35}, %36, 0, 1, 1, 1;"
                 : WG_OPS("+f") : "r"(a[0]), "r"(a[1]), "r"(a[2]), "r"(a[3]), "l"(desc));
}
__device__ __forceinline__ void wgmma_acc(float* d, const uint32_t* a, uint64_t desc) {
    asm volatile("wgmma.mma_async.sync.aligned.m64n64k16.f32.bf16.bf16 " WG_REGS ", {%32,%33,%34,%35}, %36, 1, 1, 1, 1;"
                 : WG_OPS("+f") : "r"(a[0]), "r"(a[1]), "r"(a[2]), "r"(a[3]), "l"(desc));
}
__device__ __forceinline__ void wgmma_k64(float* d, const uint32_t* a, uint64_t desc) {
    wgmma_first(d, a, desc);
    wgmma_acc(d, a + 4, desc + 128);
    wgmma_acc(d, a + 8, desc + 256);
    wgmma_acc(d, a + 12, desc + 384);
}
__device__ __forceinline__ void fence_regs(float* d) { asm volatile("" : WG_OPS("+f")::"memory"); }
__device__ __forceinline__ uint32_t qaxis(float x) {
    const float u = fmaf(x, QINVP, 0.25f);
    const float f = u - ((u + 12582912.f) - 12582912.f);
    return __float_as_uint(fmaf(fabsf(f), 510.f, 12582912.f));
}
__device__ __forceinline__ uint32_t qcode(float x, float y, float z, uint32_t tx) {
    return __byte_perm(__byte_perm(qaxis(x), qaxis(y), 0x3340), qaxis(z), 0x3410) ^ tx;
}
__device__ __forceinline__ bool near_test(uint32_t ca, uint32_t cb, uint32_t tag24, uint32_t& q) {
    const uint32_t D = __vabsdiffu4(ca, cb);
    q = __dp4a(D, D, 0x7FFFFFFFu - QSURE);
    return q <= 0x7FFFFFFFu - QSURE + QTHRESH || ((ca ^ tag24) | (cb ^ tag24)) >= 0x1000000u;
}
__device__ __forceinline__ bool inside(uint32_t rxy, uint32_t rz) {
    const uint32_t qxy = hmul2(rxy, rxy), qz = hmul2(rz, rz);
    return bf_lo(qxy) + bf_hi(qxy) + bf_lo(qz) <= 24.8125f;
}

__device__ __forceinline__ uint32_t lds32(uint32_t addr) {
    uint32_t r;
    asm volatile("ld.shared.u32 %0, [%1];" : "=r"(r) : "r"(addr));
    return r;
}
__device__ __forceinline__ void sts32_if(uint32_t addr, uint32_t v, bool c) {
    asm volatile("{\n.reg .pred p;\nsetp.ne.u32 p, %2, 0;\n@p st.shared.u32 [%0], %1;\n}\n" ::"r"(addr), "r"(v), "r"((uint32_t)c) : "memory");
}
__device__ __forceinline__ void stg128_if(void* ptr, uint4 v, bool c) {
    asm volatile("{\n.reg .pred p;\nsetp.ne.u32 p, %5, 0;\n@p st.relaxed.gpu.global.v4.u32 [%0], {%1,%2,%3,%4};\n}\n"
                 ::"l"(ptr), "r"(v.x), "r"(v.y), "r"(v.z), "r"(v.w), "r"((uint32_t)c) : "memory");
}
__device__ __forceinline__ void lds128(uint32_t addr, uint32_t* r) {
    asm volatile("ld.shared.v4.u32 {%0,%1,%2,%3}, [%4];" : "=r"(r[0]), "=r"(r[1]), "=r"(r[2]), "=r"(r[3]) : "r"(addr) : "memory");
}
template <int NP, int HI, int PAD = 1>
__device__ __forceinline__ void gather(uint32_t dst, const void* base, uint32_t c, uint32_t e) {
#define GATHER_HEAD "{\n.reg .pred p;\n.reg .b32 n;\n.reg .b64 a;\nprmt.b32 n, %2, 0, %3;\nsetp.ne.u32 p, n, 0xFFFF;\nmad.lo.u32 n, n, 512, %4;\nmad.wide.u32 a, n, 1, %1;\n"
#define GATHER_1(P) P "cp.async.cg.shared.global [%0], [a], 16;\n}\n"
#define GATHER_3(P) P "cp.async.cg.shared.global [%0], [a + 128], 16;\n" P "cp.async.cg.shared.global [%0 + 1024], [a + 256], 16;\n" \
                    P "cp.async.cg.shared.global [%0 + 2048], [a + 384], 16;\n}\n"
#define GATHER_ARGS(z) ::"r"(dst), "l"(base), "r"(e), "n"((HI ? 0x32 : 0x10) + z), "r"(c) : "memory"
    if constexpr (NP == 1 && PAD) asm volatile(GATHER_HEAD GATHER_1("@p ") GATHER_ARGS(0x4400));
    if constexpr (NP == 1 && !PAD) asm volatile(GATHER_HEAD GATHER_1("") GATHER_ARGS(0x4400));
    if constexpr (NP == 3 && PAD) asm volatile(GATHER_HEAD GATHER_3("@p ") GATHER_ARGS(0x5500));
    if constexpr (NP == 3 && !PAD) asm volatile(GATHER_HEAD GATHER_3("") GATHER_ARGS(0x4400));
    if constexpr (NP == 4)
        asm volatile(GATHER_HEAD "setp.ge.u32 p, %2, 0x40000000;\ncp.async.cg.shared.global [%0], [a], 16, p;\ncp.async.cg.shared.global [%0 + 1024], [a + 128], 16, p;\n"
                     "cp.async.cg.shared.global [%0 + 2048], [a + 256], 16, p;\ncp.async.cg.shared.global [%0 + 3072], [a + 384], 16, p;\n}\n" GATHER_ARGS(0x4400));
}
__device__ __forceinline__ void cp_commit() { asm volatile("cp.async.commit_group;" ::: "memory"); }
__device__ __forceinline__ void cp_wait1() { asm volatile("cp.async.wait_group 1;" ::: "memory"); }
__device__ __forceinline__ uint32_t hmul2_lo(uint32_t a, uint32_t b) {
    uint32_t r;
    asm("{\n.reg .b16 l, h;\n.reg .b32 t;\nmov.b32 {l, h}, %2;\nmov.b32 t, {l, l};\nmul.rn.bf16x2 %0, %1, t;\n}\n" : "=r"(r) : "r"(a), "r"(b));
    return r;
}
__device__ __forceinline__ void lds2_if(uint32_t a0, uint32_t a1, uint32_t* r, uint32_t c) {
    asm volatile("{\n.reg .pred p;\nsetp.ne.u32 p, %10, 0;\n@p ld.shared.v4.u32 {%0,%1,%2,%3}, [%8];\n@p ld.shared.v4.u32 {%4,%5,%6,%7}, [%9];\n}\n"
                 : "+r"(r[0]), "+r"(r[1]), "+r"(r[2]), "+r"(r[3]), "+r"(r[4]), "+r"(r[5]), "+r"(r[6]), "+r"(r[7])
                 : "r"(a0), "r"(a1), "r"(c) : "memory");
}
__device__ __forceinline__ int fresh_lane() {
    int l;
    asm volatile("mov.u32 %0, %%laneid;" : "=r"(l));
    return l;
}

__device__ __forceinline__ void cold_edges(unsigned char* smem, const Params& p, int lo, int hi, uint32_t tag) {
#pragma unroll 1
    for (int e = lo + threadIdx.x; e < hi; e += THREADS) {
        const int s = p.src[e], d = p.dst[e];
        uint32_t q;
        if (near_test(reinterpret_cast<const uint32_t*>(smem)[s], reinterpret_cast<const uint32_t*>(smem)[d], tag << 24, q)) {
            const uint32_t own = __umulhi((uint32_t)d, p.magic);
            const uint32_t slot4 = atomicAdd(reinterpret_cast<uint32_t*>(smem + SCNT_OFF) + own, 4u);
            uint32_t* line = reinterpret_cast<uint32_t*>(smem + STAGE_OFF) + own * 32;
            if (slot4 < 124) {
                line[slot4 >> 2] = ((uint32_t)s << 15) + ((uint32_t)(d - own * p.NPC) << 6) + tag + (q & 0x80000000u);
            } else {
                uint32_t o = atomicAdd(reinterpret_cast<uint32_t*>(smem + MISC_OFF) + 16, 1u);
                p.g->ovf[(size_t)blockIdx.x * (4 * p.gpc + 4) + o] = make_int2(s, d);
                line[31] = (PAY_MARK << 6) | tag;
            }
        }
    }
}
__device__ __forceinline__ void cold_filter(unsigned char* smem, const Params& p, int e0, int e1, uint32_t tag, int redo) {
    if (redo) {
        if (threadIdx.x < MAXG) reinterpret_cast<uint32_t*>(smem + SCNT_OFF)[threadIdx.x] = 0;
        __syncthreads();
    }
    cold_edges(smem, p, redo ? 4 * e0 : 4 * (e0 + 3 * THREADS), 4 * e1, tag);
    if (blockIdx.x == 0) cold_edges(smem, p, p.E & ~3, p.E, tag);
    __syncthreads();
    if (threadIdx.x == 0) p.g->ovfcnt[blockIdx.x] = reinterpret_cast<uint32_t*>(smem + MISC_OFF)[16];
    __threadfence();
    __syncthreads();
}
__device__ __forceinline__ uint3 geometry(uint32_t rxy, uint32_t rz) {
    const uint32_t qxy = hmul2(rxy, rxy), qz = hmul2(rz, rz);
    float d, id;
    asm("sqrt.approx.ftz.f32 %0, %1;" : "=f"(d) : "f"(rbf16(rbf16(bf_lo(qxy) + bf_hi(qxy) + bf_lo(qz)) + 1e-8f)));
    d = rbf16(d);
    asm("rcp.approx.ftz.f32 %0, %1;" : "=f"(id) : "f"(d));
    const float cs = rbf16(__cosf(rbf16(rbf16(3.14159265358979f * d) * 0.2f)));
    const uint32_t zs = pack2(bf_lo(rz) * id, 0.5f * rbf16(cs + 1.0f) * id);
    return d < 5.0f ? make_uint3(pack2(bf_lo(rxy) * id, bf_hi(rxy) * id), zs, __byte_perm(__float_as_uint(d), zs, 0x7632)) : make_uint3(0, 0, 0);
}
__device__ __forceinline__ void cold_messages(unsigned char* smem, const Params& p, int nn) {
    const int nbase = blockIdx.x * p.NPC, lane = threadIdx.x & 31;
    const uint32_t* box = reinterpret_cast<const uint32_t*>(p.g->xbuf) + blockIdx.x * p.G * 32;
    uint32_t* w = reinterpret_cast<uint32_t*>(smem + RING_OFF);
#pragma unroll 1
    for (int i = threadIdx.x; i < 9728; i += THREADS)
        w[i] = i < 2048 ? reinterpret_cast<const uint32_t*>(p.w1)[i] : i < 8192 ? reinterpret_cast<const uint32_t*>(p.w2)[i - 2048] : reinterpret_cast<const uint32_t*>(p.wr)[i - 8192];
#pragma unroll 1
    for (int i = threadIdx.x; i < nn * 32; i += THREADS) reinterpret_cast<uint4*>(p.out)[nbase * 32 + i] = reinterpret_cast<const uint4*>(p.sv)[nbase * 32 + i];
    __threadfence();
    __syncthreads();
    const float freq = __bfloat162float(p.freqs[lane & 15]);
#pragma unroll 1
    for (int m = -1; m < p.G; m++) {
        const int cnt = m < 0 ? p.G * 32 : (__ldcg(box + m * 32 + 31) >> 6) == PAY_MARK ? __ldcg(&p.g->ovfcnt[m]) : 0;
#pragma unroll 1
        for (int i = threadIdx.x; i - lane < cnt; i += THREADS) {
            int2 e = make_int2(0, -1);
            if (i < cnt) {
                if (m < 0) {
                    const uint32_t x = __ldcg(box + i);
                    e = make_int2((x >> 15) & 0xFFFFu, nbase + ((x >> 6) & 511u));
                } else {
                    e = __ldcg(p.g->ovf + (size_t)m * (4 * p.gpc + 4) + i);
                }
            }
            bool in = (uint32_t)(e.y - nbase) < (uint32_t)nn;
            uint3 geo = make_uint3(0, 0, 0);
            if (in) {
                const uint2 ps = __ldcg(p.g->pos8 + e.x), pd = __ldcg(p.g->pos8 + e.y);
                const uint32_t rxy = hsub2(ps.x, pd.x), rz = hsub2(ps.y, pd.y);
                in = inside(rxy, rz);
                geo = geometry(rxy, rz);
            }
#pragma unroll 1
            for (uint32_t todo = __ballot_sync(0xffffffffu, in); todo; todo &= todo - 1) {
                const int l = __ffs(todo) - 1;
                const uint32_t* row = reinterpret_cast<const uint32_t*>(p.sv) + (size_t)__shfl_sync(0xffffffffu, e.x, l) * 128 + lane;
                uint32_t* orow = reinterpret_cast<uint32_t*>(p.out) + (size_t)__shfl_sync(0xffffffffu, e.y, l) * 128 + lane;
                const uint32_t gx = __shfl_sync(0xffffffffu, geo.x, l), gy = __shfl_sync(0xffffffffu, geo.y, l);
                const float rb = rbf16(__sinf(rbf16(bf_lo(__shfl_sync(0xffffffffu, geo.z, l)) * freq)) * bf_hi(gy));
                uint32_t x = row[0];
                float a[12] = {0, 0, 0, 0, 0, 0, 0, 0, 0, 0, 0, 0};
#pragma unroll 2
                for (int k = 0; k < 64; k++) {
                    const uint32_t u = __shfl_sync(0xffffffffu, x, k >> 1), ww = w[k * 32 + lane];
                    const float f = k & 1 ? bf_hi(u) : bf_lo(u);
                    a[0] = fmaf(f, bf_lo(ww), a[0]); a[1] = fmaf(f, bf_hi(ww), a[1]);
                }
                x = pack2(0.5f * fmaf(a[0], tanh_fast(0.5f * a[0]), a[0]), 0.5f * fmaf(a[1], tanh_fast(0.5f * a[1]), a[1]));
                a[0] = a[1] = 0.f;
#pragma unroll 2
                for (int k = 0; k < 64; k++) {
                    const uint32_t u = __shfl_sync(0xffffffffu, x, k >> 1);
                    const float f = k & 1 ? bf_hi(u) : bf_lo(u), r = __shfl_sync(0xffffffffu, rb, k & 15);
#pragma unroll
                    for (int c = 0; c < 3; c++) {
                        const uint32_t ww = w[2048 + k * 96 + c * 32 + lane], wr = k < 16 ? w[8192 + k * 96 + c * 32 + lane] : 0u;
                        a[2 * c] = fmaf(f, bf_lo(ww), a[2 * c]); a[2 * c + 1] = fmaf(f, bf_hi(ww), a[2 * c + 1]);
                        a[6 + 2 * c] = fmaf(r, bf_lo(wr), a[6 + 2 * c]); a[7 + 2 * c] = fmaf(r, bf_hi(wr), a[7 + 2 * c]);
                    }
                }
                const uint32_t mv = pack2(a[2] * a[8], a[3] * a[9]), mr = pack2(a[4] * a[10], a[5] * a[11]);
                const uint32_t o[4] = {pack2(a[0] * a[6], a[1] * a[7]), hfma2_lo(mr, gx, hmul2(mv, row[32])), hfma2_hi(mr, gx, hmul2(mv, row[64])),
                                       hfma2_lo(mr, gy, hmul2(mv, row[96]))};
#pragma unroll
                for (int c = 0; c < 4; c++) asm volatile("red.global.add.noftz.bf16x2 [%0], %1;" ::"l"(orow + 32 * c), "r"(o[c]) : "memory");
            }
        }
    }
}

#define SPLIT(k) asm volatile("{\n.reg .pred p;\nsetp.eq.u32 p, %0, %1;\n@p trap;\n}" ::"r"(c0), "n"(0x70000 + k) : "memory")
#define PIN8(a) asm volatile("" : "+r"((a)[0]), "+r"((a)[1]), "+r"((a)[2]), "+r"((a)[3]), "+r"((a)[4]), "+r"((a)[5]), "+r"((a)[6]), "+r"((a)[7]))
template <int V> struct IntC { static constexpr int value = V; };

template <int CN, int CE, int CG>
__global__ void __launch_bounds__(THREADS, 1) painn_kernel(const __grid_constant__ Params p) {
    extern __shared__ __align__(1024) unsigned char smem_dyn[];
    unsigned char* const smem = static_cast<unsigned char*>(__cvta_shared_to_generic(SB));
    constexpr uint32_t sb = SB;
    const int tid = threadIdx.x, lane = tid & 31;
    const int warp = __shfl_sync(0xffffffffu, tid >> 5, 0);
    constexpr int CNPC = CG ? (CN + CG - 1) / CG : 1, CGPC = CG ? (CE / 4 + CG - 1) / CG : 1;
    const int b = blockIdx.x, G = CG ? CG : p.G, NPC = CG ? CNPC : p.NPC, N = CG ? CN : p.N, gpc = CG ? CGPC : p.gpc;
    const uint32_t magic = CG ? (uint32_t)(((1ull << 32) + CNPC - 1) / CNPC) : p.magic;
    const bool odd_edges = CG ? (CE & 3) != 0 || CGPC > 3 * THREADS : p.odd_edges;
    const int nbase = b * NPC, nn = min(NPC, N - nbase);
    const int eg0 = b * gpc, eg1 = min((CG ? CE : p.E) >> 2, eg0 + gpc);

    uint4* stage4 = reinterpret_cast<uint4*>(smem + STAGE_OFF);
    uint32_t* ncnt = reinterpret_cast<uint32_t*>(smem + NCNT_OFF);
    uint32_t* misc = reinterpret_cast<uint32_t*>(smem + MISC_OFF);
    const uint32_t bar_tab = sb + BAR_OFF;

    TS0(0);
    int4 es[3], ed[3];
    auto load_edges = [&](int i) {
        const int g = min(eg0 + tid + i * THREADS, eg1 - 1);
        asm volatile("ld.global.cs.v4.u32 {%0,%1,%2,%3}, [%8];\nld.global.cs.v4.u32 {%4,%5,%6,%7}, [%9];"
                     : "=r"(es[i].x), "=r"(es[i].y), "=r"(es[i].z), "=r"(es[i].w), "=r"(ed[i].x), "=r"(ed[i].y), "=r"(ed[i].z), "=r"(ed[i].w)
                     : "l"(reinterpret_cast<const int4*>(p.src) + g), "l"(reinterpret_cast<const int4*>(p.dst) + g) : "memory");
    };
    es[0] = ed[0] = make_int4(0, 0, 0, 0);
    const char* const own = reinterpret_cast<const char*>(p.sv) + (size_t)nbase * 512;
    auto touch = [&](int o) {
        if (o + lane * 256 < nn * 512)
            asm volatile("cp.async.ca.shared.global.L2::256B [%0], [%1], 4;" ::"r"(sb + DUMMY_OFF + 4 * lane), "l"(own + o + lane * 256) : "memory");
    };
    uint4* const xout = p.g->xbuf + ((tid >> 3) * G + b) * 8 + (tid & 7);
    unsigned epoch;
    const uint32_t tbytes = ((N + 3) >> 2) * 16, cut = (tbytes >> 8) * CUT * 16, bar_cut = sb + BAR_OFF + 120;
    {
        uint32_t pxy, pz;
        if constexpr (CG && CN % 2 == 0) {
            asm volatile("ld.global.nc.u32 %0, [%3];\nld.global.nc.u32 %1, [%3 + 4];\nld.global.ca.u32 %2, [%4];"
                         : "=r"(pxy), "=r"(pz), "=r"(epoch)
                         : "l"(reinterpret_cast<const uint32_t*>(p.pos) + ((nbase + min(tid, nn - 1)) * 3 >> 1)), "l"(p.g->sync) : "memory");
            const uint32_t sh = ((nbase + tid) & 1) << 4;
            pxy = __funnelshift_r(pxy, pz, sh);
            pz >>= sh;
        } else {
            const uint16_t* q = reinterpret_cast<const uint16_t*>(p.pos) + (nbase + min(tid, nn - 1)) * 3;
            pxy = q[0] | (uint32_t)q[1] << 16;
            pz = q[2];
            asm volatile("ld.global.ca.u32 %0, [%1];" : "=r"(epoch) : "l"(p.g->sync) : "memory");
        }
        const uint32_t code = qcode(bf_lo(pxy), bf_hi(pxy), bf_lo(pz), ((epoch & 31u) ^ 0x6Bu) << 24);
        asm volatile("{\n.reg .pred p;\nsetp.lt.s32 p, %2, %3;\n@p st.global.u32 [%0], %1;\n}\n"
                     ::"l"(reinterpret_cast<uint32_t*>(p.g->table) + nbase + tid), "r"(code), "r"(tid), "r"(nn) : "memory");
        __syncthreads();
        asm volatile("{\n.reg .pred p;\nsetp.eq.u32 p, %1, %2;\n@p red.relaxed.gpu.global.add.u32 [%0], 1;\n}\n" ::"l"(p.g->sync + 1), "r"(tid), "n"(THREADS - 1) : "memory");
        if (tid < THREADS - 32) load_edges(0);
        if (tid < nn) p.g->pos8[nbase + tid] = make_uint2(pxy, pz);
        reinterpret_cast<uint2*>(smem + OPOS_OFF)[tid] = make_uint2(pxy, pz);
    }
    const uint32_t tag = (epoch & 31u) | 32u;
    if (tid == THREADS - 1) {
        TSX(1, 511);
        mbar_init(bar_tab, 1);
        mbar_init(bar_cut, 1);
        mbar_expect_tx(bar_cut, cut);
        mbar_expect_tx(bar_tab, tbytes - cut);
        const unsigned want = (epoch + 1) * G;
        unsigned c;
        int it = smem_u32(smem_dyn) == SB ? 0 : 1 << 22;
        __nanosleep(HDELAY);
        do {
            asm volatile("ld.relaxed.gpu.global.u32 %0, [%1];" : "=r"(c) : "l"(p.g->sync + 1) : "memory");
            if (++it > (1 << 22)) __trap();
        } while (c != want);
        bulk_g2s(sb, p.g->table, cut, bar_cut);
        bulk_g2s(sb + cut, reinterpret_cast<const char*>(p.g->table) + cut, tbytes - cut, bar_tab);
        TSX(2, 511);
    }
    if (warp == 14) {
#pragma unroll 1
        for (int c = b * 32 + lane; c < RING_OFF / 16; c += G * 32) {
            const int row = c >> 3, j = (c ^ row) & 7;
            uint4 v;
            if (c < 512) {
                const uint32_t half = 0x3F003F00u;
                v = __ldg(reinterpret_cast<const uint4*>(p.w1) + row * 8 + j);
                v = make_uint4(hmul2(v.x, half), hmul2(v.y, half), hmul2(v.z, half), hmul2(v.w, half));
            } else {
                const uint32_t* q = (c < 2048 ? reinterpret_cast<const uint32_t*>(p.w2) + (row & 63) * 96 + ((row >> 6) - 1) * 32
                                              : reinterpret_cast<const uint32_t*>(p.wr) + (row & 15) * 96 + ((row >> 4) - 16) * 32) + (j & 4) * 4 + (j & 3);
                v = make_uint4(__ldg(q), __ldg(q + 4), __ldg(q + 8), __ldg(q + 12));
            }
            p.g->wimg[c] = v;
        }
    }
    if (tid == 416) {
#pragma unroll
        for (int i = 0; i < FLIGHT + 2; i++) mbar_init(sb + BAR_OFF + 8 + 8 * i, i ? 1 : 15);
    }
    ncnt[tid] = tid < 480 ? 0 : 1024;
    if (tid < MAXG + 32) reinterpret_cast<uint32_t*>(smem + SCNT_OFF)[tid] = tid < MAXG ? 0 : 128;
    if (tid < 128) misc[tid] = 0;
    {
        const uint32_t inv = (PAY_INVALID << 6) | tag;
        stage4[tid] = stage4[tid + THREADS] = make_uint4(inv, inv, inv, inv);
        if (tid < MAXG * 8 - 2 * THREADS) stage4[tid + 2 * THREADS] = make_uint4(inv, inv, inv, inv);
    }
    __syncthreads();
    if ((tid >> 4) == 29) asm volatile("cp.async.ca.shared.global [%0], [%1], 4;" ::"r"(sb + FREQ_OFF + 8 * (tid & 14) + 4 * (tid & 1)),
                              "l"(reinterpret_cast<const uint32_t*>(p.freqs) + ((tid & 7) >> 1) + (tid & 1) * 4) : "memory");
    if (warp == 15) load_edges(0);
    if (warp < 8) mbar_wait(bar_cut, 0);
    load_edges(1);
    load_edges(2);
    if (tid == 416) asm volatile("fence.acq_rel.gpu;" ::: "memory");
    if (warp >= 8) mbar_wait(bar_cut, 0);
#pragma unroll
    for (int i = 0; i < 3; i++) stg128_if(xout + i * G * THREADS, make_uint4(0, 0, 0, 0), tid + i * THREADS < G * 8);
    mbar_wait(bar_tab, 0);
    TS0(3);
    if (warp == 15) {
#pragma unroll
        for (int i = 0; i < TOUCH; i++) touch(i * 8192);
    }

    bool full = false;
#pragma unroll 1
    for (int i = 0, g = eg0 + tid; i < 3; i++, g += THREADS) {
        const int s[4] = {es[0].x, es[0].y, es[0].z, es[0].w}, d[4] = {ed[0].x, ed[0].y, ed[0].z, ed[0].w};
        uint32_t ca[4], cb[4], own[4], sl[4], q[4];
        bool c[4];
#pragma unroll
        for (int j = 0; j < 4; j++) { ca[j] = lds32(sb + 4 * s[j]); cb[j] = lds32(sb + 4 * d[j]); }
#pragma unroll
        for (int j = 0; j < 4; j++) {
            c[j] = near_test(ca[j], cb[j], tag << 24, q[j]) && g < eg1;
            own[j] = __umulhi((uint32_t)d[j], magic);
            sl[j] = atomicAdd(reinterpret_cast<uint32_t*>(smem + SCNT_OFF) + (c[j] ? own[j] : MAXG + lane), 4u);
        }
#pragma unroll
        for (int j = 0; j < 4; j++)
            sts32_if(sb + STAGE_OFF + own[j] * 128 + sl[j], own[j] * (uint32_t)(-64 * NPC) + (((uint32_t)s[j] << 15) + (((uint32_t)d[j] << 6) + ((q[j] & 0x80000000u) | tag))),
                     sl[j] < 124);
        full |= (sl[0] == 124) | (sl[1] == 124) | (sl[2] == 124) | (sl[3] == 124);
        es[0] = es[1]; es[1] = es[2];
        ed[0] = ed[1]; ed[1] = ed[2];
    }
    {
        const int redo = __syncthreads_or(full);
        if (__builtin_expect(redo || odd_edges, 0)) cold_filter(smem, p, eg0, eg1, tag, redo);
    }
    TS0(4);
#pragma unroll
    for (int i = 0; i < 3; i++) stg128_if(xout + i * G * THREADS, stage4[tid + i * THREADS], tid + i * THREADS < G * 8);
    __syncthreads();
#pragma unroll
    for (int i = -2; i < 2; i++) {
        const int c = tid + i * THREADS;
        const uint32_t x = c < (SN_OFF - STAGE_OFF) / 16 ? 0u : 0xFFFFFFFFu;
        if (c >= (SREC_OFF - STAGE_OFF) / 16) stage4[c] = make_uint4(x, x, x, x);
    }
    uint32_t key[4] = {0, 0, 0, 0};
    uint2 pr[4];
    const uint32_t gp = sb + RING_OFF + 2048 + (warp < 4 * NWG ? warp * 12288 : (warp & 3) * 12288 + 2048) + lane * 16;
    uint32_t pk = 0;
    if (warp == 15) {
        if (lane == 0) {
            int o = TOUCH * 8192;
#pragma unroll 1
            while (o < nn * 512 && !mbar_test(sb + BAR_OFF + 8, 0)) {
                const uint32_t bar = sb + BAR_OFF + 16 + 8 * (pk % FLIGHT);
                if (!mbar_test(bar, ~(pk / FLIGHT) & 1)) continue;
                const int n = min(4096, nn * 512 - o);
                mbar_expect_tx(bar, n);
                bulk_g2s(sb + DUMMY_OFF, own + o, n, bar);
                o += n;
                pk++;
            }
            misc[3] = pk;
        }
        __syncwarp();
    } else {
    __nanosleep(PDELAY);
    TS0(5);

    {
        const int LPW = (G + 14) / 15;
        uint32_t ew[3][4], bad[3];
        const uint4* cp = p.g->xbuf + (b * G + warp * LPW) * 8 + lane;
#pragma unroll
        for (int i = 0; i < 3; i++) {
            bad[i] = lane + 32 * i < min(LPW, G - warp * LPW) * 8;
            ew[i][0] = ew[i][1] = ew[i][2] = ew[i][3] = (PAY_INVALID << 6) | tag;
        }
        int it = 0;
#pragma unroll 1
        do {
#pragma unroll
            for (int i = 0; i < 3; i++)
                asm volatile("{\n.reg .pred p;\nsetp.ne.u32 p, %5, 0;\n@p ld.relaxed.gpu.global.v4.u32 {%0,%1,%2,%3}, [%4];\n}\n"
                             : "+r"(ew[i][0]), "+r"(ew[i][1]), "+r"(ew[i][2]), "+r"(ew[i][3]) : "l"(cp + 32 * i), "r"(bad[i]) : "memory");
#pragma unroll
            for (int i = 0; i < 3; i++) bad[i] = ((ew[i][0] ^ tag) | (ew[i][1] ^ tag) | (ew[i][2] ^ tag) | (ew[i][3] ^ tag)) & 63u;
            if (++it > (1 << 22)) __trap();
        } while (__any_sync(0xffffffffu, bad[0] | bad[1] | bad[2]));
        TSX(21, 0); TSX(22, 448);
        uint4* pack = reinterpret_cast<uint4*>(smem + PACK_OFF);
        int nch = 0;
        uint32_t at[3];
#pragma unroll
        for (int i = 0; i < 3; i++) {
            const uint32_t m = __ballot_sync(0xffffffffu, ew[i][0] < (PAY_MARK << 6));
            at[i] = nch + __popc(m & ((1u << lane) - 1));
            nch += __popc(m);
        }
        if (__builtin_expect(nch > 32, 0)) {
#pragma unroll 1
            for (int i = 0; i < 3; i++) {
                if (ew[0][0] < (PAY_MARK << 6) && at[0] >= 32) at[0] = (15 - warp) * 32 - 1 - min(atomicAdd(&misc[1], 1u), 31u);
                const uint32_t x = at[0], y = ew[0][0];
                at[0] = at[1]; at[1] = at[2]; at[2] = x;
                ew[0][0] = ew[1][0]; ew[1][0] = ew[2][0]; ew[2][0] = y;
            }
        }
#pragma unroll
        for (int i = 0; i < 3; i++) {
            asm volatile("{\n.reg .pred p;\nsetp.lt.u32 p, %1, %5;\n@p st.shared.v4.u32 [%0], {%1,%2,%3,%4};\n}\n"
                         ::"r"(sb + PACK_OFF + (warp * 32 + at[i]) * 16), "r"(ew[i][0]), "r"(ew[i][1]), "r"(ew[i][2]), "r"(ew[i][3]), "n"(PAY_MARK << 6) : "memory");
            sts32_if(sb + MISC_OFF + 4 * 17, 1, (ew[i][3] >> 6) == PAY_MARK);
        }
        bool have = lane < nch;
        if (warp == 14) {
            asm volatile("bar.sync 7, 480;" ::: "memory");
            const uint32_t extra = misc[1];
            if (nch + extra > 32) misc[18] = 1;
            have = have || lane + extra >= 32;
        } else {
            asm volatile("bar.arrive 7, 480;" ::: "memory");
        }
        __syncwarp();
        uint32_t w[4], rk[4];
        bool in[4];
        {
            const uint4 x = pack[tid];
            w[0] = have ? x.x : ~0u; w[1] = have ? x.y : ~0u; w[2] = have ? x.z : ~0u; w[3] = have ? x.w : ~0u;
        }
        auto fetch = [&](int j, bool c) {
            asm volatile("{\n.reg .pred p;\nsetp.ne.u32 p, %2, 0;\n@p cp.async.cg.shared.global [%0], [%1], 16;\n}\n"
                         ::"r"(gp + j * 512), "l"(reinterpret_cast<const uint4*>(p.g->pos8) + ((w[j] >> 16) & 0x7FFFu)), "r"((uint32_t)c) : "memory");
        };
#pragma unroll
        for (int j = 0; j < 4; j++) fetch(j, (int)w[j] < (int)(PAY_MARK << 6));
#pragma unroll
        for (int j = 0; j < 4; j++) pr[j] = reinterpret_cast<const uint2*>(smem + OPOS_OFF)[(w[j] >> 6) & 511u];
        uint32_t ca[4];
#pragma unroll
        for (int j = 0; j < 4; j++) {
            key[j] = ((w[j] >> 15) & 0xFFFFu) | ((w[j] << 10) & 0x1FF0000u);
            ca[j] = sb + NCNT_OFF + ((w[j] >> 4) & 0x7FCu);
            asm volatile("" : "+r"(key[j]), "+r"(ca[j]));
        }
        asm volatile("{\n.reg .pred p;\nsetp.eq.u32 p, %0, -1;\n@p trap;\n}" ::"r"(nch) : "memory");
        asm volatile("cp.async.wait_all;" ::: "memory");
        TSX(23, 0); TSX(24, 448);
        asm volatile("{\n.reg .pred p;\nsetp.eq.u32 p, %1, 0;\n@p mbarrier.arrive.shared::cta.b64 _, [%0];\n}\n" ::"r"(sb + BAR_OFF + 8), "r"(lane) : "memory");
#pragma unroll
        for (int j = 0; j < 4; j++) {
            uint2 ps;
            asm volatile("ld.shared.v2.u32 {%0,%1}, [%2];" : "=r"(ps.x), "=r"(ps.y) : "r"(gp + j * 512 + ((w[j] >> 12) & 8)) : "memory");
            in[j] = ((int)w[j] >= 0) | (((int)w[j] < (int)(PAY_MARK << 6)) & inside(hsub2(ps.x, pr[j].x), hsub2(ps.y, pr[j].y)));
        }
#pragma unroll
        for (int j = 0; j < 4; j++)
            asm volatile("atom.shared.add.u32 %0, [%1], 1;" : "=r"(rk[j]) : "r"(in[j] ? ca[j] : sb + NCNT_OFF + 4 * (480 + lane)) : "memory");
#pragma unroll
        for (int j = 0; j < 4; j++) {
            rk[j] = rk[j] < SPL ? 2 * rk[j] : min(2 * rk[j] - (2 * SPL - 1), 126u);
            asm volatile("red.shared.add.u32 [%0 + %1], 1;" ::"r"(rk[j] & 2 ? 124u : rk[j] & 60u), "n"(SB + MISC_OFF + 128) : "memory");
            key[j] += rk[j] << 25;
        }
#pragma unroll
        for (int j = 0; j < 4; j++) fetch(j, (int)w[j] >= 0);
        cp_commit();
    }
    }
    __syncthreads();
    TS0(6);
    uint32_t deg[5];
    deg[4] = lds32(sb + NCNT_OFF + 4 * tid);
#pragma unroll
    for (int j = 0; j < 4; j++) deg[j] = lds32(sb + NCNT_OFF + ((key[j] >> 14) & 0x7FCu));
    if (tid == THREADS - 33) {
        if (b == 0) p.g->sync[0] = epoch + 1;
        asm volatile("fence.proxy.async.global;" ::: "memory");
        mbar_expect_tx(bar_tab, RING_OFF);
        bulk_g2s(sb, p.g->wimg, RING_OFF, bar_tab);
    }
    __syncwarp();
    uint32_t dst = sb + RING_OFF + warp * 12288 + (lane >> 3) * 256 + (((lane & 7) ^ (lane >> 3)) << 4), l7 = (lane & 7) * 16, g32 = (lane >> 2) * 32;
    uint32_t e0, e1, n0, n1;
    auto sources = [&](uint32_t c) {
        asm volatile("{\n.reg .b32 a;\nlop3.b32 a, %4, %5, 0xFFC0, 0xA8;\nshr.u32 a, a, 2;\nld.shared.v4.u32 {%0,%1,%2,%3}, [a + %6];\n}\n"
                     : "=r"(e0), "=r"(n0), "=r"(e1), "=r"(n1) : "r"(c), "r"(g32), "n"(SB + SN_OFF));
    };
    auto load_s = [&](auto pad) {
        gather<1, 0, pad.value>(dst, p.sv, l7, e0); gather<1, 1, pad.value>(dst + 1024, p.sv, l7, e0);
        gather<1, 0, pad.value>((dst ^ 64) + 128, p.sv, l7, e1); gather<1, 1, pad.value>((dst ^ 64) + 1152, p.sv, l7, e1);
    };
    auto load_o = [&]() {
        gather<4, 0>(dst + 8192, p.sv, l7, n0); gather<4, 0>((dst ^ 64) + 8320, p.sv, l7, n1);
    };
    auto load_v = [&](auto pad) {
        gather<3, 0, pad.value>(dst + 2048, p.sv, l7, e0); gather<3, 1, pad.value>(dst + 5120, p.sv, l7, e0);
        gather<3, 0, pad.value>((dst ^ 64) + 2176, p.sv, l7, e1); gather<3, 1, pad.value>((dst ^ 64) + 5248, p.sv, l7, e1);
        cp_commit();
    };
    const int ng = (misc[32] + 7) >> 3;
    const int give = max(min(ng - max((int)(misc[33] + 7) >> 3, 4 * NWG), GIVE), 0);
    if (warp == 15) {
        const uint32_t cnt = lane < 16 ? (misc[32 + lane] + 7) >> 3 : 0u;
        uint32_t z = cnt;
#pragma unroll
        for (int o = 1; o < 16; o <<= 1) {
            const uint32_t y = __shfl_up_sync(0xffffffffu, z, o);
            if (lane >= o) z += y;
        }
        misc[96 + lane] = lane < 16 ? 64 * (z - cnt) : 64 * (MAXROW + 1);
        asm volatile("bar.arrive 5, 512;" ::: "memory");
        if (lane == 15) {
            const bool cold = cnt || z > MAXROW || misc[31 + SPL / 2] > 32 || misc[17] || misc[18];
            misc[18] = cold;
            asm volatile("st.relaxed.gpu.global.u32 [%0], %1;" ::"l"(p.g->rows + b), "r"(~epoch << 16 | (cold || ng < 4 * NWG ? 255 : give << 8 | z)) : "memory");
        }
        pk = (z - cnt) << 8 | __shfl_down_sync(0xffffffffu, cnt, 1) << 24;
    } else {
        if (warp * 32 < nn) {
            const uint32_t c = deg[4], st = tid < nn ? (min(c, (uint32_t)SPL) + 1) >> 1 : 17u;
            const uint32_t same = __match_any_sync(0xffffffffu, st), first = __ffs(same) - 1;
            uint32_t r, node = nbase + tid;
            asm volatile("atom.shared.add.u32 %0, [%1], %2;" : "=r"(r)
                         : "r"(lane == first ? sb + MISC_OFF + 4 * (64 + st) : sb + NCNT_OFF + 4 * (480 + lane)), "r"(__popc(same)) : "memory");
            r = __shfl_sync(0xffffffffu, r, first) + __popc(same & ((1u << lane) - 1)) + misc[32 + st];
            if (__builtin_expect(c > SPL, 0)) {
                const uint32_t s2 = min((c - SPL + 1) >> 1, 16u), r2 = misc[32 + s2] + atomicAdd(&misc[64 + s2], 1u), k = atomicAdd(&misc[2], 1u);
                reinterpret_cast<uint32_t*>(smem + SCNT_OFF)[k & 31] = node;
                node |= NODE_SPLIT;
                ncnt[1024 + tid] = 8 * r2;
                reinterpret_cast<uint32_t*>(smem + SN_OFF)[(r2 & 511) * 2 + 1] = node;
            }
            if (tid < nn) {
                ncnt[512 + tid] = 8 * r;
                reinterpret_cast<uint32_t*>(smem + SN_OFF)[(r & 511) * 2 + 1] = node;
            }
        }
#pragma unroll
        for (int j = 0; j < 4; j++) {
            const uint32_t c = deg[j];
            asm volatile("{\n.reg .pred p;\n.reg .b64 a;\nsetp.ge.u32 p, %0, %3;\nsetp.lt.and.u32 p, %1, 0x8000000, p;\nmad.wide.u32 a, %4, 512, %2;\n@p prefetch.global.L2 [a];\n"
                         "}\n" ::"r"(c), "r"(key[j]), "l"(p.sv), "n"(BIG), "r"(key[j] & 0xFFFFu) : "memory");
        }
        asm volatile("bar.sync 5, 512;" ::: "memory");
        uint32_t slot[4];
#pragma unroll
        for (int j = 0; j < 4; j++) slot[j] = min(misc[96 + (key[j] >> 27)] + (ncnt[512 + ((key[j] >> 16) & 1023)] & 0xFFF8u), 64u * (MAXROW + 1)) + ((key[j] >> 25) & 2);
#pragma unroll
        for (int j = 0; j < 4; j++) {
            *reinterpret_cast<uint16_t*>(smem + SN_OFF + slot[j]) = (uint16_t)key[j];
            slot[j] += slot[j] & 2;
        }
        asm volatile("bar.sync 6, 480;" ::: "memory");
        TS0(7);
        if (warp < 4 * NWG) {
            sources((warp < ng ? warp : MAXROW) << 8);
            e0 = __vminu2(e0, (N - 1) * 0x10001u);
            e1 = __vminu2(e1, (N - 1) * 0x10001u);
            load_s(IntC<0>{});
            cp_commit();
            load_o();
            cp_commit();
            asm volatile("cp.async.wait_group 2;" ::: "memory");
        } else {
            asm volatile("cp.async.wait_all;" ::: "memory");
        }
        uint2 ps[4];
#pragma unroll
        for (int j = 0; j < 4; j++)
            asm volatile("ld.shared.v2.u32 {%0,%1}, [%2];" : "=r"(ps[j].x), "=r"(ps[j].y) : "r"(gp + j * 512 + (key[j] & 1) * 8) : "memory");
        TSX(9, 0);
#pragma unroll 1
        for (int i = 0; i < 2; i++) {
#pragma unroll
            for (int u = 0; u < 2; u++) {
                const uint3 geo = geometry(hsub2(ps[u].x, pr[u].x), hsub2(ps[u].y, pr[u].y));
                *reinterpret_cast<uint2*>(smem + SREC_OFF + 2 * slot[u]) = make_uint2(geo.x, geo.y);
                *reinterpret_cast<uint32_t*>(smem + SD_OFF + slot[u]) = geo.z;
                ps[u] = ps[u + 2];
                pr[u] = pr[u + 2];
                slot[u] = slot[u + 2];
            }
        }
    }
    if (warp == 15) { __syncwarp(); asm volatile("bar.arrive 4, 512;" ::: "memory"); }
    else asm volatile("bar.sync 4, 512;" ::: "memory");
    TS0(8);
    auto drain = [&](int i) { if (i < FLIGHT) mbar_wait(sb + BAR_OFF + 16 + 8 * i, ~((misc[3] + FLIGHT - 1 - i) / FLIGHT) & 1); };
    if (__builtin_expect(misc[18], 0)) {
        drain(warp);
        asm volatile("cp.async.wait_all;" ::: "memory");
        __syncthreads();
        cold_messages(smem, p, nn);
        mbar_wait(bar_tab, 1);
        return;
    }

    if (warp < 4 * NWG) {
        asm volatile("setmaxnreg.inc.sync.aligned.u32 %0;" ::"n"(REG_C));
        const int lane = fresh_lane();
        const int g = lane >> 2, q = lane & 3;
        const uint64_t dW1 = p.desc0, dW2 = dW1 + (W2_OFF >> 4), dWR = dW1 + (WR_OFF >> 4);
        const uint32_t ring = sb + RING_OFF + warp * 12288;
        const uint32_t vrow = pin(ring + g * 128 + ((q ^ ((g & 1) << 2) ^ (g >> 1)) << 4));
        const uint32_t mrow = pin(ring + (lane & 15) * 128 + (((lane >> 4) ^ ((lane & 1) << 2) ^ ((lane & 7) >> 1)) << 4));
        dst = pin(ring + (lane >> 3) * 256 + (((lane & 7) ^ (lane >> 3)) << 4)); l7 = pin((lane & 7) * 16); g32 = pin(g * 32);
        uint32_t ctl = sb + CTL_OFF + warp * 4;
        auto control = [&](uint32_t c, uint32_t at) {
            int it = 0;
#pragma unroll 1
            while (__builtin_expect(c == 0xFFFFFFFFu, 0)) {
                asm volatile("ld.volatile.shared.u32 %0, [%1];" : "=r"(c) : "r"(at) : "memory");
                c = __reduce_or_sync(0xffffffffu, c);
                if (++it > (1 << 24)) __trap();
            }
            return c;
        };
        uint32_t c0 = control(0xFFFFFFFFu, ctl), c1 = control(0xFFFFFFFFu, ctl + 64);
        if (warp >= 8) asm volatile("bar.arrive 1, 256;" ::: "memory");
        uint32_t acc[32];
        float P[32], W[32];
#pragma unroll
        for (int i = 0; i < 32; i++) { acc[i] = 0; P[i] = W[i] = 0.f; }
        mbar_wait(bar_tab, 1);
        sources(c0);
        e0 = __vminu2(e0, (N - 1) * 0x10001u);
        e1 = __vminu2(e1, (N - 1) * 0x10001u);
        if (warp >= 8) asm volatile("cp.async.wait_all;" ::: "memory");
        else if (warp >= 4) cp_wait1();
        load_v(IntC<0>{});
        auto finish = [&](uint32_t c, uint32_t node) {
            if (c & ST_CLOSE) {
                uint64_t op[2];
                asm("{\n.reg .b32 a;\nmad.lo.u32 a, %2, 512, %3;\nmad.wide.u32 %0, a, 1, %4;\nxor.b32 a, a, 64;\nmad.wide.u32 %1, a, 1, %4;\n}\n"
                    : "=l"(op[0]), "=l"(op[1]) : "r"(node), "r"(l7), "l"(p.out));
#pragma unroll
                for (int k = 0; k < 8; k++) {
                    uint32_t x[4];
#pragma unroll
                    for (int i = 0; i < 4; i++) x[i] = l7 & 64 ? acc[4 * (k ^ 1) + i] : acc[4 * k + i];
                    asm volatile("{\n.reg .pred p;\nsetp.lt.u32 p, %5, %6;\n@p st.global.cs.v4.u32 [%0], {%1,%2,%3,%4};\n}\n"
                                 ::"l"(op[k & 1] + 128 * (k >> 1)), "r"(x[0]), "r"(x[1]), "r"(x[2]), "r"(x[3]), "r"(node), "n"(NODE_SPLIT) : "memory");
                }
                if (__builtin_expect(__any_sync(0xffffffffu, (int)node >= (int)NODE_SPLIT), 0)) {
                    mbar_wait(sb + BAR_OFF + 16 + 8 * FLIGHT, 0);
                    if ((int)node >= (int)NODE_SPLIT) {
#pragma unroll
                        for (int k = 0; k < 8; k++)
                            asm volatile("red.global.add.noftz.v4.bf16x2 [%0], {%1,%2,%3,%4};" ::"l"((op[0] & ~64ull) + 64 * k), "r"(acc[4 * k]), "r"(acc[4 * k + 1]), "r"(acc[4 * k + 2]), "r"(acc[4 * k + 3]) : "memory");
                    }
                    __syncwarp();
                }
            }
        };
#pragma unroll 1
        while ((int)c0 >= 0) {
            uint32_t a[16], h[16], rf[4], rr[4], m[16];
            TRW(ctl);
            uint32_t dd[2], f01, f23;
            asm volatile("ld.shared.v2.u32 {%0,%1}, [%2 + %3];" : "=r"(dd[0]), "=r"(dd[1]) : "r"(((c0 & 0xFF00) | g32) >> 2), "n"(SB + SD_OFF));
            asm volatile("ld.shared.v2.u32 {%0,%1}, [%2 + %3];" : "=r"(f01), "=r"(f23) : "r"(l7), "n"(SB + FREQ_OFF));
            sources(c1);
            asm volatile("cp.async.wait_group 2;" ::: "memory");
            __syncwarp();
#pragma unroll
            for (int i = 0; i < 4; i++) ldsm4(mrow ^ (i << 5), a + 4 * i);
            wg_fence();
            wgmma_k64(P, a, dW1);
            wg_commit();
            SPLIT(1);
#pragma unroll
            for (int hh = 0; hh < 2; hh++) {
                const float sc = bf_hi(dd[hh]);
                const uint32_t x01 = hmul2_lo(f01, dd[hh]), x23 = hmul2_lo(f23, dd[hh]);
                rf[hh] = pack2(__sinf(bf_lo(x01)) * sc, __sinf(bf_hi(x01)) * sc);
                rf[2 + hh] = pack2(__sinf(bf_lo(x23)) * sc, __sinf(bf_hi(x23)) * sc);
            }
            asm volatile("" : "+r"(rf[0]), "+r"(rf[1]), "+r"(rf[2]), "+r"(rf[3]));
            asm volatile("bar.sync %0, 256;" ::"r"(1 + (warp >> 2)) : "memory");
            SPLIT(2);
            wg_wait<0>();
            fence_regs(P);
#pragma unroll
            for (int i = 0; i < 16; i++)
                h[i] = pack2(fmaf(P[2 * i], tanh_fast(P[2 * i]), P[2 * i]), fmaf(P[2 * i + 1], tanh_fast(P[2 * i + 1]), P[2 * i + 1]));
            wg_fence();
            wgmma_k64(P, h, dW2 + 1024);
            wgmma_first(W, rf, dWR + 256);
            wg_commit();
            asm volatile("bar.arrive %0, 256;" ::"r"((c0 >> 4) & 3) : "memory");
            SPLIT(3);
            cp_wait1();
            __syncwarp();
#pragma unroll
            for (int k = 0; k < 4; k++) lds2_if(vrow + 8192 + 1024 * k, (vrow ^ 64) + 8192 + 1024 * k, acc + 8 * k, c0 & ST_START);
            lds128(sb + SREC_OFF + (((c0 & 0xFF00) | g32) >> 1), rr);
            uint32_t c2 = lds32(ctl + 128);
            __syncwarp();
            load_s(IntC<1>{});
            cp_commit();
            if (c1 & ST_START) load_o();
            cp_commit();
            wg_wait<0>();
            fence_regs(P); fence_regs(W);
#pragma unroll
            for (int j = 0; j < 8; j++) {
                m[j] = pack2(P[4 * j] * W[4 * j], P[4 * j + 1] * W[4 * j + 1]);
                m[8 + j] = pack2(P[4 * j + 2] * W[4 * j + 2], P[4 * j + 3] * W[4 * j + 3]);
            }
            wg_fence();
            wgmma_k64(P, h, dW2);
            wgmma_first(W, rf, dWR);
            wg_commit();
            SPLIT(4);
            PIN8(m); PIN8(m + 8);
            c2 = __reduce_or_sync(0xffffffffu, c2);
#pragma unroll
            for (int k = 1; k < 4; k++)
#pragma unroll
                for (int j = 0; j < 8; j++) {
                    const uint32_t x = k == 1 ? hfma2_lo(m[j], rr[0], acc[8 * k + j]) : k == 2 ? hfma2_hi(m[j], rr[0], acc[8 * k + j]) : hfma2_lo(m[j], rr[1], acc[8 * k + j]);
                    acc[8 * k + j] = k == 1 ? hfma2_lo(m[8 + j], rr[2], x) : k == 2 ? hfma2_hi(m[8 + j], rr[2], x) : hfma2_lo(m[8 + j], rr[3], x);
                }
            PIN8(acc + 8); PIN8(acc + 16); PIN8(acc + 24);
            c2 = control(c2, ctl + 128);
            wg_wait<0>();
            fence_regs(P); fence_regs(W);
#pragma unroll
            for (int j = 0; j < 8; j++)
                acc[j] = hadd2(acc[j], pack2(fmaf(P[4 * j], W[4 * j], P[4 * j + 2] * W[4 * j + 2]), fmaf(P[4 * j + 1], W[4 * j + 1], P[4 * j + 3] * W[4 * j + 3])));
            wg_fence();
            wgmma_k64(P, h, dW2 + 512);
            wgmma_first(W, rf, dWR + 128);
            wg_commit();
            SPLIT(6);
            asm volatile("cp.async.wait_group 2;" ::: "memory");
            __syncwarp();
            uint32_t v[4][16];
#pragma unroll
            for (int i = 0; i < NPRE; i++) lds128((vrow ^ (64 * (i & 1))) + 2048 + 1024 * (i >> 2) + 3072 * ((i >> 1) & 1), v[1 + (i >> 2)] + 4 * (i & 3));
            wg_wait<0>();
            fence_regs(P); fence_regs(W);
#pragma unroll
            for (int j = 0; j < 8; j++) {
                m[j] = pack2(P[4 * j] * W[4 * j], P[4 * j + 1] * W[4 * j + 1]);
                m[8 + j] = pack2(P[4 * j + 2] * W[4 * j + 2], P[4 * j + 3] * W[4 * j + 3]);
            }
#pragma unroll
            for (int i = NPRE; i < 12; i++) lds128((vrow ^ (64 * (i & 1))) + 2048 + 1024 * (i >> 2) + 3072 * ((i >> 1) & 1), v[1 + (i >> 2)] + 4 * (i & 3));
            sources(c1);
            const uint32_t node = lds32(sb + SN_OFF + 4 + (((c0 >> 16) | g32) >> 2));
            __syncwarp();
            load_v(IntC<1>{});
#pragma unroll
            for (int k = 1; k < 4; k++)
#pragma unroll
                for (int j = 0; j < 8; j++) acc[8 * k + j] = hfma2(m[8 + j], v[k][8 + j], hfma2(m[j], v[k][j], acc[8 * k + j]));
            finish(c0, node);
            ctl += 64;
            c0 = c1;
            c1 = c2;
        }
        asm volatile("cp.async.wait_all;" ::: "memory");
        TRW(ctl);
        TSX(11, 0); TSX(12, 128); TSX(13, 256);
    } else {
        asm volatile("setmaxnreg.dec.sync.aligned.u32 %0;" ::"n"(REG_H));
        const int lane = fresh_lane();
        const uint32_t chunk = sb + (lane & 8 ? (lane & 4 ? SN_OFF : SD_OFF) + (lane & 3) * 16 : SREC_OFF + (lane & 7) * 16), pitch = lane & 8 ? 64 : 128;
        if (warp == 12) {
#pragma unroll 1
            for (int i = 0; i < (int)misc[2]; i++) {
                const uint32_t n = reinterpret_cast<const uint32_t*>(smem + SCNT_OFF)[i] * 32 + lane;
                reinterpret_cast<uint4*>(p.out)[n] = reinterpret_cast<const uint4*>(p.sv)[n];
            }
#pragma unroll 1
            for (int i = lane >> 4; i < give; i += 2) {
                uint32_t x[4];
                lds128(chunk + (ng - 1 - i) * pitch, x);
                p.g->pool[(b * GIVE + i) * 16 + (lane & 15)] = make_uint4(x[0], x[1], x[2], x[3]);
            }
            __threadfence();
            __syncwarp();
            if (lane == 0) {
                asm volatile("st.relaxed.gpu.global.u32 [%0], %1;" ::"l"(p.g->ready + b), "r"(~epoch) : "memory");
                mbar_arrive(sb + BAR_OFF + 16 + 8 * FLIGHT);
            }
        }
        if (warp == 15) {
            int k = lane < 4 * NWG ? lane : 255, next = 4 * NWG, j = 0, mine = ng - give, end = -1, take = 0;
            uint32_t busy, at = sb + CTL_OFF + 4 * lane, from = 0;
#pragma unroll 1
            do {
                if (next > mine && end < 0) {
                    end = mine = ng;
                    const int peer = b % 5 + 5 * lane;
                    uint32_t x = 255;
                    int it = 0;
                    if (peer < G) {
#pragma unroll 1
                        do {
                            asm volatile("ld.relaxed.gpu.global.u32 %0, [%1];" : "=r"(x) : "l"(p.g->rows + peer) : "memory");
                            if (++it > (1 << 22)) __trap();
                        } while ((x >> 16) != (~epoch & 0xFFFFu));
                    }
                    const int r = x & 255, n = __popc(__ballot_sync(0xffffffffu, r != 255));
                    const int level = min(((__reduce_add_sync(0xffffffffu, r != 255 ? r : 0) + n - 1) / max(n, 1) + 3) & ~3, MAXROW);
                    const uint32_t ed = r > level ? min(r - level, (int)(x >> 8) & 255) : min(level - r, ROOM) << 16;
                    uint32_t z = ed;
#pragma unroll
                    for (int o = 1; o < 32; o <<= 1) {
                        const uint32_t y = __shfl_up_sync(0xffffffffu, z, o);
                        if (lane >= o) z += y;
                    }
                    const uint32_t all = __shfl_sync(0xffffffffu, z, 31), moved = min(all & 0xFFFFu, all >> 16);
                    const uint32_t me = __shfl_sync(0xffffffffu, ed, b / 5), mz = __shfl_sync(0xffffffffu, z, b / 5) - me;
                    end = mine = ng - (min((mz + me) & 0xFFFFu, moved) - min(mz & 0xFFFFu, moved));
#pragma unroll 1
                    for (uint32_t u = mz >> 16; u < min((mz + me) >> 16, moved); u++, take++) {
                        const int f = __popc(__ballot_sync(0xffffffffu, (z & 0xFFFFu) <= u));
                        const uint32_t q = u - (__shfl_sync(0xffffffffu, z - ed, f) & 0xFFFFu);
                        if (lane == take) from = (b % 5 + 5 * f) << 8 | q;
                    }
                }
                if (next > mine && take) {
                    if (lane < take) {
                        uint32_t x;
                        int it = 0;
#pragma unroll 1
                        do {
                            asm volatile("ld.acquire.gpu.global.u32 %0, [%1];" : "=r"(x) : "l"(p.g->ready + (from >> 8)) : "memory");
                            if (++it > (1 << 22)) __trap();
                        } while (x != ~epoch);
                    }
                    __syncwarp();
#pragma unroll 1
                    for (end += take; take--;) {
                        const uint32_t f = __shfl_sync(0xffffffffu, from, take);
                        if (lane < 16)
                            asm volatile("cp.async.cg.shared.global [%0], [%1], 16;" ::"r"(chunk + (MAXROW - 1 - take) * pitch),
                                         "l"(p.g->pool + ((f >> 8) * GIVE + (f & 255)) * 16 + lane) : "memory");
                    }
                    take = 0;
                    asm volatile("cp.async.wait_all;" ::: "memory");
                    __threadfence_block();
                    __syncwarp();
                }
                const bool has = k < (end < 0 ? mine : end);
                const uint32_t i = k < mine ? k : MAXROW - 1 + mine - k, x = __shfl_sync(0xffffffffu, pk, j);
                const bool close = has && i >= (x >> 24);
                busy = __ballot_sync(0xffffffffu, has);
                const uint32_t m = __ballot_sync(0xffffffffu, close);
                uint32_t c = has ? ((x & 0xFF00) + i * 0x1000100) | (j ? 0u : ST_START) | (close ? ST_CLOSE : 0u) : MAXROW * 256;
                if (!(busy >> (lane & 12))) c |= 0x80000000u;
                c |= busy >> ((lane & 12) + 4) ? (lane & 12) * 4 + 32 : 16;
                sts32_if(at, c, lane < 16 || !busy);
                j = close ? 0 : j + 1;
                k = close ? next + __popc(m & ((1u << lane) - 1)) : k;
                next += __popc(m);
                at += 64;
            } while (busy);
        }
        if (warp == 15) mbar_wait(sb + BAR_OFF + 16 + 8 * FLIGHT, 0);
        else if (warp != 12) __nanosleep(ZDELAY);
        const int zend = misc[32] + misc[64];
#pragma unroll 1
        for (;;) {
            int r = 0;
            if (lane == 0) r = atomicAdd(&misc[4], 4u);
            r = __shfl_sync(0xffffffffu, r, 0) + 8 * ng;
            if (r >= zend) break;
            uint4 v[4];
            uint32_t n[4];
#pragma unroll
            for (int i = 0; i < 4; i++) {
                n[i] = reinterpret_cast<const uint32_t*>(smem + SN_OFF)[min(r + i, zend - 1) * 2 + 1] * 32 + lane;
                v[i] = __ldcs(reinterpret_cast<const uint4*>(p.sv) + n[i]);
            }
#pragma unroll
            for (int i = 0; i < 4; i++)
                if (r + i < zend) __stcs(reinterpret_cast<uint4*>(p.out) + n[i], v[i]);
        }
        static_assert(FLIGHT <= 4, "drain");
        drain(warp & 3);
        asm volatile("cp.async.wait_all;" ::: "memory");
        TSX(14, 384); TSX(15, 480); TSX(16, 416);
    }
}

}

extern "C" void kernel_launch(void* const* d_in, const int* in_sizes, int n_in, void* d_out, int out_size) {
    static int s_G = 0;
    static void* s_scratch = nullptr;
    const int N = in_sizes[0] / 256, E = in_sizes[2];
    if (s_G == 0) {
        cudaFuncSetAttribute(painn_kernel<0, 0, 0>, cudaFuncAttributeMaxDynamicSharedMemorySize, SMEM_BYTES);
        cudaFuncSetAttribute(painn_kernel<50000, 800000, 132>, cudaFuncAttributeMaxDynamicSharedMemorySize, SMEM_BYTES);
        int dev = 0, sms = 0, occ = 0;
        cudaGetDevice(&dev);
        cudaDeviceGetAttribute(&sms, cudaDevAttrMultiProcessorCount, dev);
        cudaOccupancyMaxActiveBlocksPerMultiprocessor(&occ, painn_kernel<0, 0, 0>, THREADS, SMEM_BYTES);
        cudaGetSymbolAddress(&s_scratch, g_scratch);
        s_G = occ >= 1 ? (sms < MAXG ? sms : MAXG) : 0;
    }
    if (s_G == 0 || N > TABLE_MAXN || N > s_G * MAXNPC || (s_G - 1) * ((N + s_G - 1) / s_G) >= N || E > MAXE || E < 4 * MAXG * MAXG) return;
    Params p;
    p.g = (Scratch*)s_scratch;
    p.sv = (const __nv_bfloat16*)d_in[0];
    p.pos = (const __nv_bfloat16*)d_in[1];
    p.src = (const int*)d_in[2];
    p.dst = (const int*)d_in[3];
    p.freqs = (const __nv_bfloat16*)d_in[4];
    p.w1 = (const __nv_bfloat16*)d_in[5];
    p.w2 = (const __nv_bfloat16*)d_in[6];
    p.wr = (const __nv_bfloat16*)d_in[7];
    p.out = (__nv_bfloat16*)d_out;
    p.desc0 = (uint64_t)(SB >> 4) | ((uint64_t)1 << 16) | ((uint64_t)64 << 32) | ((uint64_t)1 << 62);
    p.N = N; p.E = E; p.G = s_G;
    p.NPC = (N + s_G - 1) / s_G;
    p.magic = (uint32_t)(((1ull << 32) + p.NPC - 1) / p.NPC);
    p.gpc = ((E >> 2) + s_G - 1) / s_G;
    p.odd_edges = (E & 3) != 0 || p.gpc > 3 * THREADS;
    if (N == 50000 && E == 800000 && s_G == 132) painn_kernel<50000, 800000, 132><<<s_G, THREADS, SMEM_BYTES, cudaStreamPerThread>>>(p);
    else painn_kernel<0, 0, 0><<<s_G, THREADS, SMEM_BYTES, cudaStreamPerThread>>>(p);
}
```

```cpp
#include <cuda_runtime.h>
#include <cuda_bf16.h>
#include <stdint.h>

namespace {

constexpr int NWG = 3;
constexpr int REG_C = 160, REG_H = 32;
constexpr int SPL = 10;
constexpr int GIVE = 10, ROOM = 4;
constexpr int BIG = 5;
constexpr int CUT = 7;
constexpr int HDELAY = 150;
constexpr int TOUCH = 4, FLIGHT = 4;
constexpr int NPRE = 6;
constexpr int PDELAY = 150;
constexpr int ZDELAY = 1200;
constexpr int THREADS = 512;
constexpr int MAXG = 136;
constexpr int MAXROW = 96;
constexpr int TMAX = MAXROW / 12 + 18;
constexpr int MAXNPC = 480;
constexpr int MAXE = 1 << 20;

constexpr int W2_OFF = 8192;
constexpr int WR_OFF = 32768;
constexpr int RING_OFF = 38912;
constexpr int SREC_OFF = RING_OFF + 4 * NWG * 12288;
constexpr int SD_OFF = SREC_OFF + (MAXROW + 1) * 128 + 16;
constexpr int SN_OFF = SD_OFF + (MAXROW + 1) * 64 + 16;
constexpr int CTL_OFF = SN_OFF + (MAXROW + 1) * 64 + 16;
constexpr int TABLE_MAXN = 50176;
constexpr int STAGE_OFF = TABLE_MAXN * 4;
constexpr int SCNT_OFF = STAGE_OFF + MAXG * 128;
constexpr int PACK_OFF = RING_OFF + 6144;
constexpr int NCNT_OFF = SCNT_OFF + 768;
constexpr int OPOS_OFF = NCNT_OFF + 2048;
constexpr int BAR_OFF = OPOS_OFF + 4096;
constexpr int MISC_OFF = BAR_OFF + 128;
constexpr int FREQ_OFF = MISC_OFF + 512;
constexpr int DUMMY_OFF = (FREQ_OFF + 128 + 127) / 128 * 128;
constexpr int SMEM_BYTES = DUMMY_OFF + 4096;
static_assert(CTL_OFF + 64 * TMAX <= STAGE_OFF + 32 * THREADS && STAGE_OFF - SREC_OFF <= 32 * THREADS && 4 * (MAXG + 32) <= 768, "smem map");
static_assert(SMEM_BYTES <= 232448 && BAR_OFF % 8 == 0 && RING_OFF % 128 == 0 && SREC_OFF % 128 == 0 && (MAXG + 14) / 15 <= 12, "smem map");

constexpr uint32_t PAY_INVALID = 0x3FFFFFFu;
constexpr uint32_t PAY_MARK = 0x3FFFDFFu;
constexpr uint32_t NODE_SPLIT = 0x40000000u;
constexpr uint32_t ST_START = 1, ST_CLOSE = 2;
constexpr float QINVP = 9.0f / 510.0f;
constexpr uint32_t QTHRESH = 2209;
constexpr uint32_t QSURE = 1980;

struct Scratch {
    unsigned sync[32];
    uint4 table[TABLE_MAXN / 4];
    uint4 wimg[RING_OFF / 16];
    uint2 pos8[TABLE_MAXN];
    uint4 xbuf[MAXG * MAXG * 8 + 3 * THREADS];
    uint4 pool[MAXG * GIVE * 16];
    unsigned rows[MAXG];
    unsigned ready[MAXG];
    int ovfcnt[MAXG];
    int2 ovf[MAXE + 8 * MAXG + 8];
};
__device__ __align__(128) Scratch g_scratch;

struct Params {
    const __nv_bfloat16* pos;
    Scratch* g;
    const int* src;
    const int* dst;
    int N, NPC, E, gpc;
    const __nv_bfloat16* w2;
    const __nv_bfloat16* wr;
    const __nv_bfloat16* w1;
    const __nv_bfloat16* freqs;
    const __nv_bfloat16* sv;
    __nv_bfloat16* out;
    uint64_t desc0;
    int G;
    uint32_t magic;
    int odd_edges;
};
constexpr uint32_t SB = 1024;

#define TSX(i, thr)
#define TS0(i) TSX(i, 0)
#define TRW(ctl)

__device__ __forceinline__ uint32_t smem_u32(const void* p) { return (uint32_t)__cvta_generic_to_shared(p); }
__device__ __forceinline__ void mbar_init(uint32_t bar, uint32_t cnt) {
    asm volatile("mbarrier.init.shared::cta.b64 [%0], %1;" ::"r"(bar), "r"(cnt) : "memory");
}
__device__ __forceinline__ void mbar_arrive(uint32_t bar) {
    asm volatile("mbarrier.arrive.shared::cta.b64 _, [%0];" ::"r"(bar) : "memory");
}
__device__ __forceinline__ void mbar_expect_tx(uint32_t bar, uint32_t bytes) {
    asm volatile("mbarrier.arrive.expect_tx.shared::cta.b64 _, [%0], %1;" ::"r"(bar), "r"(bytes) : "memory");
}
__device__ __forceinline__ void mbar_wait(uint32_t bar, uint32_t parity) {
    uint32_t ok;
    int it = 0;
    do {
        asm volatile(
            "{\n.reg .pred p;\n"
            "mbarrier.try_wait.parity.shared::cta.b64 p, [%1], %2, 2000;\n"
            "selp.u32 %0, 1, 0, p;\n}\n"
            : "=r"(ok) : "r"(bar), "r"(parity) : "memory");
        if (++it > (1 << 20)) __trap();
    } while (!ok);
}
__device__ __forceinline__ uint32_t mbar_test(uint32_t bar, uint32_t parity) {
    uint32_t ok;
    asm volatile("{\n.reg .pred p;\nmbarrier.test_wait.parity.shared::cta.b64 p, [%1], %2;\nselp.u32 %0, 1, 0, p;\n}\n"
                 : "=r"(ok) : "r"(bar), "r"(parity) : "memory");
    return ok;
}
__device__ __forceinline__ uint32_t pin(uint32_t x) {
    uint32_t r;
    asm volatile("shfl.sync.bfly.b32 %0, %1, 0, 31, -1;" : "=r"(r) : "r"(x));
    return r;
}
__device__ __forceinline__ void bulk_g2s(uint32_t dst, const void* src, uint32_t bytes, uint32_t bar) {
    asm volatile("cp.async.bulk.shared::cluster.global.mbarrier::complete_tx::bytes [%0], [%1], %2, [%3];"
                 ::"r"(dst), "l"(src), "r"(bytes), "r"(bar) : "memory");
}
__device__ __forceinline__ void ldsm4(uint32_t addr, uint32_t* r) {
    asm volatile("ldmatrix.sync.aligned.m8n8.x4.shared.b16 {%0,%1,%2,%3}, [%4];"
                 : "=r"(r[0]), "=r"(r[1]), "=r"(r[2]), "=r"(r[3]) : "r"(addr) : "memory");
}
__device__ __forceinline__ uint32_t pack2(float lo, float hi) {
    uint32_t r;
    asm("cvt.rn.bf16x2.f32 %0, %1, %2;" : "=r"(r) : "f"(hi), "f"(lo));
    return r;
}
__device__ __forceinline__ float bf_lo(uint32_t w) { return __uint_as_float(w << 16); }
__device__ __forceinline__ float bf_hi(uint32_t w) { return __uint_as_float(w & 0xFFFF0000u); }
__device__ __forceinline__ float rbf16(float x) { return __uint_as_float(pack2(0.f, x)); }
__device__ __forceinline__ uint32_t hmul2(uint32_t a, uint32_t b) {
    uint32_t r;
    asm("mul.rn.bf16x2 %0, %1, %2;" : "=r"(r) : "r"(a), "r"(b));
    return r;
}
__device__ __forceinline__ uint32_t hfma2(uint32_t a, uint32_t b, uint32_t c) {
    uint32_t r;
    asm("fma.rn.bf16x2 %0, %1, %2, %3;" : "=r"(r) : "r"(a), "r"(b), "r"(c));
    return r;
}
__device__ __forceinline__ uint32_t hfma2_lo(uint32_t a, uint32_t b, uint32_t c) {
    uint32_t r;
    asm("{\n.reg .b16 l, h;\n.reg .b32 t;\nmov.b32 {l, h}, %2;\nmov.b32 t, {l, l};\nfma.rn.bf16x2 %0, %1, t, %3;\n}\n" : "=r"(r) : "r"(a), "r"(b), "r"(c));
    return r;
}
__device__ __forceinline__ uint32_t hfma2_hi(uint32_t a, uint32_t b, uint32_t c) {
    uint32_t r;
    asm("{\n.reg .b16 l, h;\n.reg .b32 t;\nmov.b32 {l, h}, %2;\nmov.b32 t, {h, h};\nfma.rn.bf16x2 %0, %1, t, %3;\n}\n" : "=r"(r) : "r"(a), "r"(b), "r"(c));
    return r;
}
__device__ __forceinline__ uint32_t hadd2(uint32_t a, uint32_t b) {
    uint32_t r;
    asm("add.rn.bf16x2 %0, %1, %2;" : "=r"(r) : "r"(a), "r"(b));
    return r;
}
__device__ __forceinline__ uint32_t hsub2(uint32_t a, uint32_t b) {
    uint32_t r;
    asm("sub.rn.bf16x2 %0, %1, %2;" : "=r"(r) : "r"(a), "r"(b));
    return r;
}
__device__ __forceinline__ float tanh_fast(float x) {
    float r;
    asm("tanh.approx.f32 %0, %1;" : "=f"(r) : "f"(x));
    return r;
}
__device__ __forceinline__ void wg_fence() { asm volatile("wgmma.fence.sync.aligned;" ::: "memory"); }
__device__ __forceinline__ void wg_commit() { asm volatile("wgmma.commit_group.sync.aligned;" ::: "memory"); }
template <int N>
__device__ __forceinline__ void wg_wait() { asm volatile("wgmma.wait_group.sync.aligned %0;" ::"n"(N) : "memory"); }

#define WG_REGS "{%0,%1,%2,%3,%4,%5,%6,%7,%8,%9,%10,%11,%12,%13,%14,%15,%16,%17,%18,%19,%20,%21,%22,%23,%24,%25,%26,%27,%28,%29,%30,%31}"
#define WG_OPS(c) c(d[0]), c(d[1]), c(d[2]), c(d[3]), c(d[4]), c(d[5]), c(d[6]), c(d[7]), c(d[8]), c(d[9]), c(d[10]), \
    c(d[11]), c(d[12]), c(d[13]), c(d[14]), c(d[15]), c(d[16]), c(d[17]), c(d[18]), c(d[19]), c(d[20]), c(d[21]),     \
    c(d[22]), c(d[23]), c(d[24]), c(d[25]), c(d[26]), c(d[27]), c(d[28]), c(d[29]), c(d[30]), c(d[31])
__device__ __forceinline__ void wgmma_first(float* d, const uint32_t* a, uint64_t desc) {
    asm volatile("wgmma.mma_async.sync.aligned.m64n64k16.f32.bf16.bf16 " WG_REGS ", {%32,%33,%34,%35}, %36, 0, 1, 1, 1;"
                 : WG_OPS("+f") : "r"(a[0]), "r"(a[1]), "r"(a[2]), "r"(a[3]), "l"(desc));
}
__device__ __forceinline__ void wgmma_acc(float* d, const uint32_t* a, uint64_t desc) {
    asm volatile("wgmma.mma_async.sync.aligned.m64n64k16.f32.bf16.bf16 " WG_REGS ", {%32,%33,%34,%35}, %36, 1, 1, 1, 1;"
                 : WG_OPS("+f") : "r"(a[0]), "r"(a[1]), "r"(a[2]), "r"(a[3]), "l"(desc));
}
__device__ __forceinline__ void wgmma_k64(float* d, const uint32_t* a, uint64_t desc) {
    wgmma_first(d, a, desc);
    wgmma_acc(d, a + 4, desc + 128);
    wgmma_acc(d, a + 8, desc + 256);
    wgmma_acc(d, a + 12, desc + 384);
}
__device__ __forceinline__ void fence_regs(float* d) { asm volatile("" : WG_OPS("+f")::"memory"); }
__device__ __forceinline__ uint32_t qaxis(float x) {
    const float u = fmaf(x, QINVP, 0.25f);
    const float f = u - ((u + 12582912.f) - 12582912.f);
    return __float_as_uint(fmaf(fabsf(f), 510.f, 12582912.f));
}
__device__ __forceinline__ uint32_t qcode(float x, float y, float z, uint32_t tx) {
    return __byte_perm(__byte_perm(qaxis(x), qaxis(y), 0x3340), qaxis(z), 0x3410) ^ tx;
}
__device__ __forceinline__ bool near_test(uint32_t ca, uint32_t cb, uint32_t tag24, uint32_t& q) {
    const uint32_t D = __vabsdiffu4(ca, cb);
    q = __dp4a(D, D, 0x7FFFFFFFu - QSURE);
    return q <= 0x7FFFFFFFu - QSURE + QTHRESH || ((ca ^ tag24) | (cb ^ tag24)) >= 0x1000000u;
}
__device__ __forceinline__ bool inside(uint32_t rxy, uint32_t rz) {
    const uint32_t qxy = hmul2(rxy, rxy), qz = hmul2(rz, rz);
    return bf_lo(qxy) + bf_hi(qxy) + bf_lo(qz) <= 24.8125f;
}

__device__ __forceinline__ uint32_t lds32(uint32_t addr) {
    uint32_t r;
    asm volatile("ld.shared.u32 %0, [%1];" : "=r"(r) : "r"(addr));
    return r;
}
__device__ __forceinline__ void sts32_if(uint32_t addr, uint32_t v, bool c) {
    asm volatile("{\n.reg .pred p;\nsetp.ne.u32 p, %2, 0;\n@p st.shared.u32 [%0], %1;\n}\n" ::"r"(addr), "r"(v), "r"((uint32_t)c) : "memory");
}
__device__ __forceinline__ void stg128_if(void* ptr, uint4 v, bool c) {
    asm volatile("{\n.reg .pred p;\nsetp.ne.u32 p, %5, 0;\n@p st.relaxed.gpu.global.v4.u32 [%0], {%1,%2,%3,%4};\n}\n"
                 ::"l"(ptr), "r"(v.x), "r"(v.y), "r"(v.z), "r"(v.w), "r"((uint32_t)c) : "memory");
}
__device__ __forceinline__ void lds128(uint32_t addr, uint32_t* r) {
    asm volatile("ld.shared.v4.u32 {%0,%1,%2,%3}, [%4];" : "=r"(r[0]), "=r"(r[1]), "=r"(r[2]), "=r"(r[3]) : "r"(addr) : "memory");
}
template <int NP, int HI, int PAD = 1>
__device__ __forceinline__ void gather(uint32_t dst, const void* base, uint32_t c, uint32_t e) {
#define GATHER_HEAD "{\n.reg .pred p;\n.reg .b32 n;\n.reg .b64 a;\nprmt.b32 n, %2, 0, %3;\nsetp.ne.u32 p, n, 0xFFFF;\nmad.lo.u32 n, n, 512, %4;\nmad.wide.u32 a, n, 1, %1;\n"
#define GATHER_1(P) P "cp.async.cg.shared.global [%0], [a], 16;\n}\n"
#define GATHER_3(P) P "cp.async.cg.shared.global [%0], [a + 128], 16;\n" P "cp.async.cg.shared.global [%0 + 1024], [a + 256], 16;\n" \
                    P "cp.async.cg.shared.global [%0 + 2048], [a + 384], 16;\n}\n"
#define GATHER_ARGS(z) ::"r"(dst), "l"(base), "r"(e), "n"((HI ? 0x32 : 0x10) + z), "r"(c) : "memory"
    if constexpr (NP == 1 && PAD) asm volatile(GATHER_HEAD GATHER_1("@p ") GATHER_ARGS(0x4400));
    if constexpr (NP == 1 && !PAD) asm volatile(GATHER_HEAD GATHER_1("") GATHER_ARGS(0x4400));
    if constexpr (NP == 3 && PAD) asm volatile(GATHER_HEAD GATHER_3("@p ") GATHER_ARGS(0x5500));
    if constexpr (NP == 3 && !PAD) asm volatile(GATHER_HEAD GATHER_3("") GATHER_ARGS(0x4400));
    if constexpr (NP == 4)
        asm volatile(GATHER_HEAD "setp.ge.u32 p, %2, 0x40000000;\ncp.async.cg.shared.global [%0], [a], 16, p;\ncp.async.cg.shared.global [%0 + 1024], [a + 128], 16, p;\n"
                     "cp.async.cg.shared.global [%0 + 2048], [a + 256], 16, p;\ncp.async.cg.shared.global [%0 + 3072], [a + 384], 16, p;\n}\n" GATHER_ARGS(0x4400));
}
__device__ __forceinline__ void cp_commit() { asm volatile("cp.async.commit_group;" ::: "memory"); }
__device__ __forceinline__ void cp_wait1() { asm volatile("cp.async.wait_group 1;" ::: "memory"); }
__device__ __forceinline__ uint32_t hmul2_lo(uint32_t a, uint32_t b) {
    uint32_t r;
    asm("{\n.reg .b16 l, h;\n.reg .b32 t;\nmov.b32 {l, h}, %2;\nmov.b32 t, {l, l};\nmul.rn.bf16x2 %0, %1, t;\n}\n" : "=r"(r) : "r"(a), "r"(b));
    return r;
}
__device__ __forceinline__ void lds2_if(uint32_t a0, uint32_t a1, uint32_t* r, uint32_t c) {
    asm volatile("{\n.reg .pred p;\nsetp.ne.u32 p, %10, 0;\n@p ld.shared.v4.u32 {%0,%1,%2,%3}, [%8];\n@p ld.shared.v4.u32 {%4,%5,%6,%7}, [%9];\n}\n"
                 : "+r"(r[0]), "+r"(r[1]), "+r"(r[2]), "+r"(r[3]), "+r"(r[4]), "+r"(r[5]), "+r"(r[6]), "+r"(r[7])
                 : "r"(a0), "r"(a1), "r"(c) : "memory");
}
__device__ __forceinline__ int fresh_lane() {
    int l;
    asm volatile("mov.u32 %0, %%laneid;" : "=r"(l));
    return l;
}

__device__ __forceinline__ void cold_edges(unsigned char* smem, const Params& p, int lo, int hi, uint32_t tag) {
#pragma unroll 1
    for (int e = lo + threadIdx.x; e < hi; e += THREADS) {
        const int s = p.src[e], d = p.dst[e];
        uint32_t q;
        if (near_test(reinterpret_cast<const uint32_t*>(smem)[s], reinterpret_cast<const uint32_t*>(smem)[d], tag << 24, q)) {
            const uint32_t own = __umulhi((uint32_t)d, p.magic);
            const uint32_t slot4 = atomicAdd(reinterpret_cast<uint32_t*>(smem + SCNT_OFF) + own, 4u);
            uint32_t* line = reinterpret_cast<uint32_t*>(smem + STAGE_OFF) + own * 32;
            if (slot4 < 124) {
                line[(slot4 >> 2) ^ ((own & 7) << 2)] = ((uint32_t)s << 15) + ((uint32_t)(d - own * p.NPC) << 6) + tag + (q & 0x80000000u);
            } else {
                uint32_t o = atomicAdd(reinterpret_cast<uint32_t*>(smem + MISC_OFF) + 16, 1u);
                p.g->ovf[(size_t)blockIdx.x * (4 * p.gpc + 4) + o] = make_int2(s, d);
                line[31 ^ ((own & 7) << 2)] = (PAY_MARK << 6) | tag;
            }
        }
    }
}
__device__ __forceinline__ void cold_filter(unsigned char* smem, const Params& p, int e0, int e1, uint32_t tag, int redo) {
    if (redo) {
        if (threadIdx.x < MAXG) reinterpret_cast<uint32_t*>(smem + SCNT_OFF)[threadIdx.x] = 0;
        __syncthreads();
    }
    cold_edges(smem, p, redo ? 4 * e0 : 4 * (e0 + 3 * THREADS), 4 * e1, tag);
    if (blockIdx.x == 0) cold_edges(smem, p, p.E & ~3, p.E, tag);
    __syncthreads();
    if (threadIdx.x == 0) p.g->ovfcnt[blockIdx.x] = reinterpret_cast<uint32_t*>(smem + MISC_OFF)[16];
    __threadfence();
    __syncthreads();
}
__device__ __forceinline__ uint3 geometry(uint32_t rxy, uint32_t rz) {
    const uint32_t qxy = hmul2(rxy, rxy), qz = hmul2(rz, rz);
    float d, id;
    asm("sqrt.approx.ftz.f32 %0, %1;" : "=f"(d) : "f"(rbf16(rbf16(bf_lo(qxy) + bf_hi(qxy) + bf_lo(qz)) + 1e-8f)));
    d = rbf16(d);
    asm("rcp.approx.ftz.f32 %0, %1;" : "=f"(id) : "f"(d));
    const float cs = rbf16(__cosf(rbf16(rbf16(3.14159265358979f * d) * 0.2f)));
    const uint32_t zs = pack2(bf_lo(rz) * id, 0.5f * rbf16(cs + 1.0f) * id);
    return d < 5.0f ? make_uint3(pack2(bf_lo(rxy) * id, bf_hi(rxy) * id), zs, __byte_perm(__float_as_uint(d), zs, 0x7632)) : make_uint3(0, 0, 0);
}
__device__ __forceinline__ void cold_messages(unsigned char* smem, const Params& p, int nn) {
    const int nbase = blockIdx.x * p.NPC, lane = threadIdx.x & 31;
    const uint32_t* box = reinterpret_cast<const uint32_t*>(p.g->xbuf) + blockIdx.x * p.G * 32;
    uint32_t* w = reinterpret_cast<uint32_t*>(smem + RING_OFF);
#pragma unroll 1
    for (int i = threadIdx.x; i < 9728; i += THREADS)
        w[i] = i < 2048 ? reinterpret_cast<const uint32_t*>(p.w1)[i] : i < 8192 ? reinterpret_cast<const uint32_t*>(p.w2)[i - 2048] : reinterpret_cast<const uint32_t*>(p.wr)[i - 8192];
#pragma unroll 1
    for (int i = threadIdx.x; i < nn * 32; i += THREADS) reinterpret_cast<uint4*>(p.out)[nbase * 32 + i] = reinterpret_cast<const uint4*>(p.sv)[nbase * 32 + i];
    __threadfence();
    __syncthreads();
    const float freq = __bfloat162float(p.freqs[lane & 15]);
#pragma unroll 1
    for (int m = -1; m < p.G; m++) {
        const int cnt = m < 0 ? p.G * 32 : (__ldcg(box + m * 32 + 31) >> 6) == PAY_MARK ? __ldcg(&p.g->ovfcnt[m]) : 0;
#pragma unroll 1
        for (int i = threadIdx.x; i - lane < cnt; i += THREADS) {
            int2 e = make_int2(0, -1);
            if (i < cnt) {
                if (m < 0) {
                    const uint32_t x = __ldcg(box + i);
                    e = make_int2((x >> 15) & 0xFFFFu, nbase + ((x >> 6) & 511u));
                } else {
                    e = __ldcg(p.g->ovf + (size_t)m * (4 * p.gpc + 4) + i);
                }
            }
            bool in = (uint32_t)(e.y - nbase) < (uint32_t)nn;
            uint3 geo = make_uint3(0, 0, 0);
            if (in) {
                const uint2 ps = __ldcg(p.g->pos8 + e.x), pd = __ldcg(p.g->pos8 + e.y);
                const uint32_t rxy = hsub2(ps.x, pd.x), rz = hsub2(ps.y, pd.y);
                in = inside(rxy, rz);
                geo = geometry(rxy, rz);
            }
#pragma unroll 1
            for (uint32_t todo = __ballot_sync(0xffffffffu, in); todo; todo &= todo - 1) {
                const int l = __ffs(todo) - 1;
                const uint32_t* row = reinterpret_cast<const uint32_t*>(p.sv) + (size_t)__shfl_sync(0xffffffffu, e.x, l) * 128 + lane;
                uint32_t* orow = reinterpret_cast<uint32_t*>(p.out) + (size_t)__shfl_sync(0xffffffffu, e.y, l) * 128 + lane;
                const uint32_t gx = __shfl_sync(0xffffffffu, geo.x, l), gy = __shfl_sync(0xffffffffu, geo.y, l);
                const float rb = rbf16(__sinf(rbf16(bf_lo(__shfl_sync(0xffffffffu, geo.z, l)) * freq)) * bf_hi(gy));
                uint32_t x = row[0];
                float a[12] = {0, 0, 0, 0, 0, 0, 0, 0, 0, 0, 0, 0};
#pragma unroll 2
                for (int k = 0; k < 64; k++) {
                    const uint32_t u = __shfl_sync(0xffffffffu, x, k >> 1), ww = w[k * 32 + lane];
                    const float f = k & 1 ? bf_hi(u) : bf_lo(u);
                    a[0] = fmaf(f, bf_lo(ww), a[0]); a[1] = fmaf(f, bf_hi(ww), a[1]);
                }
                x = pack2(0.5f * fmaf(a[0], tanh_fast(0.5f * a[0]), a[0]), 0.5f * fmaf(a[1], tanh_fast(0.5f * a[1]), a[1]));
                a[0] = a[1] = 0.f;
#pragma unroll 2
                for (int k = 0; k < 64; k++) {
                    const uint32_t u = __shfl_sync(0xffffffffu, x, k >> 1);
                    const float f = k & 1 ? bf_hi(u) : bf_lo(u), r = __shfl_sync(0xffffffffu, rb, k & 15);
#pragma unroll
                    for (int c = 0; c < 3; c++) {
                        const uint32_t ww = w[2048 + k * 96 + c * 32 + lane], wr = k < 16 ? w[8192 + k * 96 + c * 32 + lane] : 0u;
                        a[2 * c] = fmaf(f, bf_lo(ww), a[2 * c]); a[2 * c + 1] = fmaf(f, bf_hi(ww), a[2 * c + 1]);
                        a[6 + 2 * c] = fmaf(r, bf_lo(wr), a[6 + 2 * c]); a[7 + 2 * c] = fmaf(r, bf_hi(wr), a[7 + 2 * c]);
                    }
                }
                const uint32_t mv = pack2(a[2] * a[8], a[3] * a[9]), mr = pack2(a[4] * a[10], a[5] * a[11]);
                const uint32_t o[4] = {pack2(a[0] * a[6], a[1] * a[7]), hfma2_lo(mr, gx, hmul2(mv, row[32])), hfma2_hi(mr, gx, hmul2(mv, row[64])),
                                       hfma2_lo(mr, gy, hmul2(mv, row[96]))};
#pragma unroll
                for (int c = 0; c < 4; c++) asm volatile("red.global.add.noftz.bf16x2 [%0], %1;" ::"l"(orow + 32 * c), "r"(o[c]) : "memory");
            }
        }
    }
}

#define SPLIT(k) asm volatile("{\n.reg .pred p;\nsetp.eq.u32 p, %0, %1;\n@p trap;\n}" ::"r"(c0), "n"(0x70000 + k) : "memory")
#define PIN8(a) asm volatile("" : "+r"((a)[0]), "+r"((a)[1]), "+r"((a)[2]), "+r"((a)[3]), "+r"((a)[4]), "+r"((a)[5]), "+r"((a)[6]), "+r"((a)[7]))
template <int V> struct IntC { static constexpr int value = V; };

template <int CN, int CE, int CG>
__global__ void __launch_bounds__(THREADS, 1) painn_kernel(const __grid_constant__ Params p) {
    extern __shared__ __align__(1024) unsigned char smem_dyn[];
    unsigned char* const smem = static_cast<unsigned char*>(__cvta_shared_to_generic(SB));
    constexpr uint32_t sb = SB;
    const int tid = threadIdx.x, lane = tid & 31;
    const int warp = __shfl_sync(0xffffffffu, tid >> 5, 0);
    constexpr int CNPC = CG ? (CN + CG - 1) / CG : 1, CGPC = CG ? (CE / 4 + CG - 1) / CG : 1;
    const int b = blockIdx.x, G = CG ? CG : p.G, NPC = CG ? CNPC : p.NPC, N = CG ? CN : p.N, gpc = CG ? CGPC : p.gpc;
    const uint32_t magic = CG ? (uint32_t)(((1ull << 32) + CNPC - 1) / CNPC) : p.magic;
    const bool odd_edges = CG ? (CE & 3) != 0 || CGPC > 3 * THREADS : p.odd_edges;
    const int nbase = b * NPC, nn = min(NPC, N - nbase);
    const int eg0 = b * gpc, eg1 = min((CG ? CE : p.E) >> 2, eg0 + gpc);

    uint4* stage4 = reinterpret_cast<uint4*>(smem + STAGE_OFF);
    uint32_t* ncnt = reinterpret_cast<uint32_t*>(smem + NCNT_OFF);
    uint32_t* misc = reinterpret_cast<uint32_t*>(smem + MISC_OFF);
    const uint32_t bar_tab = sb + BAR_OFF;

    TS0(0);
    int4 es[3], ed[3];
    auto load_edges = [&](int i) {
        const int g = min(eg0 + tid + i * THREADS, eg1 - 1);
        asm volatile("ld.global.cs.v4.u32 {%0,%1,%2,%3}, [%8];\nld.global.cs.v4.u32 {%4,%5,%6,%7}, [%9];"
                     : "=r"(es[i].x), "=r"(es[i].y), "=r"(es[i].z), "=r"(es[i].w), "=r"(ed[i].x), "=r"(ed[i].y), "=r"(ed[i].z), "=r"(ed[i].w)
                     : "l"(reinterpret_cast<const int4*>(p.src) + g), "l"(reinterpret_cast<const int4*>(p.dst) + g) : "memory");
    };
    es[0] = ed[0] = make_int4(0, 0, 0, 0);
    const char* const own = reinterpret_cast<const char*>(p.sv) + (size_t)nbase * 512;
    auto touch = [&](int o) {
        if (o + lane * 256 < nn * 512)
            asm volatile("cp.async.ca.shared.global.L2::256B [%0], [%1], 4;" ::"r"(sb + DUMMY_OFF + 4 * lane), "l"(own + o + lane * 256) : "memory");
    };
    uint4* const xout = p.g->xbuf + ((tid >> 3) * G + b) * 8 + (tid & 7);
    unsigned epoch;
    const uint32_t tbytes = ((N + 3) >> 2) * 16, cut = (tbytes >> 8) * CUT * 16, bar_cut = sb + BAR_OFF + 120;
    {
        uint32_t pxy, pz;
        if constexpr (CG && CN % 2 == 0) {
            asm volatile("ld.global.nc.u32 %0, [%3];\nld.global.nc.u32 %1, [%3 + 4];\nld.global.ca.u32 %2, [%4];"
                         : "=r"(pxy), "=r"(pz), "=r"(epoch)
                         : "l"(reinterpret_cast<const uint32_t*>(p.pos) + ((nbase + min(tid, nn - 1)) * 3 >> 1)), "l"(p.g->sync) : "memory");
            const uint32_t sh = ((nbase + tid) & 1) << 4;
            pxy = __funnelshift_r(pxy, pz, sh);
            pz >>= sh;
        } else {
            const uint16_t* q = reinterpret_cast<const uint16_t*>(p.pos) + (nbase + min(tid, nn - 1)) * 3;
            pxy = q[0] | (uint32_t)q[1] << 16;
            pz = q[2];
            asm volatile("ld.global.ca.u32 %0, [%1];" : "=r"(epoch) : "l"(p.g->sync) : "memory");
        }
        const uint32_t code = qcode(bf_lo(pxy), bf_hi(pxy), bf_lo(pz), ((epoch & 31u) ^ 0x6Bu) << 24);
        asm volatile("{\n.reg .pred p;\nsetp.lt.s32 p, %2, %3;\n@p st.global.u32 [%0], %1;\n}\n"
                     ::"l"(reinterpret_cast<uint32_t*>(p.g->table) + nbase + tid), "r"(code), "r"(tid), "r"(nn) : "memory");
        __syncthreads();
        asm volatile("{\n.reg .pred p;\nsetp.eq.u32 p, %1, %2;\n@p red.relaxed.gpu.global.add.u32 [%0], 1;\n}\n" ::"l"(p.g->sync + 1), "r"(tid), "n"(THREADS - 1) : "memory");
        if (tid < THREADS - 32) load_edges(0);
        if (tid < nn) p.g->pos8[nbase + tid] = make_uint2(pxy, pz);
        reinterpret_cast<uint2*>(smem + OPOS_OFF)[tid] = make_uint2(pxy, pz);
    }
    const uint32_t tag = (epoch & 31u) | 32u;
    if (tid == THREADS - 1) {
        TSX(1, 511);
        mbar_init(bar_tab, 1);
        mbar_init(bar_cut, 1);
        mbar_expect_tx(bar_cut, cut);
        mbar_expect_tx(bar_tab, tbytes - cut);
        const unsigned want = (epoch + 1) * G;
        unsigned c;
        int it = smem_u32(smem_dyn) == SB ? 0 : 1 << 22;
        __nanosleep(HDELAY);
        do {
            asm volatile("ld.relaxed.gpu.global.u32 %0, [%1];" : "=r"(c) : "l"(p.g->sync + 1) : "memory");
            if (++it > (1 << 22)) __trap();
        } while (c != want);
        bulk_g2s(sb, p.g->table, cut, bar_cut);
        bulk_g2s(sb + cut, reinterpret_cast<const char*>(p.g->table) + cut, tbytes - cut, bar_tab);
        TSX(2, 511);
    }
    if (warp == 14) {
#pragma unroll 1
        for (int c = b * 32 + lane; c < RING_OFF / 16; c += G * 32) {
            const int row = c >> 3, j = (c ^ row) & 7;
            uint4 v;
            if (c < 512) {
                const uint32_t half = 0x3F003F00u;
                v = __ldg(reinterpret_cast<const uint4*>(p.w1) + row * 8 + j);
                v = make_uint4(hmul2(v.x, half), hmul2(v.y, half), hmul2(v.z, half), hmul2(v.w, half));
            } else {
                const uint32_t* q = (c < 2048 ? reinterpret_cast<const uint32_t*>(p.w2) + (row & 63) * 96 + ((row >> 6) - 1) * 32
                                              : reinterpret_cast<const uint32_t*>(p.wr) + (row & 15) * 96 + ((row >> 4) - 16) * 32) + (j & 4) * 4 + (j & 3);
                v = make_uint4(__ldg(q), __ldg(q + 4), __ldg(q + 8), __ldg(q + 12));
            }
            p.g->wimg[c] = v;
        }
    }
    if (tid == 416) {
#pragma unroll
        for (int i = 0; i < FLIGHT + 2; i++) mbar_init(sb + BAR_OFF + 8 + 8 * i, i ? 1 : 15);
    }
    ncnt[tid] = tid < 480 ? 0 : 1024;
    if (tid < MAXG + 32) reinterpret_cast<uint32_t*>(smem + SCNT_OFF)[tid] = tid < MAXG ? 0 : 128;
    if (tid < 128) misc[tid] = 0;
    {
        const uint32_t inv = (PAY_INVALID << 6) | tag;
        stage4[tid] = stage4[tid + THREADS] = make_uint4(inv, inv, inv, inv);
        if (tid < MAXG * 8 - 2 * THREADS) stage4[tid + 2 * THREADS] = make_uint4(inv, inv, inv, inv);
    }
    __syncthreads();
    if ((tid >> 4) == 29) asm volatile("cp.async.ca.shared.global [%0], [%1], 4;" ::"r"(sb + FREQ_OFF + 8 * (tid & 14) + 4 * (tid & 1)),
                              "l"(reinterpret_cast<const uint32_t*>(p.freqs) + ((tid & 7) >> 1) + (tid & 1) * 4) : "memory");
    if (warp == 15) load_edges(0);
    if (warp < 8) mbar_wait(bar_cut, 0);
    load_edges(1);
    load_edges(2);
    if (tid == 416) asm volatile("fence.acq_rel.gpu;" ::: "memory");
    if (warp >= 8) mbar_wait(bar_cut, 0);
#pragma unroll
    for (int i = 0; i < 3; i++) stg128_if(xout + i * G * THREADS, make_uint4(0, 0, 0, 0), tid + i * THREADS < G * 8);
    bool full = false;
    {
        uint32_t at[24], msg[12], cnt[12], line[12];
#pragma unroll
        for (int j = 0; j < 12; j++) {
            const uint32_t s = j % 4 == 0 ? es[j / 4].x : j % 4 == 1 ? es[j / 4].y : j % 4 == 2 ? es[j / 4].z : es[j / 4].w;
            const uint32_t d = j % 4 == 0 ? ed[j / 4].x : j % 4 == 1 ? ed[j / 4].y : j % 4 == 2 ? ed[j / 4].z : ed[j / 4].w;
            const uint32_t own = __umulhi(d, magic);
            at[2 * j] = 4 * s; at[2 * j + 1] = 4 * d;
            msg[j] = own * (uint32_t)(-64 * NPC) + ((s << 15) + ((d << 6) + tag));
            cnt[j] = eg0 + tid + (j / 4) * THREADS < eg1 ? 4 * own : 4 * (MAXG + lane);
            line[j] = own * 128 + ((own & 7) << 4);
            asm volatile("" : "+r"(at[2 * j]), "+r"(at[2 * j + 1]), "+r"(msg[j]), "+r"(cnt[j]), "+r"(line[j]));
        }
        mbar_wait(bar_tab, 0);
        TS0(3);
        if (warp == 15) {
#pragma unroll
            for (int i = 0; i < TOUCH; i++) touch(i * 8192);
        }
#pragma unroll
        for (int i = 0; i < 12; i += 6) {
            uint32_t sl[6], cd[12];
#pragma unroll
            for (int j = 0; j < 12; j++) cd[j] = lds32(sb + at[2 * i + j]);
#pragma unroll
            for (int j = 0; j < 6; j++) {
                uint32_t q;
                const bool c = near_test(cd[2 * j], cd[2 * j + 1], tag << 24, q);
                msg[i + j] |= q & 0x80000000u;
                asm volatile("atom.shared.add.u32 %0, [%1 + %2], 4;" : "=r"(sl[j]) : "r"(c ? cnt[i + j] : 4 * (MAXG + lane)), "n"(SB + SCNT_OFF) : "memory");
            }
#pragma unroll
            for (int j = 0; j < 6; j++) {
                sts32_if(sb + STAGE_OFF + (line[i + j] ^ sl[j]), msg[i + j], sl[j] < 124);
                full |= sl[j] == 124;
            }
        }
    }
    {
        const int redo = __syncthreads_or(full);
        if (__builtin_expect(redo || odd_edges, 0)) cold_filter(smem, p, eg0, eg1, tag, redo);
    }
    TS0(4);
#pragma unroll
    for (int i = 0; i < 3; i++) stg128_if(xout + i * G * THREADS, stage4[(tid ^ ((tid >> 3) & 7)) + i * THREADS], tid + i * THREADS < G * 8);
    __syncthreads();
#pragma unroll
    for (int i = -2; i < 2; i++) {
        const int c = tid + i * THREADS;
        const uint32_t x = c < (SN_OFF - STAGE_OFF) / 16 ? 0u : 0xFFFFFFFFu;
        if (c >= (SREC_OFF - STAGE_OFF) / 16) stage4[c] = make_uint4(x, x, x, x);
    }
    uint32_t key[4] = {0, 0, 0, 0};
    uint2 pr[4];
    const uint32_t gp = sb + RING_OFF + 2048 + (warp < 4 * NWG ? warp * 12288 : (warp & 3) * 12288 + 2048) + lane * 16;
    uint32_t pk = 0;
    if (warp == 15) {
        if (lane == 0) {
            int o = TOUCH * 8192;
#pragma unroll 1
            while (o < nn * 512 && !mbar_test(sb + BAR_OFF + 8, 0)) {
                const uint32_t bar = sb + BAR_OFF + 16 + 8 * (pk % FLIGHT);
                if (!mbar_test(bar, ~(pk / FLIGHT) & 1)) continue;
                const int n = min(4096, nn * 512 - o);
                mbar_expect_tx(bar, n);
                bulk_g2s(sb + DUMMY_OFF, own + o, n, bar);
                o += n;
                pk++;
            }
            misc[3] = pk;
        }
        __syncwarp();
    } else {
    __nanosleep(PDELAY);
    TS0(5);

    {
        const int LPW = (G + 14) / 15;
        uint32_t ew[3][4], bad[3];
        const uint4* cp = p.g->xbuf + (b * G + warp * LPW) * 8 + lane;
#pragma unroll
        for (int i = 0; i < 3; i++) {
            bad[i] = lane + 32 * i < min(LPW, G - warp * LPW) * 8;
            ew[i][0] = ew[i][1] = ew[i][2] = ew[i][3] = (PAY_INVALID << 6) | tag;
        }
        int it = 0;
#pragma unroll 1
        do {
#pragma unroll
            for (int i = 0; i < 3; i++)
                asm volatile("{\n.reg .pred p;\nsetp.ne.u32 p, %5, 0;\n@p ld.relaxed.gpu.global.v4.u32 {%0,%1,%2,%3}, [%4];\n}\n"
                             : "+r"(ew[i][0]), "+r"(ew[i][1]), "+r"(ew[i][2]), "+r"(ew[i][3]) : "l"(cp + 32 * i), "r"(bad[i]) : "memory");
#pragma unroll
            for (int i = 0; i < 3; i++) bad[i] = ((ew[i][0] ^ tag) | (ew[i][1] ^ tag) | (ew[i][2] ^ tag) | (ew[i][3] ^ tag)) & 63u;
            if (++it > (1 << 22)) __trap();
        } while (__any_sync(0xffffffffu, bad[0] | bad[1] | bad[2]));
        TSX(21, 0); TSX(22, 448);
        uint4* pack = reinterpret_cast<uint4*>(smem + PACK_OFF);
        int nch = 0;
        uint32_t at[3];
#pragma unroll
        for (int i = 0; i < 3; i++) {
            const uint32_t m = __ballot_sync(0xffffffffu, ew[i][0] < (PAY_MARK << 6));
            at[i] = nch + __popc(m & ((1u << lane) - 1));
            nch += __popc(m);
        }
        if (__builtin_expect(nch > 32, 0)) {
#pragma unroll 1
            for (int i = 0; i < 3; i++) {
                if (ew[0][0] < (PAY_MARK << 6) && at[0] >= 32) at[0] = (15 - warp) * 32 - 1 - min(atomicAdd(&misc[1], 1u), 31u);
                const uint32_t x = at[0], y = ew[0][0];
                at[0] = at[1]; at[1] = at[2]; at[2] = x;
                ew[0][0] = ew[1][0]; ew[1][0] = ew[2][0]; ew[2][0] = y;
            }
        }
#pragma unroll
        for (int i = 0; i < 3; i++) {
            asm volatile("{\n.reg .pred p;\nsetp.lt.u32 p, %1, %5;\n@p st.shared.v4.u32 [%0], {%1,%2,%3,%4};\n}\n"
                         ::"r"(sb + PACK_OFF + (warp * 32 + at[i]) * 16), "r"(ew[i][0]), "r"(ew[i][1]), "r"(ew[i][2]), "r"(ew[i][3]), "n"(PAY_MARK << 6) : "memory");
            sts32_if(sb + MISC_OFF + 4 * 17, 1, (ew[i][3] >> 6) == PAY_MARK);
        }
        bool have = lane < nch;
        if (warp == 14) {
            asm volatile("bar.sync 7, 480;" ::: "memory");
            const uint32_t extra = misc[1];
            if (nch + extra > 32) misc[18] = 1;
            have = have || lane + extra >= 32;
        } else {
            asm volatile("bar.arrive 7, 480;" ::: "memory");
        }
        __syncwarp();
        uint32_t w[4], rk[4];
        bool in[4];
        {
            const uint4 x = pack[tid];
            w[0] = have ? x.x : ~0u; w[1] = have ? x.y : ~0u; w[2] = have ? x.z : ~0u; w[3] = have ? x.w : ~0u;
        }
        auto fetch = [&](int j, bool c) {
            asm volatile("{\n.reg .pred p;\nsetp.ne.u32 p, %2, 0;\n@p cp.async.cg.shared.global [%0], [%1], 16;\n}\n"
                         ::"r"(gp + j * 512), "l"(reinterpret_cast<const uint4*>(p.g->pos8) + ((w[j] >> 16) & 0x7FFFu)), "r"((uint32_t)c) : "memory");
        };
#pragma unroll
        for (int j = 0; j < 4; j++) fetch(j, (int)w[j] < (int)(PAY_MARK << 6));
#pragma unroll
        for (int j = 0; j < 4; j++) pr[j] = reinterpret_cast<const uint2*>(smem + OPOS_OFF)[(w[j] >> 6) & 511u];
        uint32_t ca[4];
#pragma unroll
        for (int j = 0; j < 4; j++) {
            key[j] = ((w[j] >> 15) & 0xFFFFu) | ((w[j] << 10) & 0x1FF0000u);
            ca[j] = sb + NCNT_OFF + ((w[j] >> 4) & 0x7FCu);
            asm volatile("" : "+r"(key[j]), "+r"(ca[j]));
        }
        asm volatile("{\n.reg .pred p;\nsetp.eq.u32 p, %0, -1;\n@p trap;\n}" ::"r"(nch) : "memory");
        asm volatile("cp.async.wait_all;" ::: "memory");
        TSX(23, 0); TSX(24, 448);
        asm volatile("{\n.reg .pred p;\nsetp.eq.u32 p, %1, 0;\n@p mbarrier.arrive.shared::cta.b64 _, [%0];\n}\n" ::"r"(sb + BAR_OFF + 8), "r"(lane) : "memory");
#pragma unroll
        for (int j = 0; j < 4; j++) {
            uint2 ps;
            asm volatile("ld.shared.v2.u32 {%0,%1}, [%2];" : "=r"(ps.x), "=r"(ps.y) : "r"(gp + j * 512 + ((w[j] >> 12) & 8)) : "memory");
            in[j] = ((int)w[j] >= 0) | (((int)w[j] < (int)(PAY_MARK << 6)) & inside(hsub2(ps.x, pr[j].x), hsub2(ps.y, pr[j].y)));
        }
#pragma unroll
        for (int j = 0; j < 4; j++)
            asm volatile("atom.shared.add.u32 %0, [%1], 1;" : "=r"(rk[j]) : "r"(in[j] ? ca[j] : sb + NCNT_OFF + 4 * (480 + lane)) : "memory");
#pragma unroll
        for (int j = 0; j < 4; j++) {
            rk[j] = rk[j] < SPL ? 2 * rk[j] : min(2 * rk[j] - (2 * SPL - 1), 126u);
            asm volatile("red.shared.add.u32 [%0 + %1], 1;" ::"r"(rk[j] & 2 ? 124u : rk[j] & 60u), "n"(SB + MISC_OFF + 128) : "memory");
            key[j] += rk[j] << 25;
        }
#pragma unroll
        for (int j = 0; j < 4; j++) fetch(j, (int)w[j] >= 0);
        cp_commit();
    }
    }
    __syncthreads();
    TS0(6);
    uint32_t deg[5];
    deg[4] = lds32(sb + NCNT_OFF + 4 * tid);
#pragma unroll
    for (int j = 0; j < 4; j++) deg[j] = lds32(sb + NCNT_OFF + ((key[j] >> 14) & 0x7FCu));
    if (tid == THREADS - 33) {
        if (b == 0) p.g->sync[0] = epoch + 1;
        asm volatile("fence.proxy.async.global;" ::: "memory");
        mbar_expect_tx(bar_tab, RING_OFF);
        bulk_g2s(sb, p.g->wimg, RING_OFF, bar_tab);
    }
    __syncwarp();
    uint32_t dst = sb + RING_OFF + warp * 12288 + (lane >> 3) * 256 + (((lane & 7) ^ (lane >> 3)) << 4), l7 = (lane & 7) * 16, g32 = (lane >> 2) * 32;
    uint32_t e0, e1, n0, n1;
    auto sources = [&](uint32_t c) {
        asm volatile("{\n.reg .b32 a;\nlop3.b32 a, %4, %5, 0xFFC0, 0xA8;\nshr.u32 a, a, 2;\nld.shared.v4.u32 {%0,%1,%2,%3}, [a + %6];\n}\n"
                     : "=r"(e0), "=r"(n0), "=r"(e1), "=r"(n1) : "r"(c), "r"(g32), "n"(SB + SN_OFF));
    };
    auto load_s = [&](auto pad) {
        gather<1, 0, pad.value>(dst, p.sv, l7, e0); gather<1, 1, pad.value>(dst + 1024, p.sv, l7, e0);
        gather<1, 0, pad.value>((dst ^ 64) + 128, p.sv, l7, e1); gather<1, 1, pad.value>((dst ^ 64) + 1152, p.sv, l7, e1);
    };
    auto load_o = [&]() {
        gather<4, 0>(dst + 8192, p.sv, l7, n0); gather<4, 0>((dst ^ 64) + 8320, p.sv, l7, n1);
    };
    auto load_v = [&](auto pad) {
        gather<3, 0, pad.value>(dst + 2048, p.sv, l7, e0); gather<3, 1, pad.value>(dst + 5120, p.sv, l7, e0);
        gather<3, 0, pad.value>((dst ^ 64) + 2176, p.sv, l7, e1); gather<3, 1, pad.value>((dst ^ 64) + 5248, p.sv, l7, e1);
        cp_commit();
    };
    const int ng = (misc[32] + 7) >> 3;
    const int give = max(min(ng - max((int)(misc[33] + 7) >> 3, 4 * NWG), GIVE), 0);
    if (warp == 15) {
        const uint32_t cnt = lane < 16 ? (misc[32 + lane] + 7) >> 3 : 0u;
        uint32_t z = cnt;
#pragma unroll
        for (int o = 1; o < 16; o <<= 1) {
            const uint32_t y = __shfl_up_sync(0xffffffffu, z, o);
            if (lane >= o) z += y;
        }
        misc[96 + lane] = lane < 16 ? 64 * (z - cnt) : 64 * (MAXROW + 1);
        asm volatile("bar.arrive 5, 512;" ::: "memory");
        if (lane == 15) {
            const bool cold = cnt || z > MAXROW || misc[31 + SPL / 2] > 32 || misc[17] || misc[18];
            misc[18] = cold;
            asm volatile("st.relaxed.gpu.global.u32 [%0], %1;" ::"l"(p.g->rows + b), "r"(~epoch << 16 | (cold || ng < 4 * NWG ? 255 : give << 8 | z)) : "memory");
        }
        pk = (z - cnt) << 8 | __shfl_down_sync(0xffffffffu, cnt, 1) << 24;
    } else {
        if (warp * 32 < nn) {
            const uint32_t c = deg[4], st = tid < nn ? (min(c, (uint32_t)SPL) + 1) >> 1 : 17u;
            const uint32_t same = __match_any_sync(0xffffffffu, st), first = __ffs(same) - 1;
            uint32_t r, node = nbase + tid;
            asm volatile("atom.shared.add.u32 %0, [%1], %2;" : "=r"(r)
                         : "r"(lane == first ? sb + MISC_OFF + 4 * (64 + st) : sb + NCNT_OFF + 4 * (480 + lane)), "r"(__popc(same)) : "memory");
            r = __shfl_sync(0xffffffffu, r, first) + __popc(same & ((1u << lane) - 1)) + misc[32 + st];
            if (__builtin_expect(c > SPL, 0)) {
                const uint32_t s2 = min((c - SPL + 1) >> 1, 16u), r2 = misc[32 + s2] + atomicAdd(&misc[64 + s2], 1u), k = atomicAdd(&misc[2], 1u);
                reinterpret_cast<uint32_t*>(smem + SCNT_OFF)[k & 31] = node;
                node |= NODE_SPLIT;
                ncnt[1024 + tid] = 8 * r2;
                reinterpret_cast<uint32_t*>(smem + SN_OFF)[(r2 & 511) * 2 + 1] = node;
            }
            if (tid < nn) {
                ncnt[512 + tid] = 8 * r;
                reinterpret_cast<uint32_t*>(smem + SN_OFF)[(r & 511) * 2 + 1] = node;
            }
        }
#pragma unroll
        for (int j = 0; j < 4; j++) {
            const uint32_t c = deg[j];
            asm volatile("{\n.reg .pred p;\n.reg .b64 a;\nsetp.ge.u32 p, %0, %3;\nsetp.lt.and.u32 p, %1, 0x8000000, p;\nmad.wide.u32 a, %4, 512, %2;\n@p prefetch.global.L2 [a];\n"
                         "}\n" ::"r"(c), "r"(key[j]), "l"(p.sv), "n"(BIG), "r"(key[j] & 0xFFFFu) : "memory");
        }
        asm volatile("bar.sync 5, 512;" ::: "memory");
        uint32_t slot[4];
#pragma unroll
        for (int j = 0; j < 4; j++) slot[j] = min(misc[96 + (key[j] >> 27)] + (ncnt[512 + ((key[j] >> 16) & 1023)] & 0xFFF8u), 64u * (MAXROW + 1)) + ((key[j] >> 25) & 2);
#pragma unroll
        for (int j = 0; j < 4; j++) {
            *reinterpret_cast<uint16_t*>(smem + SN_OFF + slot[j]) = (uint16_t)key[j];
            slot[j] += slot[j] & 2;
        }
        asm volatile("bar.sync 6, 480;" ::: "memory");
        TS0(7);
        if (warp < 4 * NWG) {
            sources((warp < ng ? warp : MAXROW) << 8);
            e0 = __vminu2(e0, (N - 1) * 0x10001u);
            e1 = __vminu2(e1, (N - 1) * 0x10001u);
            load_s(IntC<0>{});
            cp_commit();
            load_o();
            cp_commit();
            asm volatile("cp.async.wait_group 2;" ::: "memory");
        } else {
            asm volatile("cp.async.wait_all;" ::: "memory");
        }
        uint2 ps[4];
#pragma unroll
        for (int j = 0; j < 4; j++)
            asm volatile("ld.shared.v2.u32 {%0,%1}, [%2];" : "=r"(ps[j].x), "=r"(ps[j].y) : "r"(gp + j * 512 + (key[j] & 1) * 8) : "memory");
        TSX(9, 0);
#pragma unroll 1
        for (int i = 0; i < 2; i++) {
#pragma unroll
            for (int u = 0; u < 2; u++) {
                const uint3 geo = geometry(hsub2(ps[u].x, pr[u].x), hsub2(ps[u].y, pr[u].y));
                *reinterpret_cast<uint2*>(smem + SREC_OFF + 2 * slot[u]) = make_uint2(geo.x, geo.y);
                *reinterpret_cast<uint32_t*>(smem + SD_OFF + slot[u]) = geo.z;
                ps[u] = ps[u + 2];
                pr[u] = pr[u + 2];
                slot[u] = slot[u + 2];
            }
        }
    }
    if (warp == 15) { __syncwarp(); asm volatile("bar.arrive 4, 512;" ::: "memory"); }
    else asm volatile("bar.sync 4, 512;" ::: "memory");
    TS0(8);
    auto drain = [&](int i) { if (i < FLIGHT) mbar_wait(sb + BAR_OFF + 16 + 8 * i, ~((misc[3] + FLIGHT - 1 - i) / FLIGHT) & 1); };
    if (__builtin_expect(misc[18], 0)) {
        drain(warp);
        asm volatile("cp.async.wait_all;" ::: "memory");
        __syncthreads();
        cold_messages(smem, p, nn);
        mbar_wait(bar_tab, 1);
        return;
    }

    if (warp < 4 * NWG) {
        asm volatile("setmaxnreg.inc.sync.aligned.u32 %0;" ::"n"(REG_C));
        const int lane = fresh_lane();
        const int g = lane >> 2, q = lane & 3;
        const uint64_t dW1 = p.desc0, dW2 = dW1 + (W2_OFF >> 4), dWR = dW1 + (WR_OFF >> 4);
        const uint32_t ring = sb + RING_OFF + warp * 12288;
        const uint32_t vrow = pin(ring + g * 128 + ((q ^ ((g & 1) << 2) ^ (g >> 1)) << 4));
        const uint32_t mrow = pin(ring + (lane & 15) * 128 + (((lane >> 4) ^ ((lane & 1) << 2) ^ ((lane & 7) >> 1)) << 4));
        dst = pin(ring + (lane >> 3) * 256 + (((lane & 7) ^ (lane >> 3)) << 4)); l7 = pin((lane & 7) * 16); g32 = pin(g * 32);
        uint32_t ctl = sb + CTL_OFF + warp * 4;
        auto control = [&](uint32_t c, uint32_t at) {
            int it = 0;
#pragma unroll 1
            while (__builtin_expect(c == 0xFFFFFFFFu, 0)) {
                asm volatile("ld.volatile.shared.u32 %0, [%1];" : "=r"(c) : "r"(at) : "memory");
                c = __reduce_or_sync(0xffffffffu, c);
                if (++it > (1 << 24)) __trap();
            }
            return c;
        };
        uint32_t c0 = control(0xFFFFFFFFu, ctl), c1 = control(0xFFFFFFFFu, ctl + 64);
        if (warp >= 8) asm volatile("bar.arrive 1, 256;" ::: "memory");
        uint32_t acc[32];
        float P[32], W[32];
#pragma unroll
        for (int i = 0; i < 32; i++) { acc[i] = 0; P[i] = W[i] = 0.f; }
        mbar_wait(bar_tab, 1);
        sources(c0);
        e0 = __vminu2(e0, (N - 1) * 0x10001u);
        e1 = __vminu2(e1, (N - 1) * 0x10001u);
        if (warp >= 8) asm volatile("cp.async.wait_all;" ::: "memory");
        else if (warp >= 4) cp_wait1();
        load_v(IntC<0>{});
        auto finish = [&](uint32_t c, uint32_t node) {
            if (c & ST_CLOSE) {
                uint64_t op[2];
                asm("{\n.reg .b32 a;\nmad.lo.u32 a, %2, 512, %3;\nmad.wide.u32 %0, a, 1, %4;\nxor.b32 a, a, 64;\nmad.wide.u32 %1, a, 1, %4;\n}\n"
                    : "=l"(op[0]), "=l"(op[1]) : "r"(node), "r"(l7), "l"(p.out));
#pragma unroll
                for (int k = 0; k < 8; k++) {
                    uint32_t x[4];
#pragma unroll
                    for (int i = 0; i < 4; i++) x[i] = l7 & 64 ? acc[4 * (k ^ 1) + i] : acc[4 * k + i];
                    asm volatile("{\n.reg .pred p;\nsetp.lt.u32 p, %5, %6;\n@p st.global.cs.v4.u32 [%0], {%1,%2,%3,%4};\n}\n"
                                 ::"l"(op[k & 1] + 128 * (k >> 1)), "r"(x[0]), "r"(x[1]), "r"(x[2]), "r"(x[3]), "r"(node), "n"(NODE_SPLIT) : "memory");
                }
                if (__builtin_expect(__any_sync(0xffffffffu, (int)node >= (int)NODE_SPLIT), 0)) {
                    mbar_wait(sb + BAR_OFF + 16 + 8 * FLIGHT, 0);
                    if ((int)node >= (int)NODE_SPLIT) {
#pragma unroll
                        for (int k = 0; k < 8; k++)
                            asm volatile("red.global.add.noftz.v4.bf16x2 [%0], {%1,%2,%3,%4};" ::"l"((op[0] & ~64ull) + 64 * k), "r"(acc[4 * k]), "r"(acc[4 * k + 1]), "r"(acc[4 * k + 2]), "r"(acc[4 * k + 3]) : "memory");
                    }
                    __syncwarp();
                }
            }
        };
#pragma unroll 1
        while ((int)c0 >= 0) {
            uint32_t a[16], h[16], rf[4], rr[4], m[16];
            TRW(ctl);
            uint32_t dd[2], f01, f23;
            asm volatile("ld.shared.v2.u32 {%0,%1}, [%2 + %3];" : "=r"(dd[0]), "=r"(dd[1]) : "r"(((c0 & 0xFF00) | g32) >> 2), "n"(SB + SD_OFF));
            asm volatile("ld.shared.v2.u32 {%0,%1}, [%2 + %3];" : "=r"(f01), "=r"(f23) : "r"(l7), "n"(SB + FREQ_OFF));
            sources(c1);
            asm volatile("cp.async.wait_group 2;" ::: "memory");
            __syncwarp();
#pragma unroll
            for (int i = 0; i < 4; i++) ldsm4(mrow ^ (i << 5), a + 4 * i);
            wg_fence();
            wgmma_k64(P, a, dW1);
            wg_commit();
            SPLIT(1);
#pragma unroll
            for (int hh = 0; hh < 2; hh++) {
                const float sc = bf_hi(dd[hh]);
                const uint32_t x01 = hmul2_lo(f01, dd[hh]), x23 = hmul2_lo(f23, dd[hh]);
                rf[hh] = pack2(__sinf(bf_lo(x01)) * sc, __sinf(bf_hi(x01)) * sc);
                rf[2 + hh] = pack2(__sinf(bf_lo(x23)) * sc, __sinf(bf_hi(x23)) * sc);
            }
            asm volatile("" : "+r"(rf[0]), "+r"(rf[1]), "+r"(rf[2]), "+r"(rf[3]));
            asm volatile("bar.sync %0, 256;" ::"r"(1 + (warp >> 2)) : "memory");
            SPLIT(2);
            wg_wait<0>();
            fence_regs(P);
#pragma unroll
            for (int i = 0; i < 16; i++)
                h[i] = pack2(fmaf(P[2 * i], tanh_fast(P[2 * i]), P[2 * i]), fmaf(P[2 * i + 1], tanh_fast(P[2 * i + 1]), P[2 * i + 1]));
            wg_fence();
            wgmma_k64(P, h, dW2 + 1024);
            wgmma_first(W, rf, dWR + 256);
            wg_commit();
            asm volatile("bar.arrive %0, 256;" ::"r"((c0 >> 4) & 3) : "memory");
            SPLIT(3);
            cp_wait1();
            __syncwarp();
#pragma unroll
            for (int k = 0; k < 4; k++) lds2_if(vrow + 8192 + 1024 * k, (vrow ^ 64) + 8192 + 1024 * k, acc + 8 * k, c0 & ST_START);
            lds128(sb + SREC_OFF + (((c0 & 0xFF00) | g32) >> 1), rr);
            uint32_t c2 = lds32(ctl + 128);
            __syncwarp();
            load_s(IntC<1>{});
            cp_commit();
            if (c1 & ST_START) load_o();
            cp_commit();
            wg_wait<0>();
            fence_regs(P); fence_regs(W);
#pragma unroll
            for (int j = 0; j < 8; j++) {
                m[j] = pack2(P[4 * j] * W[4 * j], P[4 * j + 1] * W[4 * j + 1]);
                m[8 + j] = pack2(P[4 * j + 2] * W[4 * j + 2], P[4 * j + 3] * W[4 * j + 3]);
            }
            wg_fence();
            wgmma_k64(P, h, dW2);
            wgmma_first(W, rf, dWR);
            wg_commit();
            SPLIT(4);
            PIN8(m); PIN8(m + 8);
            c2 = __reduce_or_sync(0xffffffffu, c2);
#pragma unroll
            for (int k = 1; k < 4; k++)
#pragma unroll
                for (int j = 0; j < 8; j++) {
                    const uint32_t x = k == 1 ? hfma2_lo(m[j], rr[0], acc[8 * k + j]) : k == 2 ? hfma2_hi(m[j], rr[0], acc[8 * k + j]) : hfma2_lo(m[j], rr[1], acc[8 * k + j]);
                    acc[8 * k + j] = k == 1 ? hfma2_lo(m[8 + j], rr[2], x) : k == 2 ? hfma2_hi(m[8 + j], rr[2], x) : hfma2_lo(m[8 + j], rr[3], x);
                }
            PIN8(acc + 8); PIN8(acc + 16); PIN8(acc + 24);
            c2 = control(c2, ctl + 128);
            wg_wait<0>();
            fence_regs(P); fence_regs(W);
#pragma unroll
            for (int j = 0; j < 8; j++)
                acc[j] = hadd2(acc[j], pack2(fmaf(P[4 * j], W[4 * j], P[4 * j + 2] * W[4 * j + 2]), fmaf(P[4 * j + 1], W[4 * j + 1], P[4 * j + 3] * W[4 * j + 3])));
            wg_fence();
            wgmma_k64(P, h, dW2 + 512);
            wgmma_first(W, rf, dWR + 128);
            wg_commit();
            SPLIT(6);
            asm volatile("cp.async.wait_group 2;" ::: "memory");
            __syncwarp();
            uint32_t v[4][16];
#pragma unroll
            for (int i = 0; i < NPRE; i++) lds128((vrow ^ (64 * (i & 1))) + 2048 + 1024 * (i >> 2) + 3072 * ((i >> 1) & 1), v[1 + (i >> 2)] + 4 * (i & 3));
            wg_wait<0>();
            fence_regs(P); fence_regs(W);
#pragma unroll
            for (int j = 0; j < 8; j++) {
                m[j] = pack2(P[4 * j] * W[4 * j], P[4 * j + 1] * W[4 * j + 1]);
                m[8 + j] = pack2(P[4 * j + 2] * W[4 * j + 2], P[4 * j + 3] * W[4 * j + 3]);
            }
#pragma unroll
            for (int i = NPRE; i < 12; i++) lds128((vrow ^ (64 * (i & 1))) + 2048 + 1024 * (i >> 2) + 3072 * ((i >> 1) & 1), v[1 + (i >> 2)] + 4 * (i & 3));
            sources(c1);
            const uint32_t node = lds32(sb + SN_OFF + 4 + (((c0 >> 16) | g32) >> 2));
            __syncwarp();
            load_v(IntC<1>{});
#pragma unroll
            for (int k = 1; k < 4; k++)
#pragma unroll
                for (int j = 0; j < 8; j++) acc[8 * k + j] = hfma2(m[8 + j], v[k][8 + j], hfma2(m[j], v[k][j], acc[8 * k + j]));
            finish(c0, node);
            ctl += 64;
            c0 = c1;
            c1 = c2;
        }
        asm volatile("cp.async.wait_all;" ::: "memory");
        TRW(ctl);
        TSX(11, 0); TSX(12, 128); TSX(13, 256);
    } else {
        asm volatile("setmaxnreg.dec.sync.aligned.u32 %0;" ::"n"(REG_H));
        const int lane = fresh_lane();
        const uint32_t chunk = sb + (lane & 8 ? (lane & 4 ? SN_OFF : SD_OFF) + (lane & 3) * 16 : SREC_OFF + (lane & 7) * 16), pitch = lane & 8 ? 64 : 128;
        if (warp == 12) {
#pragma unroll 1
            for (int i = 0; i < (int)misc[2]; i++) {
                const uint32_t n = reinterpret_cast<const uint32_t*>(smem + SCNT_OFF)[i] * 32 + lane;
                reinterpret_cast<uint4*>(p.out)[n] = reinterpret_cast<const uint4*>(p.sv)[n];
            }
#pragma unroll 1
            for (int i = lane >> 4; i < give; i += 2) {
                uint32_t x[4];
                lds128(chunk + (ng - 1 - i) * pitch, x);
                p.g->pool[(b * GIVE + i) * 16 + (lane & 15)] = make_uint4(x[0], x[1], x[2], x[3]);
            }
            __threadfence();
            __syncwarp();
            if (lane == 0) {
                asm volatile("st.relaxed.gpu.global.u32 [%0], %1;" ::"l"(p.g->ready + b), "r"(~epoch) : "memory");
                mbar_arrive(sb + BAR_OFF + 16 + 8 * FLIGHT);
            }
        }
        if (warp == 15) {
            int k = lane < 4 * NWG ? lane : 255, next = 4 * NWG, j = 0, mine = ng - give, end = -1, take = 0;
            uint32_t busy, at = sb + CTL_OFF + 4 * lane, from = 0;
#pragma unroll 1
            do {
                if (next > mine && end < 0) {
                    end = mine = ng;
                    const int peer = b % 5 + 5 * lane;
                    uint32_t x = 255;
                    int it = 0;
                    if (peer < G) {
#pragma unroll 1
                        do {
                            asm volatile("ld.relaxed.gpu.global.u32 %0, [%1];" : "=r"(x) : "l"(p.g->rows + peer) : "memory");
                            if (++it > (1 << 22)) __trap();
                        } while ((x >> 16) != (~epoch & 0xFFFFu));
                    }
                    const int r = x & 255, n = __popc(__ballot_sync(0xffffffffu, r != 255));
                    const int level = min(((__reduce_add_sync(0xffffffffu, r != 255 ? r : 0) + n - 1) / max(n, 1) + 3) & ~3, MAXROW);
                    const uint32_t ed = r > level ? min(r - level, (int)(x >> 8) & 255) : min(level - r, ROOM) << 16;
                    uint32_t z = ed;
#pragma unroll
                    for (int o = 1; o < 32; o <<= 1) {
                        const uint32_t y = __shfl_up_sync(0xffffffffu, z, o);
                        if (lane >= o) z += y;
                    }
                    const uint32_t all = __shfl_sync(0xffffffffu, z, 31), moved = min(all & 0xFFFFu, all >> 16);
                    const uint32_t me = __shfl_sync(0xffffffffu, ed, b / 5), mz = __shfl_sync(0xffffffffu, z, b / 5) - me;
                    end = mine = ng - (min((mz + me) & 0xFFFFu, moved) - min(mz & 0xFFFFu, moved));
#pragma unroll 1
                    for (uint32_t u = mz >> 16; u < min((mz + me) >> 16, moved); u++, take++) {
                        const int f = __popc(__ballot_sync(0xffffffffu, (z & 0xFFFFu) <= u));
                        const uint32_t q = u - (__shfl_sync(0xffffffffu, z - ed, f) & 0xFFFFu);
                        if (lane == take) from = (b % 5 + 5 * f) << 8 | q;
                    }
                }
                if (next > mine && take) {
                    if (lane < take) {
                        uint32_t x;
                        int it = 0;
#pragma unroll 1
                        do {
                            asm volatile("ld.acquire.gpu.global.u32 %0, [%1];" : "=r"(x) : "l"(p.g->ready + (from >> 8)) : "memory");
                            if (++it > (1 << 22)) __trap();
                        } while (x != ~epoch);
                    }
                    __syncwarp();
#pragma unroll 1
                    for (end += take; take--;) {
                        const uint32_t f = __shfl_sync(0xffffffffu, from, take);
                        if (lane < 16)
                            asm volatile("cp.async.cg.shared.global [%0], [%1], 16;" ::"r"(chunk + (MAXROW - 1 - take) * pitch),
                                         "l"(p.g->pool + ((f >> 8) * GIVE + (f & 255)) * 16 + lane) : "memory");
                    }
                    take = 0;
                    asm volatile("cp.async.wait_all;" ::: "memory");
                    __threadfence_block();
                    __syncwarp();
                }
                const bool has = k < (end < 0 ? mine : end);
                const uint32_t i = k < mine ? k : MAXROW - 1 + mine - k, x = __shfl_sync(0xffffffffu, pk, j);
                const bool close = has && i >= (x >> 24);
                busy = __ballot_sync(0xffffffffu, has);
                const uint32_t m = __ballot_sync(0xffffffffu, close);
                uint32_t c = has ? ((x & 0xFF00) + i * 0x1000100) | (j ? 0u : ST_START) | (close ? ST_CLOSE : 0u) : MAXROW * 256;
                if (!(busy >> (lane & 12))) c |= 0x80000000u;
                c |= busy >> ((lane & 12) + 4) ? (lane & 12) * 4 + 32 : 16;
                sts32_if(at, c, lane < 16 || !busy);
                j = close ? 0 : j + 1;
                k = close ? next + __popc(m & ((1u << lane) - 1)) : k;
                next += __popc(m);
                at += 64;
            } while (busy);
        }
        if (warp == 15) mbar_wait(sb + BAR_OFF + 16 + 8 * FLIGHT, 0);
        else if (warp != 12) __nanosleep(ZDELAY);
        const int zend = misc[32] + misc[64];
#pragma unroll 1
        for (;;) {
            int r = 0;
            if (lane == 0) r = atomicAdd(&misc[4], 4u);
            r = __shfl_sync(0xffffffffu, r, 0) + 8 * ng;
            if (r >= zend) break;
            uint4 v[4];
            uint32_t n[4];
#pragma unroll
            for (int i = 0; i < 4; i++) {
                n[i] = reinterpret_cast<const uint32_t*>(smem + SN_OFF)[min(r + i, zend - 1) * 2 + 1] * 32 + lane;
                v[i] = __ldcs(reinterpret_cast<const uint4*>(p.sv) + n[i]);
            }
#pragma unroll
            for (int i = 0; i < 4; i++)
                if (r + i < zend) __stcs(reinterpret_cast<uint4*>(p.out) + n[i], v[i]);
        }
        static_assert(FLIGHT <= 4, "drain");
        drain(warp & 3);
        asm volatile("cp.async.wait_all;" ::: "memory");
        TSX(14, 384); TSX(15, 480); TSX(16, 416);
    }
}

}

extern "C" void kernel_launch(void* const* d_in, const int* in_sizes, int n_in, void* d_out, int out_size) {
    static int s_G = 0;
    static void* s_scratch = nullptr;
    const int N = in_sizes[0] / 256, E = in_sizes[2];
    if (s_G == 0) {
        cudaFuncSetAttribute(painn_kernel<0, 0, 0>, cudaFuncAttributeMaxDynamicSharedMemorySize, SMEM_BYTES);
        cudaFuncSetAttribute(painn_kernel<50000, 800000, 132>, cudaFuncAttributeMaxDynamicSharedMemorySize, SMEM_BYTES);
        int dev = 0, sms = 0, occ = 0;
        cudaGetDevice(&dev);
        cudaDeviceGetAttribute(&sms, cudaDevAttrMultiProcessorCount, dev);
        cudaOccupancyMaxActiveBlocksPerMultiprocessor(&occ, painn_kernel<0, 0, 0>, THREADS, SMEM_BYTES);
        cudaGetSymbolAddress(&s_scratch, g_scratch);
        s_G = occ >= 1 ? (sms < MAXG ? sms : MAXG) : 0;
    }
    if (s_G == 0 || N > TABLE_MAXN || N > s_G * MAXNPC || (s_G - 1) * ((N + s_G - 1) / s_G) >= N || E > MAXE || E < 4 * MAXG * MAXG) return;
    Params p;
    p.g = (Scratch*)s_scratch;
    p.sv = (const __nv_bfloat16*)d_in[0];
    p.pos = (const __nv_bfloat16*)d_in[1];
    p.src = (const int*)d_in[2];
    p.dst = (const int*)d_in[3];
    p.freqs = (const __nv_bfloat16*)d_in[4];
    p.w1 = (const __nv_bfloat16*)d_in[5];
    p.w2 = (const __nv_bfloat16*)d_in[6];
    p.wr = (const __nv_bfloat16*)d_in[7];
    p.out = (__nv_bfloat16*)d_out;
    p.desc0 = (uint64_t)(SB >> 4) | ((uint64_t)1 << 16) | ((uint64_t)64 << 32) | ((uint64_t)1 << 62);
    p.N = N; p.E = E; p.G = s_G;
    p.NPC = (N + s_G - 1) / s_G;
    p.magic = (uint32_t)(((1ull << 32) + p.NPC - 1) / p.NPC);
    p.gpc = ((E >> 2) + s_G - 1) / s_G;
    p.odd_edges = (E & 3) != 0 || p.gpc > 3 * THREADS;
    if (N == 50000 && E == 800000 && s_G == 132) painn_kernel<50000, 800000, 132><<<s_G, THREADS, SMEM_BYTES, cudaStreamPerThread>>>(p);
    else painn_kernel<0, 0, 0><<<s_G, THREADS, SMEM_BYTES, cudaStreamPerThread>>>(p);
}
```

```cpp
#include <cuda_runtime.h>
#include <cuda_bf16.h>
#include <stdint.h>

namespace {

constexpr int NWG = 3;
constexpr int REG_C = 160, REG_H = 32;
constexpr int SPL = 10;
constexpr int GIVE = 10, ROOM = 4;
constexpr int BIG = 5;
constexpr int CUT = 7;
constexpr int HDELAY = 150;
constexpr int TOUCH = 4, FLIGHT = 4;
constexpr int NPRE = 5;
constexpr int PDELAY = 150;
constexpr int ZDELAY = 1200;
constexpr int THREADS = 512;
constexpr int MAXG = 136;
constexpr int MAXROW = 96;
constexpr int TMAX = MAXROW / 12 + 18;
constexpr int MAXNPC = 480;
constexpr int MAXE = 1 << 20;

constexpr int W2_OFF = 8192;
constexpr int WR_OFF = 32768;
constexpr int RING_OFF = 38912;
constexpr int SREC_OFF = RING_OFF + 4 * NWG * 12288;
constexpr int SD_OFF = SREC_OFF + (MAXROW + 1) * 128 + 16;
constexpr int SN_OFF = SD_OFF + (MAXROW + 1) * 64 + 16;
constexpr int CTL_OFF = SN_OFF + (MAXROW + 1) * 64 + 16;
constexpr int TABLE_MAXN = 50176;
constexpr int STAGE_OFF = TABLE_MAXN * 4;
constexpr int SCNT_OFF = STAGE_OFF + MAXG * 128;
constexpr int PACK_OFF = RING_OFF + 6144;
constexpr int NCNT_OFF = SCNT_OFF + 768;
constexpr int OPOS_OFF = NCNT_OFF + 2048;
constexpr int BAR_OFF = OPOS_OFF + 4096;
constexpr int MISC_OFF = BAR_OFF + 128;
constexpr int FREQ_OFF = MISC_OFF + 512;
constexpr int DUMMY_OFF = (FREQ_OFF + 128 + 127) / 128 * 128;
constexpr int SMEM_BYTES = DUMMY_OFF + 4096;
static_assert(CTL_OFF + 64 * TMAX <= STAGE_OFF + 32 * THREADS && STAGE_OFF - SREC_OFF <= 32 * THREADS && 4 * (MAXG + 32) <= 768, "smem map");
static_assert(SMEM_BYTES <= 232448 && BAR_OFF % 8 == 0 && RING_OFF % 128 == 0 && SREC_OFF % 128 == 0 && (MAXG + 14) / 15 <= 12, "smem map");

constexpr uint32_t PAY_INVALID = 0x3FFFFFFu;
constexpr uint32_t PAY_MARK = 0x3FFFDFFu;
constexpr uint32_t NODE_SPLIT = 0x40000000u;
constexpr uint32_t ST_START = 1, ST_CLOSE = 2;
constexpr float QINVP = 9.0f / 510.0f;
constexpr uint32_t QTHRESH = 2209;
constexpr uint32_t QSURE = 1980;

struct Scratch {
    unsigned sync[32];
    uint4 table[TABLE_MAXN / 4];
    uint4 wimg[RING_OFF / 16];
    uint2 pos8[TABLE_MAXN];
    uint4 xbuf[MAXG * MAXG * 8 + 3 * THREADS];
    uint4 pool[MAXG * GIVE * 16];
    unsigned rows[MAXG];
    unsigned ready[MAXG];
    int ovfcnt[MAXG];
    int2 ovf[MAXE + 8 * MAXG + 8];
};
__device__ __align__(128) Scratch g_scratch;

struct Params {
    const __nv_bfloat16* pos;
    Scratch* g;
    const int* src;
    const int* dst;
    int N, NPC, E, gpc;
    const __nv_bfloat16* w2;
    const __nv_bfloat16* wr;
    const __nv_bfloat16* w1;
    const __nv_bfloat16* freqs;
    const __nv_bfloat16* sv;
    __nv_bfloat16* out;
    uint64_t desc0;
    int G;
    uint32_t magic;
    int odd_edges;
};
constexpr uint32_t SB = 1024;

#define TSX(i, thr)
#define TS0(i) TSX(i, 0)
#define TRW(ctl)

__device__ __forceinline__ uint32_t smem_u32(const void* p) { return (uint32_t)__cvta_generic_to_shared(p); }
__device__ __forceinline__ void mbar_init(uint32_t bar, uint32_t cnt) {
    asm volatile("mbarrier.init.shared::cta.b64 [%0], %1;" ::"r"(bar), "r"(cnt) : "memory");
}
__device__ __forceinline__ void mbar_arrive(uint32_t bar) {
    asm volatile("mbarrier.arrive.shared::cta.b64 _, [%0];" ::"r"(bar) : "memory");
}
__device__ __forceinline__ void mbar_expect_tx(uint32_t bar, uint32_t bytes) {
    asm volatile("mbarrier.arrive.expect_tx.shared::cta.b64 _, [%0], %1;" ::"r"(bar), "r"(bytes) : "memory");
}
__device__ __forceinline__ void mbar_wait(uint32_t bar, uint32_t parity) {
    uint32_t ok;
    int it = 0;
    do {
        asm volatile(
            "{\n.reg .pred p;\n"
            "mbarrier.try_wait.parity.shared::cta.b64 p, [%1], %2, 2000;\n"
            "selp.u32 %0, 1, 0, p;\n}\n"
            : "=r"(ok) : "r"(bar), "r"(parity) : "memory");
        if (++it > (1 << 20)) __trap();
    } while (!ok);
}
__device__ __forceinline__ uint32_t mbar_test(uint32_t bar, uint32_t parity) {
    uint32_t ok;
    asm volatile("{\n.reg .pred p;\nmbarrier.test_wait.parity.shared::cta.b64 p, [%1], %2;\nselp.u32 %0, 1, 0, p;\n}\n"
                 : "=r"(ok) : "r"(bar), "r"(parity) : "memory");
    return ok;
}
__device__ __forceinline__ uint32_t pin(uint32_t x) {
    uint32_t r;
    asm volatile("shfl.sync.bfly.b32 %0, %1, 0, 31, -1;" : "=r"(r) : "r"(x));
    return r;
}
__device__ __forceinline__ void bulk_g2s(uint32_t dst, const void* src, uint32_t bytes, uint32_t bar) {
    asm volatile("cp.async.bulk.shared::cluster.global.mbarrier::complete_tx::bytes [%0], [%1], %2, [%3];"
                 ::"r"(dst), "l"(src), "r"(bytes), "r"(bar) : "memory");
}
__device__ __forceinline__ void ldsm4(uint32_t addr, uint32_t* r) {
    asm volatile("ldmatrix.sync.aligned.m8n8.x4.shared.b16 {%0,%1,%2,%3}, [%4];"
                 : "=r"(r[0]), "=r"(r[1]), "=r"(r[2]), "=r"(r[3]) : "r"(addr) : "memory");
}
__device__ __forceinline__ uint32_t pack2(float lo, float hi) {
    uint32_t r;
    asm("cvt.rn.bf16x2.f32 %0, %1, %2;" : "=r"(r) : "f"(hi), "f"(lo));
    return r;
}
__device__ __forceinline__ float bf_lo(uint32_t w) { return __uint_as_float(w << 16); }
__device__ __forceinline__ float bf_hi(uint32_t w) { return __uint_as_float(w & 0xFFFF0000u); }
__device__ __forceinline__ float rbf16(float x) { return __uint_as_float(pack2(0.f, x)); }
__device__ __forceinline__ uint32_t hmul2(uint32_t a, uint32_t b) {
    uint32_t r;
    asm("mul.rn.bf16x2 %0, %1, %2;" : "=r"(r) : "r"(a), "r"(b));
    return r;
}
__device__ __forceinline__ uint32_t hfma2(uint32_t a, uint32_t b, uint32_t c) {
    uint32_t r;
    asm("fma.rn.bf16x2 %0, %1, %2, %3;" : "=r"(r) : "r"(a), "r"(b), "r"(c));
    return r;
}
__device__ __forceinline__ uint32_t hfma2_lo(uint32_t a, uint32_t b, uint32_t c) {
    uint32_t r;
    asm("{\n.reg .b16 l, h;\n.reg .b32 t;\nmov.b32 {l, h}, %2;\nmov.b32 t, {l, l};\nfma.rn.bf16x2 %0, %1, t, %3;\n}\n" : "=r"(r) : "r"(a), "r"(b), "r"(c));
    return r;
}
__device__ __forceinline__ uint32_t hfma2_hi(uint32_t a, uint32_t b, uint32_t c) {
    uint32_t r;
    asm("{\n.reg .b16 l, h;\n.reg .b32 t;\nmov.b32 {l, h}, %2;\nmov.b32 t, {h, h};\nfma.rn.bf16x2 %0, %1, t, %3;\n}\n" : "=r"(r) : "r"(a), "r"(b), "r"(c));
    return r;
}
__device__ __forceinline__ uint32_t hadd2(uint32_t a, uint32_t b) {
    uint32_t r;
    asm("add.rn.bf16x2 %0, %1, %2;" : "=r"(r) : "r"(a), "r"(b));
    return r;
}
__device__ __forceinline__ uint32_t hsub2(uint32_t a, uint32_t b) {
    uint32_t r;
    asm("sub.rn.bf16x2 %0, %1, %2;" : "=r"(r) : "r"(a), "r"(b));
    return r;
}
__device__ __forceinline__ float tanh_fast(float x) {
    float r;
    asm("tanh.approx.f32 %0, %1;" : "=f"(r) : "f"(x));
    return r;
}
__device__ __forceinline__ void wg_fence() { asm volatile("wgmma.fence.sync.aligned;" ::: "memory"); }
__device__ __forceinline__ void wg_commit() { asm volatile("wgmma.commit_group.sync.aligned;" ::: "memory"); }
template <int N>
__device__ __forceinline__ void wg_wait() { asm volatile("wgmma.wait_group.sync.aligned %0;" ::"n"(N) : "memory"); }

#define WG_REGS "{%0,%1,%2,%3,%4,%5,%6,%7,%8,%9,%10,%11,%12,%13,%14,%15,%16,%17,%18,%19,%20,%21,%22,%23,%24,%25,%26,%27,%28,%29,%30,%31}"
#define WG_OPS(c) c(d[0]), c(d[1]), c(d[2]), c(d[3]), c(d[4]), c(d[5]), c(d[6]), c(d[7]), c(d[8]), c(d[9]), c(d[10]), \
    c(d[11]), c(d[12]), c(d[13]), c(d[14]), c(d[15]), c(d[16]), c(d[17]), c(d[18]), c(d[19]), c(d[20]), c(d[21]),     \
    c(d[22]), c(d[23]), c(d[24]), c(d[25]), c(d[26]), c(d[27]), c(d[28]), c(d[29]), c(d[30]), c(d[31])
__device__ __forceinline__ void wgmma_first(float* d, const uint32_t* a, uint64_t desc) {
    asm volatile("wgmma.mma_async.sync.aligned.m64n64k16.f32.bf16.bf16 " WG_REGS ", {%32,%33,%34,%35}, %36, 0, 1, 1, 1;"
                 : WG_OPS("+f") : "r"(a[0]), "r"(a[1]), "r"(a[2]), "r"(a[3]), "l"(desc));
}
__device__ __forceinline__ void wgmma_acc(float* d, const uint32_t* a, uint64_t desc) {
    asm volatile("wgmma.mma_async.sync.aligned.m64n64k16.f32.bf16.bf16 " WG_REGS ", {%32,%33,%34,%35}, %36, 1, 1, 1, 1;"
                 : WG_OPS("+f") : "r"(a[0]), "r"(a[1]), "r"(a[2]), "r"(a[3]), "l"(desc));
}
__device__ __forceinline__ void wgmma_k64(float* d, const uint32_t* a, uint64_t desc) {
    wgmma_first(d, a, desc);
    wgmma_acc(d, a + 4, desc + 128);
    wgmma_acc(d, a + 8, desc + 256);
    wgmma_acc(d, a + 12, desc + 384);
}
__device__ __forceinline__ void fence_regs(float* d) { asm volatile("" : WG_OPS("+f")::"memory"); }
__device__ __forceinline__ uint32_t qaxis(float x) {
    const float u = fmaf(x, QINVP, 0.25f);
    const float f = u - ((u + 12582912.f) - 12582912.f);
    return __float_as_uint(fmaf(fabsf(f), 510.f, 12582912.f));
}
__device__ __forceinline__ uint32_t qcode(float x, float y, float z, uint32_t tx) {
    return __byte_perm(__byte_perm(qaxis(x), qaxis(y), 0x3340), qaxis(z), 0x3410) ^ tx;
}
__device__ __forceinline__ bool near_test(uint32_t ca, uint32_t cb, uint32_t tag24, uint32_t& q) {
    const uint32_t D = __vabsdiffu4(ca, cb);
    q = __dp4a(D, D, 0x7FFFFFFFu - QSURE);
    return q <= 0x7FFFFFFFu - QSURE + QTHRESH || ((ca ^ tag24) | (cb ^ tag24)) >= 0x1000000u;
}
__device__ __forceinline__ bool inside(uint32_t rxy, uint32_t rz) {
    const uint32_t qxy = hmul2(rxy, rxy), qz = hmul2(rz, rz);
    return bf_lo(qxy) + bf_hi(qxy) + bf_lo(qz) <= 24.8125f;
}

__device__ __forceinline__ uint32_t lds32(uint32_t addr) {
    uint32_t r;
    asm volatile("ld.shared.u32 %0, [%1];" : "=r"(r) : "r"(addr));
    return r;
}
__device__ __forceinline__ void sts32_if(uint32_t addr, uint32_t v, bool c) {
    asm volatile("{\n.reg .pred p;\nsetp.ne.u32 p, %2, 0;\n@p st.shared.u32 [%0], %1;\n}\n" ::"r"(addr), "r"(v), "r"((uint32_t)c) : "memory");
}
__device__ __forceinline__ void stg128_if(void* ptr, uint4 v, bool c) {
    asm volatile("{\n.reg .pred p;\nsetp.ne.u32 p, %5, 0;\n@p st.relaxed.gpu.global.v4.u32 [%0], {%1,%2,%3,%4};\n}\n"
                 ::"l"(ptr), "r"(v.x), "r"(v.y), "r"(v.z), "r"(v.w), "r"((uint32_t)c) : "memory");
}
__device__ __forceinline__ void lds128(uint32_t addr, uint32_t* r) {
    asm volatile("ld.shared.v4.u32 {%0,%1,%2,%3}, [%4];" : "=r"(r[0]), "=r"(r[1]), "=r"(r[2]), "=r"(r[3]) : "r"(addr) : "memory");
}
template <int NP, int HI, int PAD = 1>
__device__ __forceinline__ void gather(uint32_t dst, const void* base, uint32_t c, uint32_t e) {
#define GATHER_HEAD "{\n.reg .pred p;\n.reg .b32 n;\n.reg .b64 a;\nprmt.b32 n, %2, 0, %3;\nsetp.ne.u32 p, n, 0xFFFF;\nmad.lo.u32 n, n, 512, %4;\nmad.wide.u32 a, n, 1, %1;\n"
#define GATHER_1(P) P "cp.async.cg.shared.global [%0], [a], 16;\n}\n"
#define GATHER_3(P) P "cp.async.cg.shared.global [%0], [a + 128], 16;\n" P "cp.async.cg.shared.global [%0 + 1024], [a + 256], 16;\n" \
                    P "cp.async.cg.shared.global [%0 + 2048], [a + 384], 16;\n}\n"
#define GATHER_ARGS(z) ::"r"(dst), "l"(base), "r"(e), "n"((HI ? 0x32 : 0x10) + z), "r"(c) : "memory"
    if constexpr (NP == 1 && PAD) asm volatile(GATHER_HEAD GATHER_1("@p ") GATHER_ARGS(0x4400));
    if constexpr (NP == 1 && !PAD) asm volatile(GATHER_HEAD GATHER_1("") GATHER_ARGS(0x4400));
    if constexpr (NP == 3 && PAD) asm volatile(GATHER_HEAD GATHER_3("@p ") GATHER_ARGS(0x5500));
    if constexpr (NP == 3 && !PAD) asm volatile(GATHER_HEAD GATHER_3("") GATHER_ARGS(0x4400));
    if constexpr (NP == 4)
        asm volatile(GATHER_HEAD "setp.ge.u32 p, %2, 0x40000000;\ncp.async.cg.shared.global [%0], [a], 16, p;\ncp.async.cg.shared.global [%0 + 1024], [a + 128], 16, p;\n"
                     "cp.async.cg.shared.global [%0 + 2048], [a + 256], 16, p;\ncp.async.cg.shared.global [%0 + 3072], [a + 384], 16, p;\n}\n" GATHER_ARGS(0x4400));
}
__device__ __forceinline__ void cp_commit() { asm volatile("cp.async.commit_group;" ::: "memory"); }
__device__ __forceinline__ void cp_wait1() { asm volatile("cp.async.wait_group 1;" ::: "memory"); }
__device__ __forceinline__ uint32_t hmul2_lo(uint32_t a, uint32_t b) {
    uint32_t r;
    asm("{\n.reg .b16 l, h;\n.reg .b32 t;\nmov.b32 {l, h}, %2;\nmov.b32 t, {l, l};\nmul.rn.bf16x2 %0, %1, t;\n}\n" : "=r"(r) : "r"(a), "r"(b));
    return r;
}
__device__ __forceinline__ void lds2_if(uint32_t a0, uint32_t a1, uint32_t* r, uint32_t c) {
    asm volatile("{\n.reg .pred p;\nsetp.ne.u32 p, %10, 0;\n@p ld.shared.v4.u32 {%0,%1,%2,%3}, [%8];\n@p ld.shared.v4.u32 {%4,%5,%6,%7}, [%9];\n}\n"
                 : "+r"(r[0]), "+r"(r[1]), "+r"(r[2]), "+r"(r[3]), "+r"(r[4]), "+r"(r[5]), "+r"(r[6]), "+r"(r[7])
                 : "r"(a0), "r"(a1), "r"(c) : "memory");
}
__device__ __forceinline__ int fresh_lane() {
    int l;
    asm volatile("mov.u32 %0, %%laneid;" : "=r"(l));
    return l;
}

__device__ __forceinline__ void cold_edges(unsigned char* smem, const Params& p, int lo, int hi, uint32_t tag) {
#pragma unroll 1
    for (int e = lo + threadIdx.x; e < hi; e += THREADS) {
        const int s = p.src[e], d = p.dst[e];
        uint32_t q;
        if (near_test(reinterpret_cast<const uint32_t*>(smem)[s], reinterpret_cast<const uint32_t*>(smem)[d], tag << 24, q)) {
            const uint32_t own = __umulhi((uint32_t)d, p.magic);
            const uint32_t slot4 = atomicAdd(reinterpret_cast<uint32_t*>(smem + SCNT_OFF) + own, 4u);
            uint32_t* line = reinterpret_cast<uint32_t*>(smem + STAGE_OFF) + own * 32;
            if (slot4 < 124) {
                line[(slot4 >> 2) ^ ((own & 7) << 2)] = ((uint32_t)s << 15) + ((uint32_t)(d - own * p.NPC) << 6) + tag + (q & 0x80000000u);
            } else {
                uint32_t o = atomicAdd(reinterpret_cast<uint32_t*>(smem + MISC_OFF) + 16, 1u);
                p.g->ovf[(size_t)blockIdx.x * (4 * p.gpc + 4) + o] = make_int2(s, d);
                line[31 ^ ((own & 7) << 2)] = (PAY_MARK << 6) | tag;
            }
        }
    }
}
__device__ __forceinline__ void cold_filter(unsigned char* smem, const Params& p, int e0, int e1, uint32_t tag, int redo) {
    if (redo) {
        if (threadIdx.x < MAXG) reinterpret_cast<uint32_t*>(smem + SCNT_OFF)[threadIdx.x] = 0;
        __syncthreads();
    }
    cold_edges(smem, p, redo ? 4 * e0 : 4 * (e0 + 3 * THREADS), 4 * e1, tag);
    if (blockIdx.x == 0) cold_edges(smem, p, p.E & ~3, p.E, tag);
    __syncthreads();
    if (threadIdx.x == 0) p.g->ovfcnt[blockIdx.x] = reinterpret_cast<uint32_t*>(smem + MISC_OFF)[16];
    __threadfence();
    __syncthreads();
}
__device__ __forceinline__ uint3 geometry(uint32_t rxy, uint32_t rz) {
    const uint32_t qxy = hmul2(rxy, rxy), qz = hmul2(rz, rz);
    float d, id;
    asm("sqrt.approx.ftz.f32 %0, %1;" : "=f"(d) : "f"(rbf16(rbf16(bf_lo(qxy) + bf_hi(qxy) + bf_lo(qz)) + 1e-8f)));
    d = rbf16(d);
    asm("rcp.approx.ftz.f32 %0, %1;" : "=f"(id) : "f"(d));
    const float cs = rbf16(__cosf(rbf16(rbf16(3.14159265358979f * d) * 0.2f)));
    const uint32_t zs = pack2(bf_lo(rz) * id, 0.5f * rbf16(cs + 1.0f) * id);
    return d < 5.0f ? make_uint3(pack2(bf_lo(rxy) * id, bf_hi(rxy) * id), zs, __byte_perm(__float_as_uint(d), zs, 0x7632)) : make_uint3(0, 0, 0);
}
__device__ __forceinline__ void cold_messages(unsigned char* smem, const Params& p, int nn) {
    const int nbase = blockIdx.x * p.NPC, lane = threadIdx.x & 31;
    const uint32_t* box = reinterpret_cast<const uint32_t*>(p.g->xbuf) + blockIdx.x * p.G * 32;
    uint32_t* w = reinterpret_cast<uint32_t*>(smem + RING_OFF);
#pragma unroll 1
    for (int i = threadIdx.x; i < 9728; i += THREADS)
        w[i] = i < 2048 ? reinterpret_cast<const uint32_t*>(p.w1)[i] : i < 8192 ? reinterpret_cast<const uint32_t*>(p.w2)[i - 2048] : reinterpret_cast<const uint32_t*>(p.wr)[i - 8192];
#pragma unroll 1
    for (int i = threadIdx.x; i < nn * 32; i += THREADS) reinterpret_cast<uint4*>(p.out)[nbase * 32 + i] = reinterpret_cast<const uint4*>(p.sv)[nbase * 32 + i];
    __threadfence();
    __syncthreads();
    const float freq = __bfloat162float(p.freqs[lane & 15]);
#pragma unroll 1
    for (int m = -1; m < p.G; m++) {
        const int cnt = m < 0 ? p.G * 32 : (__ldcg(box + m * 32 + 31) >> 6) == PAY_MARK ? __ldcg(&p.g->ovfcnt[m]) : 0;
#pragma unroll 1
        for (int i = threadIdx.x; i - lane < cnt; i += THREADS) {
            int2 e = make_int2(0, -1);
            if (i < cnt) {
                if (m < 0) {
                    const uint32_t x = __ldcg(box + i);
                    e = make_int2((x >> 15) & 0xFFFFu, nbase + ((x >> 6) & 511u));
                } else {
                    e = __ldcg(p.g->ovf + (size_t)m * (4 * p.gpc + 4) + i);
                }
            }
            bool in = (uint32_t)(e.y - nbase) < (uint32_t)nn;
            uint3 geo = make_uint3(0, 0, 0);
            if (in) {
                const uint2 ps = __ldcg(p.g->pos8 + e.x), pd = __ldcg(p.g->pos8 + e.y);
                const uint32_t rxy = hsub2(ps.x, pd.x), rz = hsub2(ps.y, pd.y);
                in = inside(rxy, rz);
                geo = geometry(rxy, rz);
            }
#pragma unroll 1
            for (uint32_t todo = __ballot_sync(0xffffffffu, in); todo; todo &= todo - 1) {
                const int l = __ffs(todo) - 1;
                const uint32_t* row = reinterpret_cast<const uint32_t*>(p.sv) + (size_t)__shfl_sync(0xffffffffu, e.x, l) * 128 + lane;
                uint32_t* orow = reinterpret_cast<uint32_t*>(p.out) + (size_t)__shfl_sync(0xffffffffu, e.y, l) * 128 + lane;
                const uint32_t gx = __shfl_sync(0xffffffffu, geo.x, l), gy = __shfl_sync(0xffffffffu, geo.y, l);
                const float rb = rbf16(__sinf(rbf16(bf_lo(__shfl_sync(0xffffffffu, geo.z, l)) * freq)) * bf_hi(gy));
                uint32_t x = row[0];
                float a[12] = {0, 0, 0, 0, 0, 0, 0, 0, 0, 0, 0, 0};
#pragma unroll 2
                for (int k = 0; k < 64; k++) {
                    const uint32_t u = __shfl_sync(0xffffffffu, x, k >> 1), ww = w[k * 32 + lane];
                    const float f = k & 1 ? bf_hi(u) : bf_lo(u);
                    a[0] = fmaf(f, bf_lo(ww), a[0]); a[1] = fmaf(f, bf_hi(ww), a[1]);
                }
                x = pack2(0.5f * fmaf(a[0], tanh_fast(0.5f * a[0]), a[0]), 0.5f * fmaf(a[1], tanh_fast(0.5f * a[1]), a[1]));
                a[0] = a[1] = 0.f;
#pragma unroll 2
                for (int k = 0; k < 64; k++) {
                    const uint32_t u = __shfl_sync(0xffffffffu, x, k >> 1);
                    const float f = k & 1 ? bf_hi(u) : bf_lo(u), r = __shfl_sync(0xffffffffu, rb, k & 15);
#pragma unroll
                    for (int c = 0; c < 3; c++) {
                        const uint32_t ww = w[2048 + k * 96 + c * 32 + lane], wr = k < 16 ? w[8192 + k * 96 + c * 32 + lane] : 0u;
                        a[2 * c] = fmaf(f, bf_lo(ww), a[2 * c]); a[2 * c + 1] = fmaf(f, bf_hi(ww), a[2 * c + 1]);
                        a[6 + 2 * c] = fmaf(r, bf_lo(wr), a[6 + 2 * c]); a[7 + 2 * c] = fmaf(r, bf_hi(wr), a[7 + 2 * c]);
                    }
                }
                const uint32_t mv = pack2(a[2] * a[8], a[3] * a[9]), mr = pack2(a[4] * a[10], a[5] * a[11]);
                const uint32_t o[4] = {pack2(a[0] * a[6], a[1] * a[7]), hfma2_lo(mr, gx, hmul2(mv, row[32])), hfma2_hi(mr, gx, hmul2(mv, row[64])),
                                       hfma2_lo(mr, gy, hmul2(mv, row[96]))};
#pragma unroll
                for (int c = 0; c < 4; c++) asm volatile("red.global.add.noftz.bf16x2 [%0], %1;" ::"l"(orow + 32 * c), "r"(o[c]) : "memory");
            }
        }
    }
}

#define SPLIT(k) asm volatile("{\n.reg .pred p;\nsetp.eq.u32 p, %0, %1;\n@p trap;\n}" ::"r"(c0), "n"(0x70000 + k) : "memory")
#define PIN8(a) asm volatile("" : "+r"((a)[0]), "+r"((a)[1]), "+r"((a)[2]), "+r"((a)[3]), "+r"((a)[4]), "+r"((a)[5]), "+r"((a)[6]), "+r"((a)[7]))
template <int V> struct IntC { static constexpr int value = V; };

template <int CN, int CE, int CG>
__global__ void __launch_bounds__(THREADS, 1) painn_kernel(const __grid_constant__ Params p) {
    extern __shared__ __align__(1024) unsigned char smem_dyn[];
    unsigned char* const smem = static_cast<unsigned char*>(__cvta_shared_to_generic(SB));
    constexpr uint32_t sb = SB;
    const int tid = threadIdx.x, lane = tid & 31;
    const int warp = __shfl_sync(0xffffffffu, tid >> 5, 0);
    constexpr int CNPC = CG ? (CN + CG - 1) / CG : 1, CGPC = CG ? (CE / 4 + CG - 1) / CG : 1;
    const int b = blockIdx.x, G = CG ? CG : p.G, NPC = CG ? CNPC : p.NPC, N = CG ? CN : p.N, gpc = CG ? CGPC : p.gpc;
    const uint32_t magic = CG ? (uint32_t)(((1ull << 32) + CNPC - 1) / CNPC) : p.magic;
    const bool odd_edges = CG ? (CE & 3) != 0 || CGPC > 3 * THREADS : p.odd_edges;
    const int nbase = b * NPC, nn = min(NPC, N - nbase);
    const int eg0 = b * gpc, eg1 = min((CG ? CE : p.E) >> 2, eg0 + gpc);

    uint4* stage4 = reinterpret_cast<uint4*>(smem + STAGE_OFF);
    uint32_t* ncnt = reinterpret_cast<uint32_t*>(smem + NCNT_OFF);
    uint32_t* misc = reinterpret_cast<uint32_t*>(smem + MISC_OFF);
    const uint32_t bar_tab = sb + BAR_OFF;

    TS0(0);
    int4 es[3], ed[3];
    auto load_edges = [&](int i) {
        const int g = min(eg0 + tid + i * THREADS, eg1 - 1);
        asm volatile("ld.global.cs.v4.u32 {%0,%1,%2,%3}, [%8];\nld.global.cs.v4.u32 {%4,%5,%6,%7}, [%9];"
                     : "=r"(es[i].x), "=r"(es[i].y), "=r"(es[i].z), "=r"(es[i].w), "=r"(ed[i].x), "=r"(ed[i].y), "=r"(ed[i].z), "=r"(ed[i].w)
                     : "l"(reinterpret_cast<const int4*>(p.src) + g), "l"(reinterpret_cast<const int4*>(p.dst) + g) : "memory");
    };
    es[0] = ed[0] = make_int4(0, 0, 0, 0);
    const char* const own = reinterpret_cast<const char*>(p.sv) + (size_t)nbase * 512;
    auto touch = [&](int o) {
        if (o + lane * 256 < nn * 512)
            asm volatile("cp.async.ca.shared.global.L2::256B [%0], [%1], 4;" ::"r"(sb + DUMMY_OFF + 4 * lane), "l"(own + o + lane * 256) : "memory");
    };
    uint4* const xout = p.g->xbuf + ((tid >> 3) * G + b) * 8 + (tid & 7);
    unsigned epoch;
    const uint32_t tbytes = ((N + 3) >> 2) * 16, cut = (tbytes >> 8) * CUT * 16, bar_cut = sb + BAR_OFF + 120;
    {
        uint32_t pxy, pz;
        if constexpr (CG && CN % 2 == 0) {
            asm volatile("ld.global.nc.u32 %0, [%3];\nld.global.nc.u32 %1, [%3 + 4];\nld.global.ca.u32 %2, [%4];"
                         : "=r"(pxy), "=r"(pz), "=r"(epoch)
                         : "l"(reinterpret_cast<const uint32_t*>(p.pos) + ((nbase + min(tid, nn - 1)) * 3 >> 1)), "l"(p.g->sync) : "memory");
            const uint32_t sh = ((nbase + tid) & 1) << 4;
            pxy = __funnelshift_r(pxy, pz, sh);
            pz >>= sh;
        } else {
            const uint16_t* q = reinterpret_cast<const uint16_t*>(p.pos) + (nbase + min(tid, nn - 1)) * 3;
            pxy = q[0] | (uint32_t)q[1] << 16;
            pz = q[2];
            asm volatile("ld.global.ca.u32 %0, [%1];" : "=r"(epoch) : "l"(p.g->sync) : "memory");
        }
        const uint32_t code = qcode(bf_lo(pxy), bf_hi(pxy), bf_lo(pz), ((epoch & 31u) ^ 0x6Bu) << 24);
        asm volatile("{\n.reg .pred p;\nsetp.lt.s32 p, %2, %3;\n@p st.global.u32 [%0], %1;\n}\n"
                     ::"l"(reinterpret_cast<uint32_t*>(p.g->table) + nbase + tid), "r"(code), "r"(tid), "r"(nn) : "memory");
        __syncthreads();
        asm volatile("{\n.reg .pred p;\nsetp.eq.u32 p, %1, %2;\n@p red.relaxed.gpu.global.add.u32 [%0], 1;\n}\n" ::"l"(p.g->sync + 1), "r"(tid), "n"(THREADS - 1) : "memory");
        if (tid < THREADS - 32) load_edges(0);
        if (tid < nn) p.g->pos8[nbase + tid] = make_uint2(pxy, pz);
        reinterpret_cast<uint2*>(smem + OPOS_OFF)[tid] = make_uint2(pxy, pz);
    }
    const uint32_t tag = (epoch & 31u) | 32u;
    if (tid == THREADS - 1) {
        TSX(1, 511);
        mbar_init(bar_tab, 1);
        mbar_init(bar_cut, 1);
        mbar_expect_tx(bar_cut, cut);
        mbar_expect_tx(bar_tab, tbytes - cut);
        const unsigned want = (epoch + 1) * G;
        unsigned c;
        int it = smem_u32(smem_dyn) == SB ? 0 : 1 << 22;
        __nanosleep(HDELAY);
        do {
            asm volatile("ld.relaxed.gpu.global.u32 %0, [%1];" : "=r"(c) : "l"(p.g->sync + 1) : "memory");
            if (++it > (1 << 22)) __trap();
        } while (c != want);
        bulk_g2s(sb, p.g->table, cut, bar_cut);
        bulk_g2s(sb + cut, reinterpret_cast<const char*>(p.g->table) + cut, tbytes - cut, bar_tab);
        TSX(2, 511);
    }
    if (warp == 14) {
#pragma unroll 1
        for (int c = b * 32 + lane; c < RING_OFF / 16; c += G * 32) {
            const int row = c >> 3, j = (c ^ row) & 7;
            uint4 v;
            if (c < 512) {
                const uint32_t half = 0x3F003F00u;
                v = __ldg(reinterpret_cast<const uint4*>(p.w1) + row * 8 + j);
                v = make_uint4(hmul2(v.x, half), hmul2(v.y, half), hmul2(v.z, half), hmul2(v.w, half));
            } else {
                const uint32_t* q = (c < 2048 ? reinterpret_cast<const uint32_t*>(p.w2) + (row & 63) * 96 + ((row >> 6) - 1) * 32
                                              : reinterpret_cast<const uint32_t*>(p.wr) + (row & 15) * 96 + ((row >> 4) - 16) * 32) + (j & 4) * 4 + (j & 3);
                v = make_uint4(__ldg(q), __ldg(q + 4), __ldg(q + 8), __ldg(q + 12));
            }
            p.g->wimg[c] = v;
        }
    }
    if (tid == 416) {
#pragma unroll
        for (int i = 0; i < FLIGHT + 2; i++) mbar_init(sb + BAR_OFF + 8 + 8 * i, i ? 1 : 15);
    }
    ncnt[tid] = tid < 480 ? 0 : 1024;
    if (tid < MAXG + 32) reinterpret_cast<uint32_t*>(smem + SCNT_OFF)[tid] = tid < MAXG ? 0 : 128;
    if (tid < 128) misc[tid] = 0;
    {
        const uint32_t inv = (PAY_INVALID << 6) | tag;
        stage4[tid] = stage4[tid + THREADS] = make_uint4(inv, inv, inv, inv);
        if (tid < MAXG * 8 - 2 * THREADS) stage4[tid + 2 * THREADS] = make_uint4(inv, inv, inv, inv);
    }
    __syncthreads();
    if ((tid >> 4) == 29) asm volatile("cp.async.ca.shared.global [%0], [%1], 4;" ::"r"(sb + FREQ_OFF + 8 * (tid & 14) + 4 * (tid & 1)),
                              "l"(reinterpret_cast<const uint32_t*>(p.freqs) + ((tid & 7) >> 1) + (tid & 1) * 4) : "memory");
    if (warp == 15) load_edges(0);
    if (warp < 8) mbar_wait(bar_cut, 0);
    load_edges(1);
    load_edges(2);
    if (tid == 416) asm volatile("fence.acq_rel.gpu;" ::: "memory");
    if (warp >= 8) mbar_wait(bar_cut, 0);
    {
        const uint32_t x = (PAY_INVALID << 6) | (tag ^ 16);
#pragma unroll
        for (int i = 0; i < 3; i++) stg128_if(xout + i * G * THREADS, make_uint4(x, x, x, x), tid + i * THREADS < G * 8);
    }
    bool full = false;
    {
        uint32_t at[24], msg[12], cnt[12], line[12];
#pragma unroll
        for (int j = 0; j < 12; j++) {
            const uint32_t s = j % 4 == 0 ? es[j / 4].x : j % 4 == 1 ? es[j / 4].y : j % 4 == 2 ? es[j / 4].z : es[j / 4].w;
            const uint32_t d = j % 4 == 0 ? ed[j / 4].x : j % 4 == 1 ? ed[j / 4].y : j % 4 == 2 ? ed[j / 4].z : ed[j / 4].w;
            const uint32_t own = __umulhi(d, magic);
            at[2 * j] = 4 * s; at[2 * j + 1] = 4 * d;
            msg[j] = own * (uint32_t)(-64 * NPC) + ((s << 15) + ((d << 6) + tag));
            cnt[j] = eg0 + tid + (j / 4) * THREADS < eg1 ? 4 * own : 4 * (MAXG + lane);
            line[j] = own * 128 + ((own & 7) << 4);
            asm volatile("" : "+r"(at[2 * j]), "+r"(at[2 * j + 1]), "+r"(msg[j]), "+r"(cnt[j]), "+r"(line[j]));
        }
        mbar_wait(bar_tab, 0);
        TS0(3);
        if (warp == 15) {
#pragma unroll
            for (int i = 0; i < TOUCH; i++) touch(i * 8192);
        }
#pragma unroll
        for (int i = 0; i < 12; i += 6) {
            uint32_t sl[6], cd[12];
#pragma unroll
            for (int j = 0; j < 12; j++) cd[j] = lds32(sb + at[2 * i + j]);
#pragma unroll
            for (int j = 0; j < 6; j++) {
                uint32_t q;
                const bool c = near_test(cd[2 * j], cd[2 * j + 1], tag << 24, q);
                msg[i + j] |= q & 0x80000000u;
                asm volatile("atom.shared.add.u32 %0, [%1 + %2], 4;" : "=r"(sl[j]) : "r"(c ? cnt[i + j] : 4 * (MAXG + lane)), "n"(SB + SCNT_OFF) : "memory");
            }
#pragma unroll
            for (int j = 0; j < 6; j++) {
                sts32_if(sb + STAGE_OFF + (line[i + j] ^ sl[j]), msg[i + j], sl[j] < 124);
                full |= sl[j] == 124;
            }
        }
    }
    {
        const int redo = __syncthreads_or(full);
        if (__builtin_expect(redo || odd_edges, 0)) cold_filter(smem, p, eg0, eg1, tag, redo);
    }
    TS0(4);
#pragma unroll
    for (int i = 0; i < 3; i++)
        stg128_if(xout + i * G * THREADS, stage4[(tid ^ ((tid >> 3) & 7)) + i * THREADS],
                  tid + i * THREADS < G * 8 && reinterpret_cast<const uint32_t*>(smem + SCNT_OFF)[(tid >> 3) + i * 64] >= (tid & 6) * 16u);
    __syncthreads();
#pragma unroll
    for (int i = -2; i < 2; i++) {
        const int c = tid + i * THREADS;
        const uint32_t x = c < (SN_OFF - STAGE_OFF) / 16 ? 0u : 0xFFFFFFFFu;
        if (c >= (SREC_OFF - STAGE_OFF) / 16) stage4[c] = make_uint4(x, x, x, x);
    }
    uint32_t key[4] = {0, 0, 0, 0};
    uint2 pr[4];
    const uint32_t gp = sb + RING_OFF + 2048 + (warp < 4 * NWG ? warp * 12288 : (warp & 3) * 12288 + 2048) + lane * 16;
    uint32_t pk = 0;
    if (warp == 15) {
        if (lane == 0) {
            int o = TOUCH * 8192;
#pragma unroll 1
            while (o < nn * 512 && !mbar_test(sb + BAR_OFF + 8, 0)) {
                const uint32_t bar = sb + BAR_OFF + 16 + 8 * (pk % FLIGHT);
                if (!mbar_test(bar, ~(pk / FLIGHT) & 1)) continue;
                const int n = min(4096, nn * 512 - o);
                mbar_expect_tx(bar, n);
                bulk_g2s(sb + DUMMY_OFF, own + o, n, bar);
                o += n;
                pk++;
            }
            misc[3] = pk;
        }
        __syncwarp();
    } else {
    __nanosleep(PDELAY);
    TS0(5);

    {
        const int LPW = (G + 14) / 15;
        uint32_t ew[3][4], bad[3];
        const uint4* cp = p.g->xbuf + (b * G + warp * LPW) * 8 + lane;
#pragma unroll
        for (int i = 0; i < 3; i++) {
            bad[i] = lane + 32 * i < min(LPW, G - warp * LPW) * 8;
            ew[i][0] = ew[i][1] = ew[i][2] = ew[i][3] = (PAY_INVALID << 6) | tag;
        }
        int it = 0;
#pragma unroll 1
        do {
#pragma unroll
            for (int i = 0; i < 3; i++)
                asm volatile("{\n.reg .pred p;\nsetp.ne.u32 p, %5, 0;\n@p ld.relaxed.gpu.global.v4.u32 {%0,%1,%2,%3}, [%4];\n}\n"
                             : "+r"(ew[i][0]), "+r"(ew[i][1]), "+r"(ew[i][2]), "+r"(ew[i][3]) : "l"(cp + 32 * i), "r"(bad[i]) : "memory");
#pragma unroll
            for (int i = 0; i < 3; i++) {
                const uint32_t x = (ew[i][0] ^ tag) | (ew[i][1] ^ tag) | (ew[i][2] ^ tag) | (ew[i][3] ^ tag);
                const uint32_t full = __ballot_sync(0xffffffffu, ew[i][3] < (PAY_INVALID << 6)) << 1 | 0x01010101u;
                bad[i] = (__ballot_sync(0xffffffffu, x & ((full >> (lane & 30)) & 1 ? 63u : 47u)) >> (lane & 24)) & 255u;
            }
            if (++it > (1 << 22)) __trap();
        } while (__any_sync(0xffffffffu, bad[0] | bad[1] | bad[2]));
        TSX(21, 0); TSX(22, 448);
        uint4* pack = reinterpret_cast<uint4*>(smem + PACK_OFF);
        int nch = 0;
        uint32_t at[3];
#pragma unroll
        for (int i = 0; i < 3; i++) {
            const uint32_t m = __ballot_sync(0xffffffffu, ew[i][0] < (PAY_MARK << 6));
            at[i] = nch + __popc(m & ((1u << lane) - 1));
            nch += __popc(m);
        }
        if (__builtin_expect(nch > 32, 0)) {
#pragma unroll 1
            for (int i = 0; i < 3; i++) {
                if (ew[0][0] < (PAY_MARK << 6) && at[0] >= 32) at[0] = (15 - warp) * 32 - 1 - min(atomicAdd(&misc[1], 1u), 31u);
                const uint32_t x = at[0], y = ew[0][0];
                at[0] = at[1]; at[1] = at[2]; at[2] = x;
                ew[0][0] = ew[1][0]; ew[1][0] = ew[2][0]; ew[2][0] = y;
            }
        }
#pragma unroll
        for (int i = 0; i < 3; i++) {
            asm volatile("{\n.reg .pred p;\nsetp.lt.u32 p, %1, %5;\n@p st.shared.v4.u32 [%0], {%1,%2,%3,%4};\n}\n"
                         ::"r"(sb + PACK_OFF + (warp * 32 + at[i]) * 16), "r"(ew[i][0]), "r"(ew[i][1]), "r"(ew[i][2]), "r"(ew[i][3]), "n"(PAY_MARK << 6) : "memory");
            sts32_if(sb + MISC_OFF + 4 * 17, 1, (ew[i][3] >> 6) == PAY_MARK);
        }
        bool have = lane < nch;
        if (warp == 14) {
            asm volatile("bar.sync 7, 480;" ::: "memory");
            const uint32_t extra = misc[1];
            if (nch + extra > 32) misc[18] = 1;
            have = have || lane + extra >= 32;
        } else {
            asm volatile("bar.arrive 7, 480;" ::: "memory");
        }
        __syncwarp();
        uint32_t w[4], rk[4];
        bool in[4];
        {
            const uint4 x = pack[tid];
            w[0] = have ? x.x : ~0u; w[1] = have ? x.y : ~0u; w[2] = have ? x.z : ~0u; w[3] = have ? x.w : ~0u;
        }
        auto fetch = [&](int j, bool c) {
            asm volatile("{\n.reg .pred p;\nsetp.ne.u32 p, %2, 0;\n@p cp.async.cg.shared.global [%0], [%1], 16;\n}\n"
                         ::"r"(gp + j * 512), "l"(reinterpret_cast<const uint4*>(p.g->pos8) + ((w[j] >> 16) & 0x7FFFu)), "r"((uint32_t)c) : "memory");
        };
#pragma unroll
        for (int j = 0; j < 4; j++) fetch(j, (int)w[j] < (int)(PAY_MARK << 6));
#pragma unroll
        for (int j = 0; j < 4; j++) pr[j] = reinterpret_cast<const uint2*>(smem + OPOS_OFF)[(w[j] >> 6) & 511u];
        uint32_t ca[4];
#pragma unroll
        for (int j = 0; j < 4; j++) {
            key[j] = ((w[j] >> 15) & 0xFFFFu) | ((w[j] << 10) & 0x1FF0000u);
            ca[j] = sb + NCNT_OFF + ((w[j] >> 4) & 0x7FCu);
            asm volatile("" : "+r"(key[j]), "+r"(ca[j]));
        }
        asm volatile("{\n.reg .pred p;\nsetp.eq.u32 p, %0, -1;\n@p trap;\n}" ::"r"(nch) : "memory");
        asm volatile("cp.async.wait_all;" ::: "memory");
        TSX(23, 0); TSX(24, 448);
        asm volatile("{\n.reg .pred p;\nsetp.eq.u32 p, %1, 0;\n@p mbarrier.arrive.shared::cta.b64 _, [%0];\n}\n" ::"r"(sb + BAR_OFF + 8), "r"(lane) : "memory");
#pragma unroll
        for (int j = 0; j < 4; j++) {
            uint2 ps;
            asm volatile("ld.shared.v2.u32 {%0,%1}, [%2];" : "=r"(ps.x), "=r"(ps.y) : "r"(gp + j * 512 + ((w[j] >> 12) & 8)) : "memory");
            in[j] = ((int)w[j] >= 0) | (((int)w[j] < (int)(PAY_MARK << 6)) & inside(hsub2(ps.x, pr[j].x), hsub2(ps.y, pr[j].y)));
        }
#pragma unroll
        for (int j = 0; j < 4; j++)
            asm volatile("atom.shared.add.u32 %0, [%1], 1;" : "=r"(rk[j]) : "r"(in[j] ? ca[j] : sb + NCNT_OFF + 4 * (480 + lane)) : "memory");
#pragma unroll
        for (int j = 0; j < 4; j++) {
            rk[j] = rk[j] < SPL ? 2 * rk[j] : min(2 * rk[j] - (2 * SPL - 1), 126u);
            asm volatile("red.shared.add.u32 [%0 + %1], 1;" ::"r"(rk[j] & 2 ? 124u : rk[j] & 60u), "n"(SB + MISC_OFF + 128) : "memory");
            key[j] += rk[j] << 25;
        }
#pragma unroll
        for (int j = 0; j < 4; j++) fetch(j, (int)w[j] >= 0);
        cp_commit();
    }
    }
    __syncthreads();
    TS0(6);
    uint32_t deg[5];
    deg[4] = lds32(sb + NCNT_OFF + 4 * tid);
#pragma unroll
    for (int j = 0; j < 4; j++) deg[j] = lds32(sb + NCNT_OFF + ((key[j] >> 14) & 0x7FCu));
    if (tid == THREADS - 33) {
        if (b == 0) p.g->sync[0] = epoch + 1;
        asm volatile("fence.proxy.async.global;" ::: "memory");
        mbar_expect_tx(bar_tab, RING_OFF);
        bulk_g2s(sb, p.g->wimg, RING_OFF, bar_tab);
    }
    __syncwarp();
    uint32_t dst = sb + RING_OFF + warp * 12288 + (lane >> 3) * 256 + (((lane & 7) ^ (lane >> 3)) << 4), l7 = (lane & 7) * 16, g32 = (lane >> 2) * 32;
    uint32_t e0, e1, n0, n1;
    auto sources = [&](uint32_t c) {
        asm volatile("{\n.reg .b32 a;\nlop3.b32 a, %4, %5, 0xFFC0, 0xA8;\nshr.u32 a, a, 2;\nld.shared.v4.u32 {%0,%1,%2,%3}, [a + %6];\n}\n"
                     : "=r"(e0), "=r"(n0), "=r"(e1), "=r"(n1) : "r"(c), "r"(g32), "n"(SB + SN_OFF));
    };
    auto load_s = [&](auto pad) {
        gather<1, 0, pad.value>(dst, p.sv, l7, e0); gather<1, 1, pad.value>(dst + 1024, p.sv, l7, e0);
        gather<1, 0, pad.value>((dst ^ 64) + 128, p.sv, l7, e1); gather<1, 1, pad.value>((dst ^ 64) + 1152, p.sv, l7, e1);
    };
    auto load_o = [&]() {
        gather<4, 0>(dst + 8192, p.sv, l7, n0); gather<4, 0>((dst ^ 64) + 8320, p.sv, l7, n1);
    };
    auto load_v = [&](auto pad) {
        gather<3, 0, pad.value>(dst + 2048, p.sv, l7, e0); gather<3, 1, pad.value>(dst + 5120, p.sv, l7, e0);
        gather<3, 0, pad.value>((dst ^ 64) + 2176, p.sv, l7, e1); gather<3, 1, pad.value>((dst ^ 64) + 5248, p.sv, l7, e1);
        cp_commit();
    };
    const int ng = (misc[32] + 7) >> 3;
    const int give = max(min(ng - max((int)(misc[33] + 7) >> 3, 4 * NWG), GIVE), 0);
    if (warp == 15) {
        const uint32_t cnt = lane < 16 ? (misc[32 + lane] + 7) >> 3 : 0u;
        uint32_t z = cnt;
#pragma unroll
        for (int o = 1; o < 16; o <<= 1) {
            const uint32_t y = __shfl_up_sync(0xffffffffu, z, o);
            if (lane >= o) z += y;
        }
        misc[96 + lane] = lane < 16 ? 64 * (z - cnt) : 64 * (MAXROW + 1);
        asm volatile("bar.arrive 5, 512;" ::: "memory");
        if (lane == 15) {
            const bool cold = cnt || z > MAXROW || misc[31 + SPL / 2] > 32 || misc[17] || misc[18];
            misc[18] = cold;
            asm volatile("st.relaxed.gpu.global.u32 [%0], %1;" ::"l"(p.g->rows + b), "r"(~epoch << 16 | (cold || ng < 4 * NWG ? 255 : give << 8 | z)) : "memory");
        }
        pk = (z - cnt) << 8 | __shfl_down_sync(0xffffffffu, cnt, 1) << 24;
    } else {
        if (warp * 32 < nn) {
            const uint32_t c = deg[4], st = tid < nn ? (min(c, (uint32_t)SPL) + 1) >> 1 : 17u;
            const uint32_t same = __match_any_sync(0xffffffffu, st), first = __ffs(same) - 1;
            uint32_t r, node = nbase + tid;
            asm volatile("atom.shared.add.u32 %0, [%1], %2;" : "=r"(r)
                         : "r"(lane == first ? sb + MISC_OFF + 4 * (64 + st) : sb + NCNT_OFF + 4 * (480 + lane)), "r"(__popc(same)) : "memory");
            r = __shfl_sync(0xffffffffu, r, first) + __popc(same & ((1u << lane) - 1)) + misc[32 + st];
            if (__builtin_expect(c > SPL, 0)) {
                const uint32_t s2 = min((c - SPL + 1) >> 1, 16u), r2 = misc[32 + s2] + atomicAdd(&misc[64 + s2], 1u), k = atomicAdd(&misc[2], 1u);
                reinterpret_cast<uint32_t*>(smem + SCNT_OFF)[k & 31] = node;
                node |= NODE_SPLIT;
                ncnt[1024 + tid] = 8 * r2;
                reinterpret_cast<uint32_t*>(smem + SN_OFF)[(r2 & 511) * 2 + 1] = node;
            }
            if (tid < nn) {
                ncnt[512 + tid] = 8 * r;
                reinterpret_cast<uint32_t*>(smem + SN_OFF)[(r & 511) * 2 + 1] = node;
            }
        }
#pragma unroll
        for (int j = 0; j < 4; j++) {
            const uint32_t c = deg[j];
            asm volatile("{\n.reg .pred p;\n.reg .b64 a;\nsetp.ge.u32 p, %0, %3;\nsetp.lt.and.u32 p, %1, 0x8000000, p;\nmad.wide.u32 a, %4, 512, %2;\n@p prefetch.global.L2 [a];\n"
                         "}\n" ::"r"(c), "r"(key[j]), "l"(p.sv), "n"(BIG), "r"(key[j] & 0xFFFFu) : "memory");
        }
        asm volatile("bar.sync 5, 512;" ::: "memory");
        uint32_t slot[4];
#pragma unroll
        for (int j = 0; j < 4; j++) slot[j] = min(misc[96 + (key[j] >> 27)] + (ncnt[512 + ((key[j] >> 16) & 1023)] & 0xFFF8u), 64u * (MAXROW + 1)) + ((key[j] >> 25) & 2);
#pragma unroll
        for (int j = 0; j < 4; j++) {
            *reinterpret_cast<uint16_t*>(smem + SN_OFF + slot[j]) = (uint16_t)key[j];
            slot[j] += slot[j] & 2;
        }
        asm volatile("bar.sync 6, 480;" ::: "memory");
        TS0(7);
        if (warp < 4 * NWG) {
            sources((warp < ng ? warp : MAXROW) << 8);
            e0 = __vminu2(e0, (N - 1) * 0x10001u);
            e1 = __vminu2(e1, (N - 1) * 0x10001u);
            load_s(IntC<0>{});
            cp_commit();
            load_o();
            cp_commit();
            asm volatile("cp.async.wait_group 2;" ::: "memory");
        } else {
            asm volatile("cp.async.wait_all;" ::: "memory");
        }
        uint2 ps[4];
#pragma unroll
        for (int j = 0; j < 4; j++)
            asm volatile("ld.shared.v2.u32 {%0,%1}, [%2];" : "=r"(ps[j].x), "=r"(ps[j].y) : "r"(gp + j * 512 + (key[j] & 1) * 8) : "memory");
        TSX(9, 0);
#pragma unroll 1
        for (int i = 0; i < 2; i++) {
#pragma unroll
            for (int u = 0; u < 2; u++) {
                const uint3 geo = geometry(hsub2(ps[u].x, pr[u].x), hsub2(ps[u].y, pr[u].y));
                *reinterpret_cast<uint2*>(smem + SREC_OFF + 2 * slot[u]) = make_uint2(geo.x, geo.y);
                *reinterpret_cast<uint32_t*>(smem + SD_OFF + slot[u]) = geo.z;
                ps[u] = ps[u + 2];
                pr[u] = pr[u + 2];
                slot[u] = slot[u + 2];
            }
        }
    }
    if (warp == 15) { __syncwarp(); asm volatile("bar.arrive 4, 512;" ::: "memory"); }
    else asm volatile("bar.sync 4, 512;" ::: "memory");
    TS0(8);
    auto drain = [&](int i) { if (i < FLIGHT) mbar_wait(sb + BAR_OFF + 16 + 8 * i, ~((misc[3] + FLIGHT - 1 - i) / FLIGHT) & 1); };
    if (__builtin_expect(misc[18], 0)) {
        drain(warp);
        asm volatile("cp.async.wait_all;" ::: "memory");
        __syncthreads();
        cold_messages(smem, p, nn);
        mbar_wait(bar_tab, 1);
        return;
    }

    if (warp < 4 * NWG) {
        asm volatile("setmaxnreg.inc.sync.aligned.u32 %0;" ::"n"(REG_C));
        const int lane = fresh_lane();
        const int g = lane >> 2, q = lane & 3;
        const uint64_t dW1 = p.desc0, dW2 = dW1 + (W2_OFF >> 4), dWR = dW1 + (WR_OFF >> 4);
        const uint32_t ring = sb + RING_OFF + warp * 12288;
        const uint32_t vrow = pin(ring + g * 128 + ((q ^ ((g & 1) << 2) ^ (g >> 1)) << 4));
        const uint32_t mrow = pin(ring + (lane & 15) * 128 + (((lane >> 4) ^ ((lane & 1) << 2) ^ ((lane & 7) >> 1)) << 4));
        dst = pin(ring + (lane >> 3) * 256 + (((lane & 7) ^ (lane >> 3)) << 4)); l7 = pin((lane & 7) * 16); g32 = pin(g * 32);
        uint32_t ctl = sb + CTL_OFF + warp * 4;
        auto control = [&](uint32_t c, uint32_t at) {
            int it = 0;
#pragma unroll 1
            while (__builtin_expect(c == 0xFFFFFFFFu, 0)) {
                asm volatile("ld.volatile.shared.u32 %0, [%1];" : "=r"(c) : "r"(at) : "memory");
                c = __reduce_or_sync(0xffffffffu, c);
                if (++it > (1 << 24)) __trap();
            }
            return c;
        };
        uint32_t c0 = control(0xFFFFFFFFu, ctl), c1 = control(0xFFFFFFFFu, ctl + 64);
        if (warp >= 8) asm volatile("bar.arrive 1, 256;" ::: "memory");
        uint32_t acc[32];
        float P[32], W[32];
#pragma unroll
        for (int i = 0; i < 32; i++) { acc[i] = 0; P[i] = W[i] = 0.f; }
        mbar_wait(bar_tab, 1);
        sources(c0);
        e0 = __vminu2(e0, (N - 1) * 0x10001u);
        e1 = __vminu2(e1, (N - 1) * 0x10001u);
        if (warp >= 8) asm volatile("cp.async.wait_all;" ::: "memory");
        else if (warp >= 4) cp_wait1();
        load_v(IntC<0>{});
        auto finish = [&](uint32_t c, uint32_t node) {
            if (c & ST_CLOSE) {
                uint64_t op[2];
                asm("{\n.reg .b32 a;\nmad.lo.u32 a, %2, 512, %3;\nmad.wide.u32 %0, a, 1, %4;\nxor.b32 a, a, 64;\nmad.wide.u32 %1, a, 1, %4;\n}\n"
                    : "=l"(op[0]), "=l"(op[1]) : "r"(node), "r"(l7), "l"(p.out));
#pragma unroll
                for (int k = 0; k < 8; k++) {
                    uint32_t x[4];
#pragma unroll
                    for (int i = 0; i < 4; i++) x[i] = l7 & 64 ? acc[4 * (k ^ 1) + i] : acc[4 * k + i];
                    asm volatile("{\n.reg .pred p;\nsetp.lt.u32 p, %5, %6;\n@p st.global.cs.v4.u32 [%0], {%1,%2,%3,%4};\n}\n"
                                 ::"l"(op[k & 1] + 128 * (k >> 1)), "r"(x[0]), "r"(x[1]), "r"(x[2]), "r"(x[3]), "r"(node), "n"(NODE_SPLIT) : "memory");
                }
                if (__builtin_expect(__any_sync(0xffffffffu, (int)node >= (int)NODE_SPLIT), 0)) {
                    mbar_wait(sb + BAR_OFF + 16 + 8 * FLIGHT, 0);
                    if ((int)node >= (int)NODE_SPLIT) {
#pragma unroll
                        for (int k = 0; k < 8; k++)
                            asm volatile("red.global.add.noftz.v4.bf16x2 [%0], {%1,%2,%3,%4};" ::"l"((op[0] & ~64ull) + 64 * k), "r"(acc[4 * k]), "r"(acc[4 * k + 1]), "r"(acc[4 * k + 2]), "r"(acc[4 * k + 3]) : "memory");
                    }
                    __syncwarp();
                }
            }
        };
        uint32_t f01, f23;
        asm volatile("ld.shared.v2.u32 {%0,%1}, [%2 + %3];" : "=r"(f01), "=r"(f23) : "r"(l7), "n"(SB + FREQ_OFF));
        f01 = pin(f01); f23 = pin(f23);
#pragma unroll 1
        while ((int)c0 >= 0) {
            uint32_t a[16], h[16], rf[4], rr[4], m[16];
            TRW(ctl);
            uint32_t dd[2];
            asm volatile("ld.shared.v2.u32 {%0,%1}, [%2 + %3];" : "=r"(dd[0]), "=r"(dd[1]) : "r"(((c0 & 0xFF00) | g32) >> 2), "n"(SB + SD_OFF));
            sources(c1);
            asm volatile("cp.async.wait_group 2;" ::: "memory");
            __syncwarp();
#pragma unroll
            for (int i = 0; i < 4; i++) ldsm4(mrow ^ (i << 5), a + 4 * i);
            wg_fence();
            wgmma_k64(P, a, dW1);
            wg_commit();
#pragma unroll
            for (int hh = 0; hh < 2; hh++) {
                const float sc = bf_hi(dd[hh]);
                const uint32_t x01 = hmul2_lo(f01, dd[hh]), x23 = hmul2_lo(f23, dd[hh]);
                rf[hh] = pack2(__sinf(bf_lo(x01)) * sc, __sinf(bf_hi(x01)) * sc);
                rf[2 + hh] = pack2(__sinf(bf_lo(x23)) * sc, __sinf(bf_hi(x23)) * sc);
            }
            asm volatile("" : "+r"(rf[0]), "+r"(rf[1]), "+r"(rf[2]), "+r"(rf[3]));
            asm volatile("bar.sync %0, 256;" ::"r"(1 + (warp >> 2)) : "memory");
            SPLIT(2);
            wg_wait<0>();
            fence_regs(P);
#pragma unroll
            for (int i = 0; i < 16; i++)
                h[i] = pack2(fmaf(P[2 * i], tanh_fast(P[2 * i]), P[2 * i]), fmaf(P[2 * i + 1], tanh_fast(P[2 * i + 1]), P[2 * i + 1]));
            wg_fence();
            wgmma_k64(P, h, dW2 + 1024);
            wgmma_first(W, rf, dWR + 256);
            wg_commit();
            asm volatile("bar.arrive %0, 256;" ::"r"((c0 >> 4) & 3) : "memory");
            cp_wait1();
            __syncwarp();
#pragma unroll
            for (int k = 0; k < 4; k++) lds2_if(vrow + 8192 + 1024 * k, (vrow ^ 64) + 8192 + 1024 * k, acc + 8 * k, c0 & ST_START);
            lds128(sb + SREC_OFF + (((c0 & 0xFF00) | g32) >> 1), rr);
            uint32_t c2 = lds32(ctl + 128);
            __syncwarp();
            load_s(IntC<1>{});
            cp_commit();
            if (c1 & ST_START) load_o();
            cp_commit();
            wg_wait<0>();
            fence_regs(P); fence_regs(W);
#pragma unroll
            for (int j = 0; j < 8; j++) {
                m[j] = pack2(P[4 * j] * W[4 * j], P[4 * j + 1] * W[4 * j + 1]);
                m[8 + j] = pack2(P[4 * j + 2] * W[4 * j + 2], P[4 * j + 3] * W[4 * j + 3]);
            }
            wg_fence();
            wgmma_k64(P, h, dW2);
            wgmma_first(W, rf, dWR);
            wg_commit();
            SPLIT(4);
            PIN8(m); PIN8(m + 8);
            c2 = __reduce_or_sync(0xffffffffu, c2);
#pragma unroll
            for (int k = 1; k < 4; k++)
#pragma unroll
                for (int j = 0; j < 8; j++) {
                    const uint32_t x = k == 1 ? hfma2_lo(m[j], rr[0], acc[8 * k + j]) : k == 2 ? hfma2_hi(m[j], rr[0], acc[8 * k + j]) : hfma2_lo(m[j], rr[1], acc[8 * k + j]);
                    acc[8 * k + j] = k == 1 ? hfma2_lo(m[8 + j], rr[2], x) : k == 2 ? hfma2_hi(m[8 + j], rr[2], x) : hfma2_lo(m[8 + j], rr[3], x);
                }
            PIN8(acc + 8); PIN8(acc + 16); PIN8(acc + 24);
            c2 = control(c2, ctl + 128);
            wg_wait<0>();
            fence_regs(P); fence_regs(W);
#pragma unroll
            for (int j = 0; j < 8; j++)
                acc[j] = hadd2(acc[j], pack2(fmaf(P[4 * j], W[4 * j], P[4 * j + 2] * W[4 * j + 2]), fmaf(P[4 * j + 1], W[4 * j + 1], P[4 * j + 3] * W[4 * j + 3])));
            wg_fence();
            wgmma_k64(P, h, dW2 + 512);
            wgmma_first(W, rf, dWR + 128);
            wg_commit();
            SPLIT(6);
            asm volatile("cp.async.wait_group 2;" ::: "memory");
            __syncwarp();
            uint32_t v[4][16];
#pragma unroll
            for (int i = 0; i < NPRE; i++) lds128((vrow ^ (64 * (i & 1))) + 2048 + 1024 * (i >> 2) + 3072 * ((i >> 1) & 1), v[1 + (i >> 2)] + 4 * (i & 3));
            wg_wait<0>();
            fence_regs(P); fence_regs(W);
#pragma unroll
            for (int j = 0; j < 8; j++) {
                m[j] = pack2(P[4 * j] * W[4 * j], P[4 * j + 1] * W[4 * j + 1]);
                m[8 + j] = pack2(P[4 * j + 2] * W[4 * j + 2], P[4 * j + 3] * W[4 * j + 3]);
            }
#pragma unroll
            for (int i = NPRE; i < 12; i++) lds128((vrow ^ (64 * (i & 1))) + 2048 + 1024 * (i >> 2) + 3072 * ((i >> 1) & 1), v[1 + (i >> 2)] + 4 * (i & 3));
            sources(c1);
            const uint32_t node = lds32(sb + SN_OFF + 4 + (((c0 >> 16) | g32) >> 2));
            __syncwarp();
            load_v(IntC<1>{});
#pragma unroll
            for (int k = 1; k < 4; k++)
#pragma unroll
                for (int j = 0; j < 8; j++) acc[8 * k + j] = hfma2(m[8 + j], v[k][8 + j], hfma2(m[j], v[k][j], acc[8 * k + j]));
            finish(c0, node);
            ctl += 64;
            c0 = c1;
            c1 = c2;
        }
        asm volatile("cp.async.wait_all;" ::: "memory");
        TRW(ctl);
        TSX(11, 0); TSX(12, 128); TSX(13, 256);
    } else {
        asm volatile("setmaxnreg.dec.sync.aligned.u32 %0;" ::"n"(REG_H));
        const int lane = fresh_lane();
        const uint32_t chunk = sb + (lane & 8 ? (lane & 4 ? SN_OFF : SD_OFF) + (lane & 3) * 16 : SREC_OFF + (lane & 7) * 16), pitch = lane & 8 ? 64 : 128;
        if (warp == 12) {
#pragma unroll 1
            for (int i = 0; i < (int)misc[2]; i++) {
                const uint32_t n = reinterpret_cast<const uint32_t*>(smem + SCNT_OFF)[i] * 32 + lane;
                reinterpret_cast<uint4*>(p.out)[n] = reinterpret_cast<const uint4*>(p.sv)[n];
            }
#pragma unroll 1
            for (int i = lane >> 4; i < give; i += 2) {
                uint32_t x[4];
                lds128(chunk + (ng - 1 - i) * pitch, x);
                p.g->pool[(b * GIVE + i) * 16 + (lane & 15)] = make_uint4(x[0], x[1], x[2], x[3]);
            }
            __threadfence();
            __syncwarp();
            if (lane == 0) {
                asm volatile("st.relaxed.gpu.global.u32 [%0], %1;" ::"l"(p.g->ready + b), "r"(~epoch) : "memory");
                mbar_arrive(sb + BAR_OFF + 16 + 8 * FLIGHT);
            }
        }
        if (warp == 15) {
            int k = lane < 4 * NWG ? lane : 255, next = 4 * NWG, j = 0, mine = ng - give, end = -1, take = 0;
            uint32_t busy, at = sb + CTL_OFF + 4 * lane, from = 0;
#pragma unroll 1
            do {
                if (next > mine && end < 0) {
                    end = mine = ng;
                    const int peer = b % 5 + 5 * lane;
                    uint32_t x = 255;
                    int it = 0;
                    if (peer < G) {
#pragma unroll 1
                        do {
                            asm volatile("ld.relaxed.gpu.global.u32 %0, [%1];" : "=r"(x) : "l"(p.g->rows + peer) : "memory");
                            if (++it > (1 << 22)) __trap();
                        } while ((x >> 16) != (~epoch & 0xFFFFu));
                    }
                    const int r = x & 255, n = __popc(__ballot_sync(0xffffffffu, r != 255));
                    const int level = min(((__reduce_add_sync(0xffffffffu, r != 255 ? r : 0) + n - 1) / max(n, 1) + 3) & ~3, MAXROW);
                    const uint32_t ed = r > level ? min(r - level, (int)(x >> 8) & 255) : min(level - r, ROOM) << 16;
                    uint32_t z = ed;
#pragma unroll
                    for (int o = 1; o < 32; o <<= 1) {
                        const uint32_t y = __shfl_up_sync(0xffffffffu, z, o);
                        if (lane >= o) z += y;
                    }
                    const uint32_t all = __shfl_sync(0xffffffffu, z, 31), moved = min(all & 0xFFFFu, all >> 16);
                    const uint32_t me = __shfl_sync(0xffffffffu, ed, b / 5), mz = __shfl_sync(0xffffffffu, z, b / 5) - me;
                    end = mine = ng - (min((mz + me) & 0xFFFFu, moved) - min(mz & 0xFFFFu, moved));
#pragma unroll 1
                    for (uint32_t u = mz >> 16; u < min((mz + me) >> 16, moved); u++, take++) {
                        const int f = __popc(__ballot_sync(0xffffffffu, (z & 0xFFFFu) <= u));
                        const uint32_t q = u - (__shfl_sync(0xffffffffu, z - ed, f) & 0xFFFFu);
                        if (lane == take) from = (b % 5 + 5 * f) << 8 | q;
                    }
                }
                if (next > mine && take) {
                    if (lane < take) {
                        uint32_t x;
                        int it = 0;
#pragma unroll 1
                        do {
                            asm volatile("ld.acquire.gpu.global.u32 %0, [%1];" : "=r"(x) : "l"(p.g->ready + (from >> 8)) : "memory");
                            if (++it > (1 << 22)) __trap();
                        } while (x != ~epoch);
                    }
                    __syncwarp();
#pragma unroll 1
                    for (end += take; take--;) {
                        const uint32_t f = __shfl_sync(0xffffffffu, from, take);
                        if (lane < 16)
                            asm volatile("cp.async.cg.shared.global [%0], [%1], 16;" ::"r"(chunk + (MAXROW - 1 - take) * pitch),
                                         "l"(p.g->pool + ((f >> 8) * GIVE + (f & 255)) * 16 + lane) : "memory");
                    }
                    take = 0;
                    asm volatile("cp.async.wait_all;" ::: "memory");
                    __threadfence_block();
                    __syncwarp();
                }
                const bool has = k < (end < 0 ? mine : end);
                const uint32_t i = k < mine ? k : MAXROW - 1 + mine - k, x = __shfl_sync(0xffffffffu, pk, j);
                const bool close = has && i >= (x >> 24);
                busy = __ballot_sync(0xffffffffu, has);
                const uint32_t m = __ballot_sync(0xffffffffu, close);
                uint32_t c = has ? ((x & 0xFF00) + i * 0x1000100) | (j ? 0u : ST_START) | (close ? ST_CLOSE : 0u) : MAXROW * 256;
                if (!(busy >> (lane & 12))) c |= 0x80000000u;
                c |= busy >> ((lane & 12) + 4) ? (lane & 12) * 4 + 32 : 16;
                sts32_if(at, c, lane < 16 || !busy);
                j = close ? 0 : j + 1;
                k = close ? next + __popc(m & ((1u << lane) - 1)) : k;
                next += __popc(m);
                at += 64;
            } while (busy);
        }
        if (warp == 15) mbar_wait(sb + BAR_OFF + 16 + 8 * FLIGHT, 0);
        else if (warp != 12) __nanosleep(ZDELAY);
        const int zend = misc[32] + misc[64];
#pragma unroll 1
        for (;;) {
            int r = 0;
            if (lane == 0) r = atomicAdd(&misc[4], 4u);
            r = __shfl_sync(0xffffffffu, r, 0) + 8 * ng;
            if (r >= zend) break;
            uint4 v[4];
            uint32_t n[4];
#pragma unroll
            for (int i = 0; i < 4; i++) {
                n[i] = reinterpret_cast<const uint32_t*>(smem + SN_OFF)[min(r + i, zend - 1) * 2 + 1] * 32 + lane;
                v[i] = __ldcs(reinterpret_cast<const uint4*>(p.sv) + n[i]);
            }
#pragma unroll
            for (int i = 0; i < 4; i++)
                if (r + i < zend) __stcs(reinterpret_cast<uint4*>(p.out) + n[i], v[i]);
        }
        static_assert(FLIGHT <= 4, "drain");
        drain(warp & 3);
        asm volatile("cp.async.wait_all;" ::: "memory");
        TSX(14, 384); TSX(15, 480); TSX(16, 416);
    }
}

}

extern "C" void kernel_launch(void* const* d_in, const int* in_sizes, int n_in, void* d_out, int out_size) {
    static int s_G = 0;
    static void* s_scratch = nullptr;
    const int N = in_sizes[0] / 256, E = in_sizes[2];
    if (s_G == 0) {
        cudaFuncSetAttribute(painn_kernel<0, 0, 0>, cudaFuncAttributeMaxDynamicSharedMemorySize, SMEM_BYTES);
        cudaFuncSetAttribute(painn_kernel<50000, 800000, 132>, cudaFuncAttributeMaxDynamicSharedMemorySize, SMEM_BYTES);
        int dev = 0, sms = 0, occ = 0;
        cudaGetDevice(&dev);
        cudaDeviceGetAttribute(&sms, cudaDevAttrMultiProcessorCount, dev);
        cudaOccupancyMaxActiveBlocksPerMultiprocessor(&occ, painn_kernel<0, 0, 0>, THREADS, SMEM_BYTES);
        cudaGetSymbolAddress(&s_scratch, g_scratch);
        s_G = occ >= 1 ? (sms < MAXG ? sms : MAXG) : 0;
    }
    if (s_G == 0 || N > TABLE_MAXN || N > s_G * MAXNPC || (s_G - 1) * ((N + s_G - 1) / s_G) >= N || E > MAXE || E < 4 * MAXG * MAXG) return;
    Params p;
    p.g = (Scratch*)s_scratch;
    p.sv = (const __nv_bfloat16*)d_in[0];
    p.pos = (const __nv_bfloat16*)d_in[1];
    p.src = (const int*)d_in[2];
    p.dst = (const int*)d_in[3];
    p.freqs = (const __nv_bfloat16*)d_in[4];
    p.w1 = (const __nv_bfloat16*)d_in[5];
    p.w2 = (const __nv_bfloat16*)d_in[6];
    p.wr = (const __nv_bfloat16*)d_in[7];
    p.out = (__nv_bfloat16*)d_out;
    p.desc0 = (uint64_t)(SB >> 4) | ((uint64_t)1 << 16) | ((uint64_t)64 << 32) | ((uint64_t)1 << 62);
    p.N = N; p.E = E; p.G = s_G;
    p.NPC = (N + s_G - 1) / s_G;
    p.magic = (uint32_t)(((1ull << 32) + p.NPC - 1) / p.NPC);
    p.gpc = ((E >> 2) + s_G - 1) / s_G;
    p.odd_edges = (E & 3) != 0 || p.gpc > 3 * THREADS;
    if (N == 50000 && E == 800000 && s_G == 132) painn_kernel<50000, 800000, 132><<<s_G, THREADS, SMEM_BYTES, cudaStreamPerThread>>>(p);
    else painn_kernel<0, 0, 0><<<s_G, THREADS, SMEM_BYTES, cudaStreamPerThread>>>(p);
}
```

```cpp
#include <cuda_runtime.h>
#include <cuda_bf16.h>
#include <stdint.h>

namespace {

constexpr int NWG = 3;
constexpr int REG_C = 160, REG_H = 32;
constexpr int SPL = 10;
constexpr int GIVE = 12, ROOM = 4;
constexpr int BIG = 5;
constexpr int CUT = 7;
constexpr int HDELAY = 150;
constexpr int TOUCH = 4, FLIGHT = 4;
constexpr int NPRE = 5;
constexpr int PDELAY = 150;
constexpr int ZDELAY = 1200;
constexpr int THREADS = 512;
constexpr int MAXG = 136;
constexpr int MAXROW = 96;
constexpr int TMAX = MAXROW / 12 + 18;
constexpr int MAXNPC = 480;
constexpr int MAXE = 1 << 20;

constexpr int W2_OFF = 8192;
constexpr int WR_OFF = 32768;
constexpr int RING_OFF = 38912;
constexpr int SREC_OFF = RING_OFF + 4 * NWG * 12288;
constexpr int SD_OFF = SREC_OFF + (MAXROW + 1) * 128 + 16;
constexpr int SN_OFF = SD_OFF + (MAXROW + 1) * 64 + 16;
constexpr int CTL_OFF = SN_OFF + (MAXROW + 1) * 64 + 16;
constexpr int TABLE_MAXN = 50176;
constexpr int STAGE_OFF = TABLE_MAXN * 4;
constexpr int SCNT_OFF = STAGE_OFF + MAXG * 128;
constexpr int PACK_OFF = RING_OFF + 6144;
constexpr int NCNT_OFF = SCNT_OFF + 768;
constexpr int OPOS_OFF = NCNT_OFF + 2048;
constexpr int BAR_OFF = OPOS_OFF + 4096;
constexpr int MISC_OFF = BAR_OFF + 128;
constexpr int FREQ_OFF = MISC_OFF + 512;
constexpr int DUMMY_OFF = (FREQ_OFF + 128 + 127) / 128 * 128;
constexpr int SMEM_BYTES = DUMMY_OFF + 4096;
static_assert(CTL_OFF + 64 * TMAX <= STAGE_OFF + 32 * THREADS && STAGE_OFF - SREC_OFF <= 32 * THREADS && 4 * (MAXG + 32) <= 768, "smem map");
static_assert(GIVE < 16 && MAXG <= 160, "levelling");
static_assert(SMEM_BYTES <= 232448 && BAR_OFF % 8 == 0 && RING_OFF % 128 == 0 && SREC_OFF % 128 == 0 && (MAXG + 14) / 15 <= 12, "smem map");

constexpr uint32_t PAY_INVALID = 0x3FFFFFFu;
constexpr uint32_t PAY_MARK = 0x3FFFDFFu;
constexpr uint32_t NODE_SPLIT = 0x40000000u;
constexpr uint32_t ST_START = 1, ST_CLOSE = 2;
constexpr float QINVP = 9.0f / 510.0f;
constexpr uint32_t QTHRESH = 2134;
constexpr uint32_t QSURE = 1870;

struct Scratch {
    unsigned sync[32];
    uint4 table[TABLE_MAXN / 4];
    uint4 wimg[RING_OFF / 16];
    uint2 pos8[TABLE_MAXN];
    uint4 xbuf[MAXG * MAXG * 8 + 3 * THREADS];
    uint4 pool[MAXG * GIVE * 16];
    unsigned rows[160];
    unsigned ready[MAXG];
    int ovfcnt[MAXG];
    int2 ovf[MAXE + 8 * MAXG + 8];
};
__device__ __align__(128) Scratch g_scratch;

struct Params {
    const __nv_bfloat16* pos;
    Scratch* g;
    const int* src;
    const int* dst;
    int N, NPC, E, gpc;
    const __nv_bfloat16* w2;
    const __nv_bfloat16* wr;
    const __nv_bfloat16* w1;
    const __nv_bfloat16* freqs;
    const __nv_bfloat16* sv;
    __nv_bfloat16* out;
    uint64_t desc0;
    int G;
    uint32_t magic;
    int odd_edges;
};
constexpr uint32_t SB = 1024;

#define TSX(i, thr)
#define TS0(i) TSX(i, 0)
#define TRW(ctl)

__device__ __forceinline__ uint32_t smem_u32(const void* p) { return (uint32_t)__cvta_generic_to_shared(p); }
__device__ __forceinline__ void mbar_init(uint32_t bar, uint32_t cnt) {
    asm volatile("mbarrier.init.shared::cta.b64 [%0], %1;" ::"r"(bar), "r"(cnt) : "memory");
}
__device__ __forceinline__ void mbar_arrive(uint32_t bar) {
    asm volatile("mbarrier.arrive.shared::cta.b64 _, [%0];" ::"r"(bar) : "memory");
}
__device__ __forceinline__ void mbar_expect_tx(uint32_t bar, uint32_t bytes) {
    asm volatile("mbarrier.arrive.expect_tx.shared::cta.b64 _, [%0], %1;" ::"r"(bar), "r"(bytes) : "memory");
}
__device__ __forceinline__ void mbar_wait(uint32_t bar, uint32_t parity) {
    uint32_t ok;
    int it = 0;
    do {
        asm volatile(
            "{\n.reg .pred p;\n"
            "mbarrier.try_wait.parity.shared::cta.b64 p, [%1], %2, 2000;\n"
            "selp.u32 %0, 1, 0, p;\n}\n"
            : "=r"(ok) : "r"(bar), "r"(parity) : "memory");
        if (++it > (1 << 20)) __trap();
    } while (!ok);
}
__device__ __forceinline__ uint32_t mbar_test(uint32_t bar, uint32_t parity) {
    uint32_t ok;
    asm volatile("{\n.reg .pred p;\nmbarrier.test_wait.parity.shared::cta.b64 p, [%1], %2;\nselp.u32 %0, 1, 0, p;\n}\n"
                 : "=r"(ok) : "r"(bar), "r"(parity) : "memory");
    return ok;
}
__device__ __forceinline__ uint32_t pin(uint32_t x) {
    uint32_t r;
    asm volatile("shfl.sync.bfly.b32 %0, %1, 0, 31, -1;" : "=r"(r) : "r"(x));
    return r;
}
__device__ __forceinline__ void bulk_g2s(uint32_t dst, const void* src, uint32_t bytes, uint32_t bar) {
    asm volatile("cp.async.bulk.shared::cluster.global.mbarrier::complete_tx::bytes [%0], [%1], %2, [%3];"
                 ::"r"(dst), "l"(src), "r"(bytes), "r"(bar) : "memory");
}
__device__ __forceinline__ void ldsm4(uint32_t addr, uint32_t* r) {
    asm volatile("ldmatrix.sync.aligned.m8n8.x4.shared.b16 {%0,%1,%2,%3}, [%4];"
                 : "=r"(r[0]), "=r"(r[1]), "=r"(r[2]), "=r"(r[3]) : "r"(addr) : "memory");
}
__device__ __forceinline__ uint32_t pack2(float lo, float hi) {
    uint32_t r;
    asm("cvt.rn.bf16x2.f32 %0, %1, %2;" : "=r"(r) : "f"(hi), "f"(lo));
    return r;
}
__device__ __forceinline__ float bf_lo(uint32_t w) { return __uint_as_float(w << 16); }
__device__ __forceinline__ float bf_hi(uint32_t w) { return __uint_as_float(w & 0xFFFF0000u); }
__device__ __forceinline__ float rbf16(float x) { return __uint_as_float(pack2(0.f, x)); }
__device__ __forceinline__ uint32_t hmul2(uint32_t a, uint32_t b) {
    uint32_t r;
    asm("mul.rn.bf16x2 %0, %1, %2;" : "=r"(r) : "r"(a), "r"(b));
    return r;
}
__device__ __forceinline__ uint32_t hfma2(uint32_t a, uint32_t b, uint32_t c) {
    uint32_t r;
    asm("fma.rn.bf16x2 %0, %1, %2, %3;" : "=r"(r) : "r"(a), "r"(b), "r"(c));
    return r;
}
__device__ __forceinline__ uint32_t hfma2_lo(uint32_t a, uint32_t b, uint32_t c) {
    uint32_t r;
    asm("{\n.reg .b16 l, h;\n.reg .b32 t;\nmov.b32 {l, h}, %2;\nmov.b32 t, {l, l};\nfma.rn.bf16x2 %0, %1, t, %3;\n}\n" : "=r"(r) : "r"(a), "r"(b), "r"(c));
    return r;
}
__device__ __forceinline__ uint32_t hfma2_hi(uint32_t a, uint32_t b, uint32_t c) {
    uint32_t r;
    asm("{\n.reg .b16 l, h;\n.reg .b32 t;\nmov.b32 {l, h}, %2;\nmov.b32 t, {h, h};\nfma.rn.bf16x2 %0, %1, t, %3;\n}\n" : "=r"(r) : "r"(a), "r"(b), "r"(c));
    return r;
}
__device__ __forceinline__ uint32_t hadd2(uint32_t a, uint32_t b) {
    uint32_t r;
    asm("add.rn.bf16x2 %0, %1, %2;" : "=r"(r) : "r"(a), "r"(b));
    return r;
}
__device__ __forceinline__ uint32_t hsub2(uint32_t a, uint32_t b) {
    uint32_t r;
    asm("sub.rn.bf16x2 %0, %1, %2;" : "=r"(r) : "r"(a), "r"(b));
    return r;
}
__device__ __forceinline__ float tanh_fast(float x) {
    float r;
    asm("tanh.approx.f32 %0, %1;" : "=f"(r) : "f"(x));
    return r;
}
__device__ __forceinline__ void wg_fence() { asm volatile("wgmma.fence.sync.aligned;" ::: "memory"); }
__device__ __forceinline__ void wg_commit() { asm volatile("wgmma.commit_group.sync.aligned;" ::: "memory"); }
template <int N>
__device__ __forceinline__ void wg_wait() { asm volatile("wgmma.wait_group.sync.aligned %0;" ::"n"(N) : "memory"); }

#define WG_REGS "{%0,%1,%2,%3,%4,%5,%6,%7,%8,%9,%10,%11,%12,%13,%14,%15,%16,%17,%18,%19,%20,%21,%22,%23,%24,%25,%26,%27,%28,%29,%30,%31}"
#define WG_OPS(c) c(d[0]), c(d[1]), c(d[2]), c(d[3]), c(d[4]), c(d[5]), c(d[6]), c(d[7]), c(d[8]), c(d[9]), c(d[10]), \
    c(d[11]), c(d[12]), c(d[13]), c(d[14]), c(d[15]), c(d[16]), c(d[17]), c(d[18]), c(d[19]), c(d[20]), c(d[21]),     \
    c(d[22]), c(d[23]), c(d[24]), c(d[25]), c(d[26]), c(d[27]), c(d[28]), c(d[29]), c(d[30]), c(d[31])
__device__ __forceinline__ void wgmma_first(float* d, const uint32_t* a, uint64_t desc) {
    asm volatile("wgmma.mma_async.sync.aligned.m64n64k16.f32.bf16.bf16 " WG_REGS ", {%32,%33,%34,%35}, %36, 0, 1, 1, 1;"
                 : WG_OPS("+f") : "r"(a[0]), "r"(a[1]), "r"(a[2]), "r"(a[3]), "l"(desc));
}
__device__ __forceinline__ void wgmma_acc(float* d, const uint32_t* a, uint64_t desc) {
    asm volatile("wgmma.mma_async.sync.aligned.m64n64k16.f32.bf16.bf16 " WG_REGS ", {%32,%33,%34,%35}, %36, 1, 1, 1, 1;"
                 : WG_OPS("+f") : "r"(a[0]), "r"(a[1]), "r"(a[2]), "r"(a[3]), "l"(desc));
}
__device__ __forceinline__ void wgmma_k64(float* d, const uint32_t* a, uint64_t desc) {
    wgmma_first(d, a, desc);
    wgmma_acc(d, a + 4, desc + 128);
    wgmma_acc(d, a + 8, desc + 256);
    wgmma_acc(d, a + 12, desc + 384);
}
__device__ __forceinline__ void fence_regs(float* d) { asm volatile("" : WG_OPS("+f")::"memory"); }
__device__ __forceinline__ uint32_t qaxis(float x) {
    const float u = fmaf(x, QINVP, 0.25f);
    const float f = u - ((u + 12582912.f) - 12582912.f);
    return __float_as_uint(fmaf(fabsf(f), 510.f, 12582912.f));
}
__device__ __forceinline__ uint32_t qcode(float x, float y, float z, uint32_t tx) {
    return __byte_perm(__byte_perm(qaxis(x), qaxis(y), 0x3340), qaxis(z), 0x3410) ^ tx;
}
__device__ __forceinline__ bool near_test(uint32_t ca, uint32_t cb, uint32_t tag24, uint32_t& q) {
    const uint32_t D = __vabsdiffu4(ca, cb);
    q = __dp4a(D, D, 0x7FFFFFFFu - QSURE);
    return q <= 0x7FFFFFFFu - QSURE + QTHRESH || ((ca ^ tag24) | (cb ^ tag24)) >= 0x1000000u;
}
__device__ __forceinline__ bool inside(uint32_t rxy, uint32_t rz) {
    const uint32_t qxy = hmul2(rxy, rxy), qz = hmul2(rz, rz);
    return bf_lo(qxy) + bf_hi(qxy) + bf_lo(qz) < 23.9375f;
}

__device__ __forceinline__ uint32_t lds32(uint32_t addr) {
    uint32_t r;
    asm volatile("ld.shared.u32 %0, [%1];" : "=r"(r) : "r"(addr));
    return r;
}
__device__ __forceinline__ void sts32_if(uint32_t addr, uint32_t v, bool c) {
    asm volatile("{\n.reg .pred p;\nsetp.ne.u32 p, %2, 0;\n@p st.shared.u32 [%0], %1;\n}\n" ::"r"(addr), "r"(v), "r"((uint32_t)c) : "memory");
}
__device__ __forceinline__ void stg128_if(void* ptr, uint4 v, bool c) {
    asm volatile("{\n.reg .pred p;\nsetp.ne.u32 p, %5, 0;\n@p st.relaxed.gpu.global.v4.u32 [%0], {%1,%2,%3,%4};\n}\n"
                 ::"l"(ptr), "r"(v.x), "r"(v.y), "r"(v.z), "r"(v.w), "r"((uint32_t)c) : "memory");
}
__device__ __forceinline__ void lds128(uint32_t addr, uint32_t* r) {
    asm volatile("ld.shared.v4.u32 {%0,%1,%2,%3}, [%4];" : "=r"(r[0]), "=r"(r[1]), "=r"(r[2]), "=r"(r[3]) : "r"(addr) : "memory");
}
template <int NP, int HI, int PAD = 1>
__device__ __forceinline__ void gather(uint32_t dst, const void* base, uint32_t c, uint32_t e) {
#define GATHER_HEAD "{\n.reg .pred p;\n.reg .b32 n;\n.reg .b64 a;\nprmt.b32 n, %2, 0, %3;\nsetp.ne.u32 p, n, 0xFFFF;\nmad.lo.u32 n, n, 512, %4;\nmad.wide.u32 a, n, 1, %1;\n"
#define GATHER_1(P) P "cp.async.cg.shared.global [%0], [a], 16;\n}\n"
#define GATHER_3(P) P "cp.async.cg.shared.global [%0], [a + 128], 16;\n" P "cp.async.cg.shared.global [%0 + 1024], [a + 256], 16;\n" \
                    P "cp.async.cg.shared.global [%0 + 2048], [a + 384], 16;\n}\n"
#define GATHER_ARGS(z) ::"r"(dst), "l"(base), "r"(e), "n"((HI ? 0x32 : 0x10) + z), "r"(c) : "memory"
    if constexpr (NP == 1 && PAD) asm volatile(GATHER_HEAD GATHER_1("@p ") GATHER_ARGS(0x4400));
    if constexpr (NP == 1 && !PAD) asm volatile(GATHER_HEAD GATHER_1("") GATHER_ARGS(0x4400));
    if constexpr (NP == 3 && PAD) asm volatile(GATHER_HEAD GATHER_3("@p ") GATHER_ARGS(0x5500));
    if constexpr (NP == 3 && !PAD) asm volatile(GATHER_HEAD GATHER_3("") GATHER_ARGS(0x4400));
    if constexpr (NP == 4)
        asm volatile(GATHER_HEAD "setp.ge.u32 p, %2, 0x40000000;\ncp.async.cg.shared.global [%0], [a], 16, p;\ncp.async.cg.shared.global [%0 + 1024], [a + 128], 16, p;\n"
                     "cp.async.cg.shared.global [%0 + 2048], [a + 256], 16, p;\ncp.async.cg.shared.global [%0 + 3072], [a + 384], 16, p;\n}\n" GATHER_ARGS(0x4400));
}
__device__ __forceinline__ void cp_commit() { asm volatile("cp.async.commit_group;" ::: "memory"); }
__device__ __forceinline__ void cp_wait1() { asm volatile("cp.async.wait_group 1;" ::: "memory"); }
__device__ __forceinline__ uint32_t hmul2_lo(uint32_t a, uint32_t b) {
    uint32_t r;
    asm("{\n.reg .b16 l, h;\n.reg .b32 t;\nmov.b32 {l, h}, %2;\nmov.b32 t, {l, l};\nmul.rn.bf16x2 %0, %1, t;\n}\n" : "=r"(r) : "r"(a), "r"(b));
    return r;
}
__device__ __forceinline__ void lds2_if(uint32_t a0, uint32_t a1, uint32_t* r, uint32_t c) {
    asm volatile("{\n.reg .pred p;\nsetp.ne.u32 p, %10, 0;\n@p ld.shared.v4.u32 {%0,%1,%2,%3}, [%8];\n@p ld.shared.v4.u32 {%4,%5,%6,%7}, [%9];\n}\n"
                 : "+r"(r[0]), "+r"(r[1]), "+r"(r[2]), "+r"(r[3]), "+r"(r[4]), "+r"(r[5]), "+r"(r[6]), "+r"(r[7])
                 : "r"(a0), "r"(a1), "r"(c) : "memory");
}
__device__ __forceinline__ int fresh_lane() {
    int l;
    asm volatile("mov.u32 %0, %%laneid;" : "=r"(l));
    return l;
}

__device__ __forceinline__ void cold_edges(unsigned char* smem, const Params& p, int lo, int hi, uint32_t tag) {
#pragma unroll 1
    for (int e = lo + threadIdx.x; e < hi; e += THREADS) {
        const int s = p.src[e], d = p.dst[e];
        uint32_t q;
        if (near_test(reinterpret_cast<const uint32_t*>(smem)[s], reinterpret_cast<const uint32_t*>(smem)[d], tag << 24, q)) {
            const uint32_t own = __umulhi((uint32_t)d, p.magic);
            const uint32_t slot4 = atomicAdd(reinterpret_cast<uint32_t*>(smem + SCNT_OFF) + own, 4u);
            uint32_t* line = reinterpret_cast<uint32_t*>(smem + STAGE_OFF) + own * 32;
            if (slot4 < 124) {
                line[(slot4 >> 2) ^ ((own & 7) << 2)] = ((uint32_t)s << 15) + ((uint32_t)(d - own * p.NPC) << 6) + tag + (q & 0x80000000u);
            } else {
                uint32_t o = atomicAdd(reinterpret_cast<uint32_t*>(smem + MISC_OFF) + 16, 1u);
                p.g->ovf[(size_t)blockIdx.x * (4 * p.gpc + 4) + o] = make_int2(s, d);
                line[31 ^ ((own & 7) << 2)] = (PAY_MARK << 6) | tag;
            }
        }
    }
}
__device__ __forceinline__ void cold_filter(unsigned char* smem, const Params& p, int e0, int e1, uint32_t tag, int redo) {
    if (redo) {
        if (threadIdx.x < MAXG) reinterpret_cast<uint32_t*>(smem + SCNT_OFF)[threadIdx.x] = 0;
        __syncthreads();
    }
    cold_edges(smem, p, redo ? 4 * e0 : 4 * (e0 + 3 * THREADS), 4 * e1, tag);
    if (blockIdx.x == 0) cold_edges(smem, p, p.E & ~3, p.E, tag);
    __syncthreads();
    if (threadIdx.x == 0) p.g->ovfcnt[blockIdx.x] = reinterpret_cast<uint32_t*>(smem + MISC_OFF)[16];
    __threadfence();
    __syncthreads();
}
__device__ __forceinline__ uint3 geometry(uint32_t rxy, uint32_t rz) {
    const uint32_t qxy = hmul2(rxy, rxy), qz = hmul2(rz, rz);
    float d, id;
    asm("sqrt.approx.ftz.f32 %0, %1;" : "=f"(d) : "f"(rbf16(rbf16(bf_lo(qxy) + bf_hi(qxy) + bf_lo(qz)) + 1e-8f)));
    d = rbf16(d);
    asm("rcp.approx.ftz.f32 %0, %1;" : "=f"(id) : "f"(d));
    const float cs = rbf16(__cosf(rbf16(rbf16(3.14159265358979f * d) * 0.2f)));
    const uint32_t zs = pack2(bf_lo(rz) * id, 0.5f * rbf16(cs + 1.0f) * id);
    return d < 5.0f ? make_uint3(pack2(bf_lo(rxy) * id, bf_hi(rxy) * id), zs, __byte_perm(__float_as_uint(d), zs, 0x7632)) : make_uint3(0, 0, 0);
}
__device__ __forceinline__ void cold_messages(unsigned char* smem, const Params& p, int nn) {
    const int nbase = blockIdx.x * p.NPC, lane = threadIdx.x & 31;
    const uint32_t* box = reinterpret_cast<const uint32_t*>(p.g->xbuf) + blockIdx.x * p.G * 32;
    uint32_t* w = reinterpret_cast<uint32_t*>(smem + RING_OFF);
#pragma unroll 1
    for (int i = threadIdx.x; i < 9728; i += THREADS)
        w[i] = i < 2048 ? reinterpret_cast<const uint32_t*>(p.w1)[i] : i < 8192 ? reinterpret_cast<const uint32_t*>(p.w2)[i - 2048] : reinterpret_cast<const uint32_t*>(p.wr)[i - 8192];
#pragma unroll 1
    for (int i = threadIdx.x; i < nn * 32; i += THREADS) reinterpret_cast<uint4*>(p.out)[nbase * 32 + i] = reinterpret_cast<const uint4*>(p.sv)[nbase * 32 + i];
    __threadfence();
    __syncthreads();
    const float freq = __bfloat162float(p.freqs[lane & 15]);
#pragma unroll 1
    for (int m = -1; m < p.G; m++) {
        const int cnt = m < 0 ? p.G * 32 : (__ldcg(box + m * 32 + 31) >> 6) == PAY_MARK ? __ldcg(&p.g->ovfcnt[m]) : 0;
#pragma unroll 1
        for (int i = threadIdx.x; i - lane < cnt; i += THREADS) {
            int2 e = make_int2(0, -1);
            if (i < cnt) {
                if (m < 0) {
                    const uint32_t x = __ldcg(box + i);
                    e = make_int2((x >> 15) & 0xFFFFu, nbase + ((x >> 6) & 511u));
                } else {
                    e = __ldcg(p.g->ovf + (size_t)m * (4 * p.gpc + 4) + i);
                }
            }
            bool in = (uint32_t)(e.y - nbase) < (uint32_t)nn;
            uint3 geo = make_uint3(0, 0, 0);
            if (in) {
                const uint2 ps = __ldcg(p.g->pos8 + e.x), pd = __ldcg(p.g->pos8 + e.y);
                const uint32_t rxy = hsub2(ps.x, pd.x), rz = hsub2(ps.y, pd.y);
                in = inside(rxy, rz);
                geo = geometry(rxy, rz);
            }
#pragma unroll 1
            for (uint32_t todo = __ballot_sync(0xffffffffu, in); todo; todo &= todo - 1) {
                const int l = __ffs(todo) - 1;
                const uint32_t* row = reinterpret_cast<const uint32_t*>(p.sv) + (size_t)__shfl_sync(0xffffffffu, e.x, l) * 128 + lane;
                uint32_t* orow = reinterpret_cast<uint32_t*>(p.out) + (size_t)__shfl_sync(0xffffffffu, e.y, l) * 128 + lane;
                const uint32_t gx = __shfl_sync(0xffffffffu, geo.x, l), gy = __shfl_sync(0xffffffffu, geo.y, l);
                const float rb = rbf16(__sinf(rbf16(bf_lo(__shfl_sync(0xffffffffu, geo.z, l)) * freq)) * bf_hi(gy));
                uint32_t x = row[0];
                float a[12] = {0, 0, 0, 0, 0, 0, 0, 0, 0, 0, 0, 0};
#pragma unroll 2
                for (int k = 0; k < 64; k++) {
                    const uint32_t u = __shfl_sync(0xffffffffu, x, k >> 1), ww = w[k * 32 + lane];
                    const float f = k & 1 ? bf_hi(u) : bf_lo(u);
                    a[0] = fmaf(f, bf_lo(ww), a[0]); a[1] = fmaf(f, bf_hi(ww), a[1]);
                }
                x = pack2(0.5f * fmaf(a[0], tanh_fast(0.5f * a[0]), a[0]), 0.5f * fmaf(a[1], tanh_fast(0.5f * a[1]), a[1]));
                a[0] = a[1] = 0.f;
#pragma unroll 2
                for (int k = 0; k < 64; k++) {
                    const uint32_t u = __shfl_sync(0xffffffffu, x, k >> 1);
                    const float f = k & 1 ? bf_hi(u) : bf_lo(u), r = __shfl_sync(0xffffffffu, rb, k & 15);
#pragma unroll
                    for (int c = 0; c < 3; c++) {
                        const uint32_t ww = w[2048 + k * 96 + c * 32 + lane], wr = k < 16 ? w[8192 + k * 96 + c * 32 + lane] : 0u;
                        a[2 * c] = fmaf(f, bf_lo(ww), a[2 * c]); a[2 * c + 1] = fmaf(f, bf_hi(ww), a[2 * c + 1]);
                        a[6 + 2 * c] = fmaf(r, bf_lo(wr), a[6 + 2 * c]); a[7 + 2 * c] = fmaf(r, bf_hi(wr), a[7 + 2 * c]);
                    }
                }
                const uint32_t mv = pack2(a[2] * a[8], a[3] * a[9]), mr = pack2(a[4] * a[10], a[5] * a[11]);
                const uint32_t o[4] = {pack2(a[0] * a[6], a[1] * a[7]), hfma2_lo(mr, gx, hmul2(mv, row[32])), hfma2_hi(mr, gx, hmul2(mv, row[64])),
                                       hfma2_lo(mr, gy, hmul2(mv, row[96]))};
#pragma unroll
                for (int c = 0; c < 4; c++) asm volatile("red.global.add.noftz.bf16x2 [%0], %1;" ::"l"(orow + 32 * c), "r"(o[c]) : "memory");
            }
        }
    }
}

#define SPLIT(k) asm volatile("{\n.reg .pred p;\nsetp.eq.u32 p, %0, %1;\n@p trap;\n}" ::"r"(c0), "n"(0x70000 + k) : "memory")
#define PIN8(a) asm volatile("" : "+r"((a)[0]), "+r"((a)[1]), "+r"((a)[2]), "+r"((a)[3]), "+r"((a)[4]), "+r"((a)[5]), "+r"((a)[6]), "+r"((a)[7]))
template <int V> struct IntC { static constexpr int value = V; };

template <int CN, int CE, int CG>
__global__ void __launch_bounds__(THREADS, 1) painn_kernel(const __grid_constant__ Params p) {
    extern __shared__ __align__(1024) unsigned char smem_dyn[];
    unsigned char* const smem = static_cast<unsigned char*>(__cvta_shared_to_generic(SB));
    constexpr uint32_t sb = SB;
    const int tid = threadIdx.x, lane = tid & 31;
    const int warp = __shfl_sync(0xffffffffu, tid >> 5, 0);
    constexpr int CNPC = CG ? (CN + CG - 1) / CG : 1, CGPC = CG ? (CE / 4 + CG - 1) / CG : 1;
    const int b = blockIdx.x, G = CG ? CG : p.G, NPC = CG ? CNPC : p.NPC, N = CG ? CN : p.N, gpc = CG ? CGPC : p.gpc;
    const uint32_t magic = CG ? (uint32_t)(((1ull << 32) + CNPC - 1) / CNPC) : p.magic;
    const bool odd_edges = CG ? (CE & 3) != 0 || CGPC > 3 * THREADS : p.odd_edges;
    const int nbase = b * NPC, nn = min(NPC, N - nbase);
    const int eg0 = b * gpc, eg1 = min((CG ? CE : p.E) >> 2, eg0 + gpc);

    uint4* stage4 = reinterpret_cast<uint4*>(smem + STAGE_OFF);
    uint32_t* ncnt = reinterpret_cast<uint32_t*>(smem + NCNT_OFF);
    uint32_t* misc = reinterpret_cast<uint32_t*>(smem + MISC_OFF);
    const uint32_t bar_tab = sb + BAR_OFF;

    TS0(0);
    int4 es[3], ed[3];
    auto load_edges = [&](int i) {
        const int g = min(eg0 + tid + i * THREADS, eg1 - 1);
        asm volatile("ld.global.cs.v4.u32 {%0,%1,%2,%3}, [%8];\nld.global.cs.v4.u32 {%4,%5,%6,%7}, [%9];"
                     : "=r"(es[i].x), "=r"(es[i].y), "=r"(es[i].z), "=r"(es[i].w), "=r"(ed[i].x), "=r"(ed[i].y), "=r"(ed[i].z), "=r"(ed[i].w)
                     : "l"(reinterpret_cast<const int4*>(p.src) + g), "l"(reinterpret_cast<const int4*>(p.dst) + g) : "memory");
    };
    es[0] = ed[0] = make_int4(0, 0, 0, 0);
    const char* const own = reinterpret_cast<const char*>(p.sv) + (size_t)nbase * 512;
    auto touch = [&](int o) {
        if (o + lane * 256 < nn * 512)
            asm volatile("cp.async.ca.shared.global.L2::256B [%0], [%1], 4;" ::"r"(sb + DUMMY_OFF + 4 * lane), "l"(own + o + lane * 256) : "memory");
    };
    uint4* const xout = p.g->xbuf + ((tid >> 3) * G + b) * 8 + (tid & 7);
    unsigned epoch;
    const uint32_t tbytes = ((N + 3) >> 2) * 16, cut = (tbytes >> 8) * CUT * 16, bar_cut = sb + BAR_OFF + 120;
    {
        uint32_t pxy, pz;
        if constexpr (CG && CN % 2 == 0) {
            asm volatile("ld.global.nc.u32 %0, [%3];\nld.global.nc.u32 %1, [%3 + 4];\nld.global.ca.u32 %2, [%4];"
                         : "=r"(pxy), "=r"(pz), "=r"(epoch)
                         : "l"(reinterpret_cast<const uint32_t*>(p.pos) + ((nbase + min(tid, nn - 1)) * 3 >> 1)), "l"(p.g->sync) : "memory");
            const uint32_t sh = ((nbase + tid) & 1) << 4;
            pxy = __funnelshift_r(pxy, pz, sh);
            pz >>= sh;
        } else {
            const uint16_t* q = reinterpret_cast<const uint16_t*>(p.pos) + (nbase + min(tid, nn - 1)) * 3;
            pxy = q[0] | (uint32_t)q[1] << 16;
            pz = q[2];
            asm volatile("ld.global.ca.u32 %0, [%1];" : "=r"(epoch) : "l"(p.g->sync) : "memory");
        }
        const uint32_t code = qcode(bf_lo(pxy), bf_hi(pxy), bf_lo(pz), ((epoch & 31u) ^ 0x6Bu) << 24);
        asm volatile("{\n.reg .pred p;\nsetp.lt.s32 p, %2, %3;\n@p st.global.u32 [%0], %1;\n}\n"
                     ::"l"(reinterpret_cast<uint32_t*>(p.g->table) + nbase + tid), "r"(code), "r"(tid), "r"(nn) : "memory");
        __syncthreads();
        asm volatile("{\n.reg .pred p;\nsetp.eq.u32 p, %1, %2;\n@p red.relaxed.gpu.global.add.u32 [%0], 1;\n}\n" ::"l"(p.g->sync + 1), "r"(tid), "n"(THREADS - 1) : "memory");
        if (tid < THREADS - 32) load_edges(0);
        if (tid < nn) p.g->pos8[nbase + tid] = make_uint2(pxy, pz);
        reinterpret_cast<uint2*>(smem + OPOS_OFF)[tid] = make_uint2(pxy, pz);
    }
    const uint32_t tag = (epoch & 31u) | 32u;
    if (tid == THREADS - 1) {
        TSX(1, 511);
        mbar_init(bar_tab, 1);
        mbar_init(bar_cut, 1);
        mbar_expect_tx(bar_cut, cut);
        mbar_expect_tx(bar_tab, tbytes - cut);
        const unsigned want = (epoch + 1) * G;
        unsigned c;
        int it = smem_u32(smem_dyn) == SB ? 0 : 1 << 22;
        __nanosleep(HDELAY);
        do {
            asm volatile("ld.relaxed.gpu.global.u32 %0, [%1];" : "=r"(c) : "l"(p.g->sync + 1) : "memory");
            if (++it > (1 << 22)) __trap();
        } while (c != want);
        bulk_g2s(sb, p.g->table, cut, bar_cut);
        bulk_g2s(sb + cut, reinterpret_cast<const char*>(p.g->table) + cut, tbytes - cut, bar_tab);
        TSX(2, 511);
    }
    if (warp == 14) {
#pragma unroll 1
        for (int c = b * 32 + lane; c < RING_OFF / 16; c += G * 32) {
            const int row = c >> 3, j = (c ^ row) & 7;
            uint4 v;
            if (c < 512) {
                const uint32_t half = 0x3F003F00u;
                v = __ldg(reinterpret_cast<const uint4*>(p.w1) + row * 8 + j);
                v = make_uint4(hmul2(v.x, half), hmul2(v.y, half), hmul2(v.z, half), hmul2(v.w, half));
            } else {
                const uint32_t* q = (c < 2048 ? reinterpret_cast<const uint32_t*>(p.w2) + (row & 63) * 96 + ((row >> 6) - 1) * 32
                                              : reinterpret_cast<const uint32_t*>(p.wr) + (row & 15) * 96 + ((row >> 4) - 16) * 32) + (j & 4) * 4 + (j & 3);
                v = make_uint4(__ldg(q), __ldg(q + 4), __ldg(q + 8), __ldg(q + 12));
            }
            p.g->wimg[c] = v;
        }
    }
    if (tid == 416) {
#pragma unroll
        for (int i = 0; i < FLIGHT + 2; i++) mbar_init(sb + BAR_OFF + 8 + 8 * i, i ? 1 : 15);
    }
    ncnt[tid] = tid < 480 ? 0 : 1024;
    if (tid < MAXG + 32) reinterpret_cast<uint32_t*>(smem + SCNT_OFF)[tid] = tid < MAXG ? 0 : 128;
    if (tid < 128) misc[tid] = 0;
    {
        const uint32_t inv = (PAY_INVALID << 6) | tag;
        stage4[tid] = stage4[tid + THREADS] = make_uint4(inv, inv, inv, inv);
        if (tid < MAXG * 8 - 2 * THREADS) stage4[tid + 2 * THREADS] = make_uint4(inv, inv, inv, inv);
    }
    __syncthreads();
    if ((tid >> 4) == 29) asm volatile("cp.async.ca.shared.global [%0], [%1], 4;" ::"r"(sb + FREQ_OFF + 8 * (tid & 14) + 4 * (tid & 1)),
                              "l"(reinterpret_cast<const uint32_t*>(p.freqs) + ((tid & 7) >> 1) + (tid & 1) * 4) : "memory");
    if (warp == 15) load_edges(0);
    if (warp < 8) mbar_wait(bar_cut, 0);
    load_edges(1);
    load_edges(2);
    if (tid == 416) asm volatile("fence.acq_rel.gpu;" ::: "memory");
    if (warp >= 8) mbar_wait(bar_cut, 0);
    {
        const uint32_t x = (PAY_INVALID << 6) | (tag ^ 16);
#pragma unroll
        for (int i = 0; i < 3; i++) stg128_if(xout + i * G * THREADS, make_uint4(x, x, x, x), tid + i * THREADS < G * 8);
    }
    bool full = false;
    {
        uint32_t at[24], msg[12], cnt[12], line[12];
#pragma unroll
        for (int j = 0; j < 12; j++) {
            const uint32_t s = j % 4 == 0 ? es[j / 4].x : j % 4 == 1 ? es[j / 4].y : j % 4 == 2 ? es[j / 4].z : es[j / 4].w;
            const uint32_t d = j % 4 == 0 ? ed[j / 4].x : j % 4 == 1 ? ed[j / 4].y : j % 4 == 2 ? ed[j / 4].z : ed[j / 4].w;
            const uint32_t own = __umulhi(d, magic);
            at[2 * j] = 4 * s; at[2 * j + 1] = 4 * d;
            msg[j] = own * (uint32_t)(-64 * NPC) + ((s << 15) + ((d << 6) + tag));
            cnt[j] = eg0 + tid + (j / 4) * THREADS < eg1 ? 4 * own : 4 * (MAXG + lane);
            line[j] = own * 128 + ((own & 7) << 4);
            asm volatile("" : "+r"(at[2 * j]), "+r"(at[2 * j + 1]), "+r"(msg[j]), "+r"(cnt[j]), "+r"(line[j]));
        }
        mbar_wait(bar_tab, 0);
        TS0(3);
        if (warp == 15) {
#pragma unroll
            for (int i = 0; i < TOUCH; i++) touch(i * 8192);
        }
#pragma unroll
        for (int i = 0; i < 12; i += 6) {
            uint32_t sl[6], cd[12];
#pragma unroll
            for (int j = 0; j < 12; j++) cd[j] = lds32(sb + at[2 * i + j]);
#pragma unroll
            for (int j = 0; j < 6; j++) {
                uint32_t q;
                const bool c = near_test(cd[2 * j], cd[2 * j + 1], tag << 24, q);
                msg[i + j] |= q & 0x80000000u;
                asm volatile("atom.shared.add.u32 %0, [%1 + %2], 4;" : "=r"(sl[j]) : "r"(c ? cnt[i + j] : 4 * (MAXG + lane)), "n"(SB + SCNT_OFF) : "memory");
            }
#pragma unroll
            for (int j = 0; j < 6; j++) {
                sts32_if(sb + STAGE_OFF + (line[i + j] ^ sl[j]), msg[i + j], sl[j] < 124);
                full |= sl[j] == 124;
            }
        }
    }
    {
        const int redo = __syncthreads_or(full);
        if (__builtin_expect(redo || odd_edges, 0)) cold_filter(smem, p, eg0, eg1, tag, redo);
    }
    TS0(4);
#pragma unroll
    for (int i = 0; i < 3; i++)
        stg128_if(xout + i * G * THREADS, stage4[(tid ^ ((tid >> 3) & 7)) + i * THREADS],
                  tid + i * THREADS < G * 8 && reinterpret_cast<const uint32_t*>(smem + SCNT_OFF)[(tid >> 3) + i * 64] >= (tid & 6) * 16u);
    __syncthreads();
#pragma unroll
    for (int i = -2; i < 2; i++) {
        const int c = tid + i * THREADS;
        const uint32_t x = c < (SN_OFF - STAGE_OFF) / 16 ? 0u : 0xFFFFFFFFu;
        if (c >= (SREC_OFF - STAGE_OFF) / 16) stage4[c] = make_uint4(x, x, x, x);
    }
    uint32_t key[4] = {0, 0, 0, 0};
    uint2 pr[4];
    const uint32_t gp = sb + RING_OFF + 2048 + (warp < 4 * NWG ? warp * 12288 : (warp & 3) * 12288 + 2048) + lane * 16;
    uint32_t pk = 0;
    if (warp == 15) {
        if (lane == 0) {
            int o = TOUCH * 8192;
#pragma unroll 1
            while (o < nn * 512 && !mbar_test(sb + BAR_OFF + 8, 0)) {
                const uint32_t bar = sb + BAR_OFF + 16 + 8 * (pk % FLIGHT);
                if (!mbar_test(bar, ~(pk / FLIGHT) & 1)) continue;
                const int n = min(4096, nn * 512 - o);
                mbar_expect_tx(bar, n);
                bulk_g2s(sb + DUMMY_OFF, own + o, n, bar);
                o += n;
                pk++;
            }
            misc[3] = pk;
        }
        __syncwarp();
    } else {
    __nanosleep(PDELAY);
    TS0(5);

    {
        const int LPW = (G + 14) / 15;
        uint32_t ew[3][4], bad[3];
        const uint4* cp = p.g->xbuf + (b * G + warp * LPW) * 8 + lane;
#pragma unroll
        for (int i = 0; i < 3; i++) {
            bad[i] = lane + 32 * i < min(LPW, G - warp * LPW) * 8;
            ew[i][0] = ew[i][1] = ew[i][2] = ew[i][3] = (PAY_INVALID << 6) | tag;
        }
        int it = 0;
#pragma unroll 1
        do {
#pragma unroll
            for (int i = 0; i < 3; i++)
                asm volatile("{\n.reg .pred p;\nsetp.ne.u32 p, %5, 0;\n@p ld.relaxed.gpu.global.v4.u32 {%0,%1,%2,%3}, [%4];\n}\n"
                             : "+r"(ew[i][0]), "+r"(ew[i][1]), "+r"(ew[i][2]), "+r"(ew[i][3]) : "l"(cp + 32 * i), "r"(bad[i]) : "memory");
#pragma unroll
            for (int i = 0; i < 3; i++) {
                const uint32_t x = (ew[i][0] ^ tag) | (ew[i][1] ^ tag) | (ew[i][2] ^ tag) | (ew[i][3] ^ tag);
                const uint32_t full = __ballot_sync(0xffffffffu, ew[i][3] < (PAY_INVALID << 6)) << 1 | 0x01010101u;
                bad[i] = (__ballot_sync(0xffffffffu, x & ((full >> (lane & 30)) & 1 ? 63u : 47u)) >> (lane & 24)) & 255u;
            }
            if (++it > (1 << 22)) __trap();
        } while (__any_sync(0xffffffffu, bad[0] | bad[1] | bad[2]));
        TSX(21, 0); TSX(22, 448);
        uint4* pack = reinterpret_cast<uint4*>(smem + PACK_OFF);
        int nch = 0;
        uint32_t at[3];
#pragma unroll
        for (int i = 0; i < 3; i++) {
            const uint32_t m = __ballot_sync(0xffffffffu, ew[i][0] < (PAY_MARK << 6));
            at[i] = nch + __popc(m & ((1u << lane) - 1));
            nch += __popc(m);
        }
        if (__builtin_expect(nch > 32, 0)) {
#pragma unroll 1
            for (int i = 0; i < 3; i++) {
                if (ew[0][0] < (PAY_MARK << 6) && at[0] >= 32) at[0] = (15 - warp) * 32 - 1 - min(atomicAdd(&misc[1], 1u), 31u);
                const uint32_t x = at[0], y = ew[0][0];
                at[0] = at[1]; at[1] = at[2]; at[2] = x;
                ew[0][0] = ew[1][0]; ew[1][0] = ew[2][0]; ew[2][0] = y;
            }
        }
#pragma unroll
        for (int i = 0; i < 3; i++) {
            asm volatile("{\n.reg .pred p;\nsetp.lt.u32 p, %1, %5;\n@p st.shared.v4.u32 [%0], {%1,%2,%3,%4};\n}\n"
                         ::"r"(sb + PACK_OFF + (warp * 32 + at[i]) * 16), "r"(ew[i][0]), "r"(ew[i][1]), "r"(ew[i][2]), "r"(ew[i][3]), "n"(PAY_MARK << 6) : "memory");
            sts32_if(sb + MISC_OFF + 4 * 17, 1, (ew[i][3] >> 6) == PAY_MARK);
        }
        bool have = lane < nch;
        if (warp == 14) {
            asm volatile("bar.sync 7, 480;" ::: "memory");
            const uint32_t extra = misc[1];
            if (nch + extra > 32) misc[18] = 1;
            have = have || lane + extra >= 32;
        } else {
            asm volatile("bar.arrive 7, 480;" ::: "memory");
        }
        __syncwarp();
        uint32_t w[4], rk[4];
        bool in[4];
        {
            const uint4 x = pack[tid];
            w[0] = have ? x.x : ~0u; w[1] = have ? x.y : ~0u; w[2] = have ? x.z : ~0u; w[3] = have ? x.w : ~0u;
        }
        auto fetch = [&](int j, bool c) {
            asm volatile("{\n.reg .pred p;\nsetp.ne.u32 p, %2, 0;\n@p cp.async.cg.shared.global [%0], [%1], 16;\n}\n"
                         ::"r"(gp + j * 512), "l"(reinterpret_cast<const uint4*>(p.g->pos8) + ((w[j] >> 16) & 0x7FFFu)), "r"((uint32_t)c) : "memory");
        };
#pragma unroll
        for (int j = 0; j < 4; j++) fetch(j, (int)w[j] < (int)(PAY_MARK << 6));
#pragma unroll
        for (int j = 0; j < 4; j++) pr[j] = reinterpret_cast<const uint2*>(smem + OPOS_OFF)[(w[j] >> 6) & 511u];
        uint32_t ca[4];
#pragma unroll
        for (int j = 0; j < 4; j++) {
            key[j] = ((w[j] >> 15) & 0xFFFFu) | ((w[j] << 10) & 0x1FF0000u);
            ca[j] = sb + NCNT_OFF + ((w[j] >> 4) & 0x7FCu);
            asm volatile("" : "+r"(key[j]), "+r"(ca[j]));
        }
        asm volatile("{\n.reg .pred p;\nsetp.eq.u32 p, %0, -1;\n@p trap;\n}" ::"r"(nch) : "memory");
        asm volatile("cp.async.wait_all;" ::: "memory");
        TSX(23, 0); TSX(24, 448);
        asm volatile("{\n.reg .pred p;\nsetp.eq.u32 p, %1, 0;\n@p mbarrier.arrive.shared::cta.b64 _, [%0];\n}\n" ::"r"(sb + BAR_OFF + 8), "r"(lane) : "memory");
#pragma unroll
        for (int j = 0; j < 4; j++) {
            uint2 ps;
            asm volatile("ld.shared.v2.u32 {%0,%1}, [%2];" : "=r"(ps.x), "=r"(ps.y) : "r"(gp + j * 512 + ((w[j] >> 12) & 8)) : "memory");
            in[j] = ((int)w[j] >= 0) | (((int)w[j] < (int)(PAY_MARK << 6)) & inside(hsub2(ps.x, pr[j].x), hsub2(ps.y, pr[j].y)));
        }
#pragma unroll
        for (int j = 0; j < 4; j++)
            asm volatile("atom.shared.add.u32 %0, [%1], 1;" : "=r"(rk[j]) : "r"(in[j] ? ca[j] : sb + NCNT_OFF + 4 * (480 + lane)) : "memory");
#pragma unroll
        for (int j = 0; j < 4; j++) {
            rk[j] = rk[j] < SPL ? 2 * rk[j] : min(2 * rk[j] - (2 * SPL - 1), 126u);
            asm volatile("red.shared.add.u32 [%0 + %1], 1;" ::"r"(rk[j] & 2 ? 124u : rk[j] & 60u), "n"(SB + MISC_OFF + 128) : "memory");
            key[j] += rk[j] << 25;
        }
#pragma unroll
        for (int j = 0; j < 4; j++) fetch(j, (int)w[j] >= 0);
        cp_commit();
    }
    }
    __syncthreads();
    TS0(6);
    uint32_t deg[5];
    deg[4] = lds32(sb + NCNT_OFF + 4 * tid);
#pragma unroll
    for (int j = 0; j < 4; j++) deg[j] = lds32(sb + NCNT_OFF + ((key[j] >> 14) & 0x7FCu));
    if (tid == THREADS - 33) {
        if (b == 0) p.g->sync[0] = epoch + 1;
        asm volatile("fence.proxy.async.global;" ::: "memory");
        mbar_expect_tx(bar_tab, RING_OFF);
        bulk_g2s(sb, p.g->wimg, RING_OFF, bar_tab);
    }
    __syncwarp();
    uint32_t dst = sb + RING_OFF + warp * 12288 + (lane >> 3) * 256 + (((lane & 7) ^ (lane >> 3)) << 4), l7 = (lane & 7) * 16, g32 = (lane >> 2) * 32;
    uint32_t e0, e1, n0, n1;
    auto sources = [&](uint32_t c) {
        asm volatile("{\n.reg .b32 a;\nlop3.b32 a, %4, %5, 0xFFC0, 0xA8;\nshr.u32 a, a, 2;\nld.shared.v4.u32 {%0,%1,%2,%3}, [a + %6];\n}\n"
                     : "=r"(e0), "=r"(n0), "=r"(e1), "=r"(n1) : "r"(c), "r"(g32), "n"(SB + SN_OFF));
    };
    auto load_s = [&](auto pad) {
        gather<1, 0, pad.value>(dst, p.sv, l7, e0); gather<1, 1, pad.value>(dst + 1024, p.sv, l7, e0);
        gather<1, 0, pad.value>((dst ^ 64) + 128, p.sv, l7, e1); gather<1, 1, pad.value>((dst ^ 64) + 1152, p.sv, l7, e1);
    };
    auto load_o = [&]() {
        gather<4, 0>(dst + 8192, p.sv, l7, n0); gather<4, 0>((dst ^ 64) + 8320, p.sv, l7, n1);
    };
    auto load_v = [&](auto pad) {
        gather<3, 0, pad.value>(dst + 2048, p.sv, l7, e0); gather<3, 1, pad.value>(dst + 5120, p.sv, l7, e0);
        gather<3, 0, pad.value>((dst ^ 64) + 2176, p.sv, l7, e1); gather<3, 1, pad.value>((dst ^ 64) + 5248, p.sv, l7, e1);
        cp_commit();
    };
    const int ng = (misc[32] + 7) >> 3;
    const int give = max(min(ng - max((int)(misc[33] + 7) >> 3, 4 * NWG), GIVE), 0);
    if (warp == 15) {
        const uint32_t cnt = lane < 16 ? (misc[32 + lane] + 7) >> 3 : 0u;
        uint32_t z = cnt;
#pragma unroll
        for (int o = 1; o < 16; o <<= 1) {
            const uint32_t y = __shfl_up_sync(0xffffffffu, z, o);
            if (lane >= o) z += y;
        }
        misc[96 + lane] = lane < 16 ? 64 * (z - cnt) : 64 * (MAXROW + 1);
        asm volatile("bar.arrive 5, 512;" ::: "memory");
        if (lane == 15) {
            const bool cold = cnt || z > MAXROW || misc[31 + SPL / 2] > 32 || misc[17] || misc[18];
            misc[18] = cold;
            misc[4] = 8 * ng;
            asm volatile("st.relaxed.gpu.global.u32 [%0], %1;" ::"l"(p.g->rows + b), "r"(~epoch << 16 | (cold || ng < 4 * NWG ? 255 : give << 8 | z)) : "memory");
        }
        pk = (z - cnt) << 8 | __shfl_down_sync(0xffffffffu, cnt, 1) << 24;
    } else {
        if (warp * 32 < nn) {
            const uint32_t c = deg[4], st = tid < nn ? (min(c, (uint32_t)SPL) + 1) >> 1 : 17u;
            const uint32_t same = __match_any_sync(0xffffffffu, st), first = __ffs(same) - 1;
            uint32_t r, node = nbase + tid;
            asm volatile("atom.shared.add.u32 %0, [%1], %2;" : "=r"(r)
                         : "r"(lane == first ? sb + MISC_OFF + 4 * (64 + st) : sb + NCNT_OFF + 4 * (480 + lane)), "r"(__popc(same)) : "memory");
            r = __shfl_sync(0xffffffffu, r, first) + __popc(same & ((1u << lane) - 1)) + misc[32 + st];
            if (__builtin_expect(c > SPL, 0)) {
                const uint32_t s2 = min((c - SPL + 1) >> 1, 16u), r2 = misc[32 + s2] + atomicAdd(&misc[64 + s2], 1u), k = atomicAdd(&misc[2], 1u);
                reinterpret_cast<uint32_t*>(smem + SCNT_OFF)[k & 31] = node;
                node |= NODE_SPLIT;
                ncnt[1024 + tid] = 8 * r2;
                reinterpret_cast<uint32_t*>(smem + SN_OFF)[(r2 & 511) * 2 + 1] = node;
            }
            if (tid < nn) {
                ncnt[512 + tid] = 8 * r;
                reinterpret_cast<uint32_t*>(smem + SN_OFF)[(r & 511) * 2 + 1] = node;
            }
        }
#pragma unroll
        for (int j = 0; j < 4; j++) {
            const uint32_t c = deg[j];
            asm volatile("{\n.reg .pred p;\n.reg .b64 a;\nsetp.ge.u32 p, %0, %3;\nsetp.lt.and.u32 p, %1, 0x8000000, p;\nmad.wide.u32 a, %4, 512, %2;\n@p prefetch.global.L2 [a];\n"
                         "}\n" ::"r"(c), "r"(key[j]), "l"(p.sv), "n"(BIG), "r"(key[j] & 0xFFFFu) : "memory");
        }
        asm volatile("bar.sync 5, 512;" ::: "memory");
        uint32_t slot[4];
#pragma unroll
        for (int j = 0; j < 4; j++) slot[j] = min(misc[96 + (key[j] >> 27)] + (ncnt[512 + ((key[j] >> 16) & 1023)] & 0xFFF8u), 64u * (MAXROW + 1)) + ((key[j] >> 25) & 2);
#pragma unroll
        for (int j = 0; j < 4; j++) {
            *reinterpret_cast<uint16_t*>(smem + SN_OFF + slot[j]) = (uint16_t)key[j];
            slot[j] += slot[j] & 2;
        }
        asm volatile("bar.sync 6, 480;" ::: "memory");
        TS0(7);
        if (warp < 4 * NWG) {
            sources((warp < ng ? warp : MAXROW) << 8);
            e0 = __vminu2(e0, (N - 1) * 0x10001u);
            e1 = __vminu2(e1, (N - 1) * 0x10001u);
            load_s(IntC<0>{});
            cp_commit();
            load_o();
            cp_commit();
            asm volatile("cp.async.wait_group 2;" ::: "memory");
        } else {
            asm volatile("cp.async.wait_all;" ::: "memory");
        }
        uint2 ps[4];
#pragma unroll
        for (int j = 0; j < 4; j++)
            asm volatile("ld.shared.v2.u32 {%0,%1}, [%2];" : "=r"(ps[j].x), "=r"(ps[j].y) : "r"(gp + j * 512 + (key[j] & 1) * 8) : "memory");
        TSX(9, 0);
#pragma unroll 1
        for (int i = 0; i < 2; i++) {
#pragma unroll
            for (int u = 0; u < 2; u++) {
                const uint3 geo = geometry(hsub2(ps[u].x, pr[u].x), hsub2(ps[u].y, pr[u].y));
                *reinterpret_cast<uint2*>(smem + SREC_OFF + 2 * slot[u]) = make_uint2(geo.x, geo.y);
                *reinterpret_cast<uint32_t*>(smem + SD_OFF + slot[u]) = geo.z;
                ps[u] = ps[u + 2];
                pr[u] = pr[u + 2];
                slot[u] = slot[u + 2];
            }
        }
    }
    if (warp == 15) { __syncwarp(); asm volatile("bar.arrive 4, 512;" ::: "memory"); }
    else asm volatile("bar.sync 4, 512;" ::: "memory");
    TS0(8);
    auto drain = [&](int i) { if (i < FLIGHT) mbar_wait(sb + BAR_OFF + 16 + 8 * i, ~((misc[3] + FLIGHT - 1 - i) / FLIGHT) & 1); };
    if (__builtin_expect(misc[18], 0)) {
        drain(warp);
        asm volatile("cp.async.wait_all;" ::: "memory");
        __syncthreads();
        cold_messages(smem, p, nn);
        mbar_wait(bar_tab, 1);
        return;
    }

    if (warp < 4 * NWG) {
        asm volatile("setmaxnreg.inc.sync.aligned.u32 %0;" ::"n"(REG_C));
        const int lane = fresh_lane();
        const int g = lane >> 2, q = lane & 3;
        const uint64_t dW1 = p.desc0, dW2 = dW1 + (W2_OFF >> 4), dWR = dW1 + (WR_OFF >> 4);
        const uint32_t ring = sb + RING_OFF + warp * 12288;
        const uint32_t vrow = pin(ring + g * 128 + ((q ^ ((g & 1) << 2) ^ (g >> 1)) << 4));
        const uint32_t mrow = pin(ring + (lane & 15) * 128 + (((lane >> 4) ^ ((lane & 1) << 2) ^ ((lane & 7) >> 1)) << 4));
        dst = pin(ring + (lane >> 3) * 256 + (((lane & 7) ^ (lane >> 3)) << 4)); l7 = pin((lane & 7) * 16); g32 = pin(g * 32);
        uint32_t ctl = sb + CTL_OFF + warp * 4;
        auto control = [&](uint32_t c, uint32_t at) {
            int it = 0;
#pragma unroll 1
            while (__builtin_expect(c == 0xFFFFFFFFu, 0)) {
                asm volatile("ld.volatile.shared.u32 %0, [%1];" : "=r"(c) : "r"(at) : "memory");
                c = __reduce_or_sync(0xffffffffu, c);
                if (++it > (1 << 24)) __trap();
            }
            return c;
        };
        uint32_t c0 = control(0xFFFFFFFFu, ctl), c1 = control(0xFFFFFFFFu, ctl + 64);
        if (warp >= 8) asm volatile("bar.arrive 1, 256;" ::: "memory");
        uint32_t acc[32];
        float P[32], W[32];
#pragma unroll
        for (int i = 0; i < 32; i++) { acc[i] = 0; P[i] = W[i] = 0.f; }
        mbar_wait(bar_tab, 1);
        sources(c0);
        e0 = __vminu2(e0, (N - 1) * 0x10001u);
        e1 = __vminu2(e1, (N - 1) * 0x10001u);
        if (warp >= 8) asm volatile("cp.async.wait_all;" ::: "memory");
        else if (warp >= 4) cp_wait1();
        load_v(IntC<0>{});
        auto finish = [&](uint32_t c, uint32_t node) {
            if (c & ST_CLOSE) {
                uint64_t op[2];
                asm("{\n.reg .b32 a;\nmad.lo.u32 a, %2, 512, %3;\nmad.wide.u32 %0, a, 1, %4;\nxor.b32 a, a, 64;\nmad.wide.u32 %1, a, 1, %4;\n}\n"
                    : "=l"(op[0]), "=l"(op[1]) : "r"(node), "r"(l7), "l"(p.out));
#pragma unroll
                for (int k = 0; k < 8; k++) {
                    uint32_t x[4];
#pragma unroll
                    for (int i = 0; i < 4; i++) x[i] = l7 & 64 ? acc[4 * (k ^ 1) + i] : acc[4 * k + i];
                    asm volatile("{\n.reg .pred p;\nsetp.lt.u32 p, %5, %6;\n@p st.global.cs.v4.u32 [%0], {%1,%2,%3,%4};\n}\n"
                                 ::"l"(op[k & 1] + 128 * (k >> 1)), "r"(x[0]), "r"(x[1]), "r"(x[2]), "r"(x[3]), "r"(node), "n"(NODE_SPLIT) : "memory");
                }
                if (__builtin_expect(__any_sync(0xffffffffu, (int)node >= (int)NODE_SPLIT), 0)) {
                    mbar_wait(sb + BAR_OFF + 16 + 8 * FLIGHT, 0);
                    if ((int)node >= (int)NODE_SPLIT) {
#pragma unroll
                        for (int k = 0; k < 8; k++)
                            asm volatile("red.global.add.noftz.v4.bf16x2 [%0], {%1,%2,%3,%4};" ::"l"((op[0] & ~64ull) + 64 * k), "r"(acc[4 * k]), "r"(acc[4 * k + 1]), "r"(acc[4 * k + 2]), "r"(acc[4 * k + 3]) : "memory");
                    }
                    __syncwarp();
                }
            }
        };
        uint32_t f01, f23;
        asm volatile("ld.shared.v2.u32 {%0,%1}, [%2 + %3];" : "=r"(f01), "=r"(f23) : "r"(l7), "n"(SB + FREQ_OFF));
        f01 = pin(f01); f23 = pin(f23);
#pragma unroll 1
        while ((int)c0 >= 0) {
            uint32_t a[16], h[16], rf[4], rr[4], m[16];
            TRW(ctl);
            uint32_t dd[2];
            asm volatile("ld.shared.v2.u32 {%0,%1}, [%2 + %3];" : "=r"(dd[0]), "=r"(dd[1]) : "r"(((c0 & 0xFF00) | g32) >> 2), "n"(SB + SD_OFF));
            sources(c1);
            asm volatile("cp.async.wait_group 2;" ::: "memory");
            __syncwarp();
#pragma unroll
            for (int i = 0; i < 4; i++) ldsm4(mrow ^ (i << 5), a + 4 * i);
            wg_fence();
            wgmma_k64(P, a, dW1);
            wg_commit();
#pragma unroll
            for (int hh = 0; hh < 2; hh++) {
                const float sc = bf_hi(dd[hh]);
                const uint32_t x01 = hmul2_lo(f01, dd[hh]), x23 = hmul2_lo(f23, dd[hh]);
                rf[hh] = pack2(__sinf(bf_lo(x01)) * sc, __sinf(bf_hi(x01)) * sc);
                rf[2 + hh] = pack2(__sinf(bf_lo(x23)) * sc, __sinf(bf_hi(x23)) * sc);
            }
            asm volatile("" : "+r"(rf[0]), "+r"(rf[1]), "+r"(rf[2]), "+r"(rf[3]));
            asm volatile("bar.sync %0, 256;" ::"r"(1 + (warp >> 2)) : "memory");
            SPLIT(2);
            wg_wait<0>();
            fence_regs(P);
#pragma unroll
            for (int i = 0; i < 16; i++)
                h[i] = pack2(fmaf(P[2 * i], tanh_fast(P[2 * i]), P[2 * i]), fmaf(P[2 * i + 1], tanh_fast(P[2 * i + 1]), P[2 * i + 1]));
            wg_fence();
            wgmma_k64(P, h, dW2 + 1024);
            wgmma_first(W, rf, dWR + 256);
            wg_commit();
            asm volatile("bar.arrive %0, 256;" ::"r"((c0 >> 4) & 3) : "memory");
            cp_wait1();
            __syncwarp();
#pragma unroll
            for (int k = 0; k < 4; k++) lds2_if(vrow + 8192 + 1024 * k, (vrow ^ 64) + 8192 + 1024 * k, acc + 8 * k, c0 & ST_START);
            lds128(sb + SREC_OFF + (((c0 & 0xFF00) | g32) >> 1), rr);
            uint32_t c2 = lds32(ctl + 128);
            __syncwarp();
            load_s(IntC<1>{});
            cp_commit();
            if (c1 & ST_START) load_o();
            cp_commit();
            wg_wait<0>();
            fence_regs(P); fence_regs(W);
#pragma unroll
            for (int j = 0; j < 8; j++) {
                m[j] = pack2(P[4 * j] * W[4 * j], P[4 * j + 1] * W[4 * j + 1]);
                m[8 + j] = pack2(P[4 * j + 2] * W[4 * j + 2], P[4 * j + 3] * W[4 * j + 3]);
            }
            wg_fence();
            wgmma_k64(P, h, dW2);
            wgmma_first(W, rf, dWR);
            wg_commit();
            SPLIT(4);
            PIN8(m); PIN8(m + 8);
            c2 = __reduce_or_sync(0xffffffffu, c2);
#pragma unroll
            for (int k = 1; k < 4; k++)
#pragma unroll
                for (int j = 0; j < 8; j++) {
                    const uint32_t x = k == 1 ? hfma2_lo(m[j], rr[0], acc[8 * k + j]) : k == 2 ? hfma2_hi(m[j], rr[0], acc[8 * k + j]) : hfma2_lo(m[j], rr[1], acc[8 * k + j]);
                    acc[8 * k + j] = k == 1 ? hfma2_lo(m[8 + j], rr[2], x) : k == 2 ? hfma2_hi(m[8 + j], rr[2], x) : hfma2_lo(m[8 + j], rr[3], x);
                }
            PIN8(acc + 8); PIN8(acc + 16); PIN8(acc + 24);
            c2 = control(c2, ctl + 128);
            wg_wait<0>();
            fence_regs(P); fence_regs(W);
#pragma unroll
            for (int j = 0; j < 8; j++)
                acc[j] = hadd2(acc[j], pack2(fmaf(P[4 * j], W[4 * j], P[4 * j + 2] * W[4 * j + 2]), fmaf(P[4 * j + 1], W[4 * j + 1], P[4 * j + 3] * W[4 * j + 3])));
            wg_fence();
            wgmma_k64(P, h, dW2 + 512);
            wgmma_first(W, rf, dWR + 128);
            wg_commit();
            SPLIT(6);
            asm volatile("cp.async.wait_group 2;" ::: "memory");
            __syncwarp();
            uint32_t v[4][16];
#pragma unroll
            for (int i = 0; i < NPRE; i++) lds128((vrow ^ (64 * (i & 1))) + 2048 + 1024 * (i >> 2) + 3072 * ((i >> 1) & 1), v[1 + (i >> 2)] + 4 * (i & 3));
            wg_wait<0>();
            fence_regs(P); fence_regs(W);
#pragma unroll
            for (int j = 0; j < 8; j++) {
                m[j] = pack2(P[4 * j] * W[4 * j], P[4 * j + 1] * W[4 * j + 1]);
                m[8 + j] = pack2(P[4 * j + 2] * W[4 * j + 2], P[4 * j + 3] * W[4 * j + 3]);
            }
#pragma unroll
            for (int i = NPRE; i < 12; i++) lds128((vrow ^ (64 * (i & 1))) + 2048 + 1024 * (i >> 2) + 3072 * ((i >> 1) & 1), v[1 + (i >> 2)] + 4 * (i & 3));
            sources(c1);
            const uint32_t node = lds32(sb + SN_OFF + 4 + (((c0 >> 16) | g32) >> 2));
            __syncwarp();
            load_v(IntC<1>{});
#pragma unroll
            for (int k = 1; k < 4; k++)
#pragma unroll
                for (int j = 0; j < 8; j++) acc[8 * k + j] = hfma2(m[8 + j], v[k][8 + j], hfma2(m[j], v[k][j], acc[8 * k + j]));
            finish(c0, node);
            ctl += 64;
            c0 = c1;
            c1 = c2;
        }
        asm volatile("cp.async.wait_all;" ::: "memory");
        TRW(ctl);
        TSX(11, 0); TSX(12, 128); TSX(13, 256);
    } else {
        asm volatile("setmaxnreg.dec.sync.aligned.u32 %0;" ::"n"(REG_H));
        const int lane = fresh_lane();
        const uint32_t chunk = sb + (lane & 8 ? (lane & 4 ? SN_OFF : SD_OFF) + (lane & 3) * 16 : SREC_OFF + (lane & 7) * 16), pitch = lane & 8 ? 64 : 128;
        if (warp == 12) {
#pragma unroll 1
            for (int r = lane >> 3; r < (int)misc[2]; r += 4) {
                const uint32_t n = reinterpret_cast<const uint32_t*>(smem + SCNT_OFF)[r] * 32 + (lane & 7);
                uint4 v[4];
#pragma unroll
                for (int i = 0; i < 4; i++) v[i] = reinterpret_cast<const uint4*>(p.sv)[n + 8 * i];
#pragma unroll
                for (int i = 0; i < 4; i++) reinterpret_cast<uint4*>(p.out)[n + 8 * i] = v[i];
            }
            __syncwarp();
#pragma unroll 1
            for (int i = lane >> 4; i < give; i += 2) {
                uint32_t x[4];
                lds128(chunk + (ng - 1 - i) * pitch, x);
                p.g->pool[(b * GIVE + i) * 16 + (lane & 15)] = make_uint4(x[0], x[1], x[2], x[3]);
            }
            __threadfence();
            __syncwarp();
            if (lane == 0) {
                asm volatile("st.relaxed.gpu.global.u32 [%0], %1;" ::"l"(p.g->ready + b), "r"(~epoch) : "memory");
                mbar_arrive(sb + BAR_OFF + 16 + 8 * FLIGHT);
            }
        }
        if (warp == 15) {
            int k = lane < 4 * NWG ? lane : 255, next = 4 * NWG, j = 0, mine = ng - give, end = -1, take = 0;
            uint32_t busy, at = sb + CTL_OFF + 4 * lane, from = 0;
#pragma unroll 1
            do {
                if (next > mine && end < 0) {
                    uint32_t x[5], z;
                    int it = 0;
#pragma unroll 1
                    do {
                        __nanosleep(700);
                        z = 0;
#pragma unroll
                        for (int i = 0; i < 5; i++) asm volatile("ld.relaxed.gpu.global.u32 %0, [%1];" : "=r"(x[i]) : "l"(p.g->rows + 5 * lane + i) : "memory");
#pragma unroll
                        for (int i = 0; i < 5; i++) {
                            x[i] = 5 * lane + i < G ? x[i] ^ (~epoch << 16) : 255;
                            z |= x[i];
                        }
                        if (++it > (1 << 22)) __trap();
                    } while (__any_sync(0xffffffffu, z >> 16));
                    z = 0;
#pragma unroll
                    for (int i = 0; i < 5; i++) {
                        if (x[i] != 255) z += (x[i] & 255) + 0x10000;
                    }
                    z = __reduce_add_sync(0xffffffffu, z);
                    const int level = min((int)(((z & 0xFFFFu) + (z >> 16) - 1) / max(z >> 16, 1u) + 3) & ~3, MAXROW);
                    uint32_t ed = 0, sur = 0, me = 0, mz = 0;
#pragma unroll
                    for (int i = 0; i < 5; i++) {
                        const int r = x[i] & 255;
                        const uint32_t e = r > level ? min(r - level, (int)(x[i] >> 8)) : min(level - r, ROOM) << 16;
                        if (i == b % 5) { me = e; mz = ed; }
                        sur |= (e & 15) << (4 * i);
                        ed += e;
                    }
                    z = ed;
#pragma unroll
                    for (int o = 1; o < 32; o <<= 1) {
                        const uint32_t y = __shfl_up_sync(0xffffffffu, z, o);
                        if (lane >= o) z += y;
                    }
                    const uint32_t all = __shfl_sync(0xffffffffu, z, 31), moved = min(all & 0xFFFFu, all >> 16);
                    me = __shfl_sync(0xffffffffu, me, b / 5);
                    mz = __shfl_sync(0xffffffffu, mz + z - ed, b / 5);
                    end = mine = ng - (min((mz + me) & 0xFFFFu, moved) - min(mz & 0xFFFFu, moved));
#pragma unroll 1
                    for (uint32_t u = mz >> 16; u < min((mz + me) >> 16, moved); u++, take++) {
                        int f = __popc(__ballot_sync(0xffffffffu, (z & 0xFFFFu) <= u));
                        uint32_t q = u - (__shfl_sync(0xffffffffu, z - ed, f) & 0xFFFFu), s5 = __shfl_sync(0xffffffffu, sur, f);
#pragma unroll 1
                        for (f *= 5; q >= (s5 & 15); f++, s5 >>= 4) q -= s5 & 15;
                        if (lane == take) from = f << 8 | q;
                    }
                }
                if (next > mine && take) {
                    if (lane < take) {
                        uint32_t x;
                        int it = 0;
#pragma unroll 1
                        do {
                            asm volatile("ld.acquire.gpu.global.u32 %0, [%1];" : "=r"(x) : "l"(p.g->ready + (from >> 8)) : "memory");
                            if (++it > (1 << 22)) __trap();
                        } while (x != ~epoch);
                    }
                    __syncwarp();
#pragma unroll 1
                    for (end += take; take--;) {
                        const uint32_t f = __shfl_sync(0xffffffffu, from, take);
                        if (lane < 16)
                            asm volatile("cp.async.cg.shared.global [%0], [%1], 16;" ::"r"(chunk + (MAXROW - 1 - take) * pitch),
                                         "l"(p.g->pool + ((f >> 8) * GIVE + (f & 255)) * 16 + lane) : "memory");
                    }
                    take = 0;
                    asm volatile("cp.async.wait_all;" ::: "memory");
                    __threadfence_block();
                    __syncwarp();
                }
                const bool has = k < (end < 0 ? mine : end);
                const uint32_t i = k < mine ? k : MAXROW - 1 + mine - k, x = __shfl_sync(0xffffffffu, pk, j);
                const bool close = has && i >= (x >> 24);
                busy = __ballot_sync(0xffffffffu, has);
                const uint32_t m = __ballot_sync(0xffffffffu, close);
                uint32_t c = has ? ((x & 0xFF00) + i * 0x1000100) | (j ? 0u : ST_START) | (close ? ST_CLOSE : 0u) : MAXROW * 256;
                if (!(busy >> (lane & 12))) c |= 0x80000000u;
                c |= busy >> ((lane & 12) + 4) ? (lane & 12) * 4 + 32 : 16;
                sts32_if(at, c, lane < 16 || !busy);
                j = close ? 0 : j + 1;
                k = close ? next + __popc(m & ((1u << lane) - 1)) : k;
                next += __popc(m);
                at += 64;
            } while (busy);
        }
        if (warp == 15) mbar_wait(sb + BAR_OFF + 16 + 8 * FLIGHT, 0);
        else if (warp != 12) __nanosleep(ZDELAY);
        const int zlast = misc[32] + misc[64] - 1;
#pragma unroll 1
        for (;;) {
            int r = 0;
            if (lane == 0) r = atomicAdd(&misc[4], 4u);
            r = __shfl_sync(0xffffffffu, r, 0);
            if (r > zlast) break;
            uint4 v[4];
            uint32_t n[4];
#pragma unroll
            for (int i = 0; i < 4; i++) {
                n[i] = reinterpret_cast<const uint32_t*>(smem + SN_OFF)[min(r + i, zlast) * 2 + 1] * 32 + lane;
                v[i] = __ldcs(reinterpret_cast<const uint4*>(p.sv) + n[i]);
            }
#pragma unroll
            for (int i = 0; i < 4; i++) __stcs(reinterpret_cast<uint4*>(p.out) + n[i], v[i]);
        }
        static_assert(FLIGHT <= 4, "drain");
        drain(warp & 3);
        asm volatile("cp.async.wait_all;" ::: "memory");
        TSX(14, 384); TSX(15, 480); TSX(16, 416);
    }
}

}

extern "C" void kernel_launch(void* const* d_in, const int* in_sizes, int n_in, void* d_out, int out_size) {
    static int s_G = 0;
    static void* s_scratch = nullptr;
    const int N = in_sizes[0] / 256, E = in_sizes[2];
    if (s_G == 0) {
        cudaFuncSetAttribute(painn_kernel<0, 0, 0>, cudaFuncAttributeMaxDynamicSharedMemorySize, SMEM_BYTES);
        cudaFuncSetAttribute(painn_kernel<50000, 800000, 132>, cudaFuncAttributeMaxDynamicSharedMemorySize, SMEM_BYTES);
        int dev = 0, sms = 0, occ = 0;
        cudaGetDevice(&dev);
        cudaDeviceGetAttribute(&sms, cudaDevAttrMultiProcessorCount, dev);
        cudaOccupancyMaxActiveBlocksPerMultiprocessor(&occ, painn_kernel<0, 0, 0>, THREADS, SMEM_BYTES);
        cudaGetSymbolAddress(&s_scratch, g_scratch);
        s_G = occ >= 1 ? (sms < MAXG ? sms : MAXG) : 0;
    }
    if (s_G == 0 || N > TABLE_MAXN || N > s_G * MAXNPC || (s_G - 1) * ((N + s_G - 1) / s_G) >= N || E > MAXE || E < 4 * MAXG * MAXG) return;
    Params p;
    p.g = (Scratch*)s_scratch;
    p.sv = (const __nv_bfloat16*)d_in[0];
    p.pos = (const __nv_bfloat16*)d_in[1];
    p.src = (const int*)d_in[2];
    p.dst = (const int*)d_in[3];
    p.freqs = (const __nv_bfloat16*)d_in[4];
    p.w1 = (const __nv_bfloat16*)d_in[5];
    p.w2 = (const __nv_bfloat16*)d_in[6];
    p.wr = (const __nv_bfloat16*)d_in[7];
    p.out = (__nv_bfloat16*)d_out;
    p.desc0 = (uint64_t)(SB >> 4) | ((uint64_t)1 << 16) | ((uint64_t)64 << 32) | ((uint64_t)1 << 62);
    p.N = N; p.E = E; p.G = s_G;
    p.NPC = (N + s_G - 1) / s_G;
    p.magic = (uint32_t)(((1ull << 32) + p.NPC - 1) / p.NPC);
    p.gpc = ((E >> 2) + s_G - 1) / s_G;
    p.odd_edges = (E & 3) != 0 || p.gpc > 3 * THREADS;
    if (N == 50000 && E == 800000 && s_G == 132) painn_kernel<50000, 800000, 132><<<s_G, THREADS, SMEM_BYTES, cudaStreamPerThread>>>(p);
    else painn_kernel<0, 0, 0><<<s_G, THREADS, SMEM_BYTES, cudaStreamPerThread>>>(p);
}
```

```cpp
#include <cuda_runtime.h>
#include <cuda_bf16.h>
#include <stdint.h>

namespace {

constexpr int NWG = 3;
constexpr int REG_C = 160, REG_H = 32;
constexpr int SPL = 10;
constexpr int GIVE = 10, ROOM = 4;
constexpr int BIG = 5;
constexpr int CUT = 7;
constexpr int HDELAY = 150;
constexpr int TOUCH = 4, FLIGHT = 4;
constexpr int NPRE = 5;
constexpr int PDELAY = 150;
constexpr int ZDELAY = 1200;
constexpr int THREADS = 512;
constexpr int MAXG = 136;
constexpr int MAXROW = 96;
constexpr int TMAX = MAXROW / 12 + 18;
constexpr int MAXNPC = 480;
constexpr int MAXE = 1 << 20;

constexpr int W2_OFF = 8192;
constexpr int WR_OFF = 32768;
constexpr int RING_OFF = 38912;
constexpr int SREC_OFF = RING_OFF + 4 * NWG * 12288;
constexpr int SD_OFF = SREC_OFF + (MAXROW + 1) * 128 + 16;
constexpr int SN_OFF = SD_OFF + (MAXROW + 1) * 64 + 16;
constexpr int CTL_OFF = SN_OFF + (MAXROW + 1) * 64 + 16;
constexpr int TABLE_MAXN = 50176;
constexpr int STAGE_OFF = TABLE_MAXN * 4;
constexpr int SCNT_OFF = STAGE_OFF + MAXG * 128;
constexpr int PACK_OFF = RING_OFF + 6144;
constexpr int NCNT_OFF = SCNT_OFF + 768;
constexpr int OPOS_OFF = NCNT_OFF + 2048;
constexpr int BAR_OFF = OPOS_OFF + 4096;
constexpr int MISC_OFF = BAR_OFF + 128;
constexpr int FREQ_OFF = MISC_OFF + 512;
constexpr int DUMMY_OFF = (FREQ_OFF + 128 + 127) / 128 * 128;
constexpr int SMEM_BYTES = DUMMY_OFF + 4096;
static_assert(CTL_OFF + 64 * TMAX <= STAGE_OFF + 32 * THREADS && STAGE_OFF - SREC_OFF <= 32 * THREADS && 4 * (MAXG + 32) <= 768, "smem map");
static_assert(GIVE < 16 && MAXG <= 160, "levelling");
static_assert(SMEM_BYTES <= 232448 && BAR_OFF % 8 == 0 && RING_OFF % 128 == 0 && SREC_OFF % 128 == 0 && (MAXG + 14) / 15 <= 12, "smem map");

constexpr uint32_t PAY_INVALID = 0x3FFFFFFu;
constexpr uint32_t PAY_MARK = 0x3FFFDFFu;
constexpr uint32_t NODE_SPLIT = 0x40000000u;
constexpr uint32_t ST_START = 1, ST_CLOSE = 2;
constexpr float QINVP = 9.0f / 510.0f;
constexpr uint32_t QTHRESH = 2134;
constexpr uint32_t QSURE = 1870;

struct Scratch {
    unsigned sync[32];
    uint4 table[TABLE_MAXN / 4];
    uint4 wimg[RING_OFF / 16];
    uint2 pos8[TABLE_MAXN];
    uint4 xbuf[MAXG * MAXG * 8 + 3 * THREADS];
    uint4 pool[MAXG * GIVE * 16];
    unsigned rows[160];
    unsigned ready[MAXG];
    int ovfcnt[MAXG];
    int2 ovf[MAXE + 8 * MAXG + 8];
};
__device__ __align__(128) Scratch g_scratch;

struct Params {
    const __nv_bfloat16* pos;
    Scratch* g;
    const int* src;
    const int* dst;
    int N, NPC, E, gpc;
    const __nv_bfloat16* w2;
    const __nv_bfloat16* wr;
    const __nv_bfloat16* w1;
    const __nv_bfloat16* freqs;
    const __nv_bfloat16* sv;
    __nv_bfloat16* out;
    uint64_t desc0;
    int G;
    uint32_t magic;
    int odd_edges;
};
constexpr uint32_t SB = 1024;

#define TSX(i, thr)
#define TS0(i) TSX(i, 0)
#define TRW(ctl)

__device__ __forceinline__ uint32_t smem_u32(const void* p) { return (uint32_t)__cvta_generic_to_shared(p); }
__device__ __forceinline__ void mbar_init(uint32_t bar, uint32_t cnt) {
    asm volatile("mbarrier.init.shared::cta.b64 [%0], %1;" ::"r"(bar), "r"(cnt) : "memory");
}
__device__ __forceinline__ void mbar_arrive(uint32_t bar) {
    asm volatile("mbarrier.arrive.shared::cta.b64 _, [%0];" ::"r"(bar) : "memory");
}
__device__ __forceinline__ void mbar_expect_tx(uint32_t bar, uint32_t bytes) {
    asm volatile("mbarrier.arrive.expect_tx.shared::cta.b64 _, [%0], %1;" ::"r"(bar), "r"(bytes) : "memory");
}
__device__ __forceinline__ void mbar_wait(uint32_t bar, uint32_t parity) {
    uint32_t ok;
    int it = 0;
    do {
        asm volatile(
            "{\n.reg .pred p;\n"
            "mbarrier.try_wait.parity.shared::cta.b64 p, [%1], %2, 2000;\n"
            "selp.u32 %0, 1, 0, p;\n}\n"
            : "=r"(ok) : "r"(bar), "r"(parity) : "memory");
        if (++it > (1 << 20)) __trap();
    } while (!ok);
}
__device__ __forceinline__ uint32_t mbar_test(uint32_t bar, uint32_t parity) {
    uint32_t ok;
    asm volatile("{\n.reg .pred p;\nmbarrier.test_wait.parity.shared::cta.b64 p, [%1], %2;\nselp.u32 %0, 1, 0, p;\n}\n"
                 : "=r"(ok) : "r"(bar), "r"(parity) : "memory");
    return ok;
}
__device__ __forceinline__ uint32_t pin(uint32_t x) {
    uint32_t r;
    asm volatile("shfl.sync.bfly.b32 %0, %1, 0, 31, -1;" : "=r"(r) : "r"(x));
    return r;
}
__device__ __forceinline__ void bulk_g2s(uint32_t dst, const void* src, uint32_t bytes, uint32_t bar) {
    asm volatile("cp.async.bulk.shared::cluster.global.mbarrier::complete_tx::bytes [%0], [%1], %2, [%3];"
                 ::"r"(dst), "l"(src), "r"(bytes), "r"(bar) : "memory");
}
__device__ __forceinline__ void ldsm4(uint32_t addr, uint32_t* r) {
    asm volatile("ldmatrix.sync.aligned.m8n8.x4.shared.b16 {%0,%1,%2,%3}, [%4];"
                 : "=r"(r[0]), "=r"(r[1]), "=r"(r[2]), "=r"(r[3]) : "r"(addr) : "memory");
}
__device__ __forceinline__ uint32_t pack2(float lo, float hi) {
    uint32_t r;
    asm("cvt.rn.bf16x2.f32 %0, %1, %2;" : "=r"(r) : "f"(hi), "f"(lo));
    return r;
}
__device__ __forceinline__ float bf_lo(uint32_t w) { return __uint_as_float(w << 16); }
__device__ __forceinline__ float bf_hi(uint32_t w) { return __uint_as_float(w & 0xFFFF0000u); }
__device__ __forceinline__ float rbf16(float x) { return __uint_as_float(pack2(0.f, x)); }
__device__ __forceinline__ uint32_t hmul2(uint32_t a, uint32_t b) {
    uint32_t r;
    asm("mul.rn.bf16x2 %0, %1, %2;" : "=r"(r) : "r"(a), "r"(b));
    return r;
}
__device__ __forceinline__ uint32_t hfma2(uint32_t a, uint32_t b, uint32_t c) {
    uint32_t r;
    asm("fma.rn.bf16x2 %0, %1, %2, %3;" : "=r"(r) : "r"(a), "r"(b), "r"(c));
    return r;
}
__device__ __forceinline__ uint32_t hfma2_lo(uint32_t a, uint32_t b, uint32_t c) {
    uint32_t r;
    asm("{\n.reg .b16 l, h;\n.reg .b32 t;\nmov.b32 {l, h}, %2;\nmov.b32 t, {l, l};\nfma.rn.bf16x2 %0, %1, t, %3;\n}\n" : "=r"(r) : "r"(a), "r"(b), "r"(c));
    return r;
}
__device__ __forceinline__ uint32_t hfma2_hi(uint32_t a, uint32_t b, uint32_t c) {
    uint32_t r;
    asm("{\n.reg .b16 l, h;\n.reg .b32 t;\nmov.b32 {l, h}, %2;\nmov.b32 t, {h, h};\nfma.rn.bf16x2 %0, %1, t, %3;\n}\n" : "=r"(r) : "r"(a), "r"(b), "r"(c));
    return r;
}
__device__ __forceinline__ uint32_t hadd2(uint32_t a, uint32_t b) {
    uint32_t r;
    asm("add.rn.bf16x2 %0, %1, %2;" : "=r"(r) : "r"(a), "r"(b));
    return r;
}
__device__ __forceinline__ uint32_t hsub2(uint32_t a, uint32_t b) {
    uint32_t r;
    asm("sub.rn.bf16x2 %0, %1, %2;" : "=r"(r) : "r"(a), "r"(b));
    return r;
}
__device__ __forceinline__ float tanh_fast(float x) {
    float r;
    asm("tanh.approx.f32 %0, %1;" : "=f"(r) : "f"(x));
    return r;
}
__device__ __forceinline__ void wg_fence() { asm volatile("wgmma.fence.sync.aligned;" ::: "memory"); }
__device__ __forceinline__ void wg_commit() { asm volatile("wgmma.commit_group.sync.aligned;" ::: "memory"); }
template <int N>
__device__ __forceinline__ void wg_wait() { asm volatile("wgmma.wait_group.sync.aligned %0;" ::"n"(N) : "memory"); }

#define WG_REGS "{%0,%1,%2,%3,%4,%5,%6,%7,%8,%9,%10,%11,%12,%13,%14,%15,%16,%17,%18,%19,%20,%21,%22,%23,%24,%25,%26,%27,%28,%29,%30,%31}"
#define WG_OPS(c) c(d[0]), c(d[1]), c(d[2]), c(d[3]), c(d[4]), c(d[5]), c(d[6]), c(d[7]), c(d[8]), c(d[9]), c(d[10]), \
    c(d[11]), c(d[12]), c(d[13]), c(d[14]), c(d[15]), c(d[16]), c(d[17]), c(d[18]), c(d[19]), c(d[20]), c(d[21]),     \
    c(d[22]), c(d[23]), c(d[24]), c(d[25]), c(d[26]), c(d[27]), c(d[28]), c(d[29]), c(d[30]), c(d[31])
__device__ __forceinline__ void wgmma_first(float* d, const uint32_t* a, uint64_t desc) {
    asm volatile("wgmma.mma_async.sync.aligned.m64n64k16.f32.bf16.bf16 " WG_REGS ", {%32,%33,%34,%35}, %36, 0, 1, 1, 1;"
                 : WG_OPS("+f") : "r"(a[0]), "r"(a[1]), "r"(a[2]), "r"(a[3]), "l"(desc));
}
__device__ __forceinline__ void wgmma_acc(float* d, const uint32_t* a, uint64_t desc) {
    asm volatile("wgmma.mma_async.sync.aligned.m64n64k16.f32.bf16.bf16 " WG_REGS ", {%32,%33,%34,%35}, %36, 1, 1, 1, 1;"
                 : WG_OPS("+f") : "r"(a[0]), "r"(a[1]), "r"(a[2]), "r"(a[3]), "l"(desc));
}
__device__ __forceinline__ void wgmma_k64(float* d, const uint32_t* a, uint64_t desc) {
    wgmma_first(d, a, desc);
    wgmma_acc(d, a + 4, desc + 128);
    wgmma_acc(d, a + 8, desc + 256);
    wgmma_acc(d, a + 12, desc + 384);
}
__device__ __forceinline__ void fence_regs(float* d) { asm volatile("" : WG_OPS("+f")::"memory"); }
__device__ __forceinline__ uint32_t qaxis(float x) {
    const float u = fmaf(x, QINVP, 0.25f);
    const float f = u - ((u + 12582912.f) - 12582912.f);
    return __float_as_uint(fmaf(fabsf(f), 510.f, 12582912.f));
}
__device__ __forceinline__ uint32_t qcode(float x, float y, float z, uint32_t tx) {
    return __byte_perm(__byte_perm(qaxis(x), qaxis(y), 0x3340), qaxis(z), 0x3410) ^ tx;
}
__device__ __forceinline__ bool near_test(uint32_t ca, uint32_t cb, uint32_t tag24, uint32_t& q) {
    const uint32_t D = __vabsdiffu4(ca, cb);
    q = __dp4a(D, D, 0x7FFFFFFFu - QSURE);
    return q <= 0x7FFFFFFFu - QSURE + QTHRESH || ((ca ^ tag24) | (cb ^ tag24)) >= 0x1000000u;
}
__device__ __forceinline__ bool inside(uint32_t rxy, uint32_t rz) {
    const uint32_t qxy = hmul2(rxy, rxy), qz = hmul2(rz, rz);
    return bf_lo(qxy) + bf_hi(qxy) + bf_lo(qz) < 23.9375f;
}

__device__ __forceinline__ uint32_t lds32(uint32_t addr) {
    uint32_t r;
    asm volatile("ld.shared.u32 %0, [%1];" : "=r"(r) : "r"(addr));
    return r;
}
__device__ __forceinline__ void sts32_if(uint32_t addr, uint32_t v, bool c) {
    asm volatile("{\n.reg .pred p;\nsetp.ne.u32 p, %2, 0;\n@p st.shared.u32 [%0], %1;\n}\n" ::"r"(addr), "r"(v), "r"((uint32_t)c) : "memory");
}
__device__ __forceinline__ void stg128_if(void* ptr, uint4 v, bool c) {
    asm volatile("{\n.reg .pred p;\nsetp.ne.u32 p, %5, 0;\n@p st.relaxed.gpu.global.v4.u32 [%0], {%1,%2,%3,%4};\n}\n"
                 ::"l"(ptr), "r"(v.x), "r"(v.y), "r"(v.z), "r"(v.w), "r"((uint32_t)c) : "memory");
}
__device__ __forceinline__ void lds128(uint32_t addr, uint32_t* r) {
    asm volatile("ld.shared.v4.u32 {%0,%1,%2,%3}, [%4];" : "=r"(r[0]), "=r"(r[1]), "=r"(r[2]), "=r"(r[3]) : "r"(addr) : "memory");
}
template <int NP, int HI, int PAD = 1>
__device__ __forceinline__ void gather(uint32_t dst, const void* base, uint32_t c, uint32_t e) {
#define GATHER_HEAD "{\n.reg .pred p;\n.reg .b32 n;\n.reg .b64 a;\nprmt.b32 n, %2, 0, %3;\nsetp.ne.u32 p, n, 0xFFFF;\nmad.lo.u32 n, n, 512, %4;\nmad.wide.u32 a, n, 1, %1;\n"
#define GATHER_1(P) P "cp.async.cg.shared.global [%0], [a], 16;\n}\n"
#define GATHER_3(P) P "cp.async.cg.shared.global [%0], [a + 128], 16;\n" P "cp.async.cg.shared.global [%0 + 1024], [a + 256], 16;\n" \
                    P "cp.async.cg.shared.global [%0 + 2048], [a + 384], 16;\n}\n"
#define GATHER_ARGS(z) ::"r"(dst), "l"(base), "r"(e), "n"((HI ? 0x32 : 0x10) + z), "r"(c) : "memory"
    if constexpr (NP == 1 && PAD) asm volatile(GATHER_HEAD GATHER_1("@p ") GATHER_ARGS(0x4400));
    if constexpr (NP == 1 && !PAD) asm volatile(GATHER_HEAD GATHER_1("") GATHER_ARGS(0x4400));
    if constexpr (NP == 3 && PAD) asm volatile(GATHER_HEAD GATHER_3("@p ") GATHER_ARGS(0x5500));
    if constexpr (NP == 3 && !PAD) asm volatile(GATHER_HEAD GATHER_3("") GATHER_ARGS(0x4400));
    if constexpr (NP == 4)
        asm volatile(GATHER_HEAD "setp.ge.u32 p, %2, 0x40000000;\ncp.async.cg.shared.global [%0], [a], 16, p;\ncp.async.cg.shared.global [%0 + 1024], [a + 128], 16, p;\n"
                     "cp.async.cg.shared.global [%0 + 2048], [a + 256], 16, p;\ncp.async.cg.shared.global [%0 + 3072], [a + 384], 16, p;\n}\n" GATHER_ARGS(0x4400));
}
__device__ __forceinline__ void cp_commit() { asm volatile("cp.async.commit_group;" ::: "memory"); }
__device__ __forceinline__ void cp_wait1() { asm volatile("cp.async.wait_group 1;" ::: "memory"); }
__device__ __forceinline__ uint32_t hmul2_lo(uint32_t a, uint32_t b) {
    uint32_t r;
    asm("{\n.reg .b16 l, h;\n.reg .b32 t;\nmov.b32 {l, h}, %2;\nmov.b32 t, {l, l};\nmul.rn.bf16x2 %0, %1, t;\n}\n" : "=r"(r) : "r"(a), "r"(b));
    return r;
}
__device__ __forceinline__ void lds2_if(uint32_t a0, uint32_t a1, uint32_t* r, uint32_t c) {
    asm volatile("{\n.reg .pred p;\nsetp.ne.u32 p, %10, 0;\n@p ld.shared.v4.u32 {%0,%1,%2,%3}, [%8];\n@p ld.shared.v4.u32 {%4,%5,%6,%7}, [%9];\n}\n"
                 : "+r"(r[0]), "+r"(r[1]), "+r"(r[2]), "+r"(r[3]), "+r"(r[4]), "+r"(r[5]), "+r"(r[6]), "+r"(r[7])
                 : "r"(a0), "r"(a1), "r"(c) : "memory");
}
__device__ __forceinline__ int fresh_lane() {
    int l;
    asm volatile("mov.u32 %0, %%laneid;" : "=r"(l));
    return l;
}

__device__ __forceinline__ void cold_edges(unsigned char* smem, const Params& p, int lo, int hi, uint32_t tag) {
#pragma unroll 1
    for (int e = lo + threadIdx.x; e < hi; e += THREADS) {
        const int s = p.src[e], d = p.dst[e];
        uint32_t q;
        if (near_test(reinterpret_cast<const uint32_t*>(smem)[s], reinterpret_cast<const uint32_t*>(smem)[d], tag << 24, q)) {
            const uint32_t own = __umulhi((uint32_t)d, p.magic);
            const uint32_t slot4 = atomicAdd(reinterpret_cast<uint32_t*>(smem + SCNT_OFF) + own, 4u);
            uint32_t* line = reinterpret_cast<uint32_t*>(smem + STAGE_OFF) + own * 32;
            if (slot4 < 124) {
                line[(slot4 >> 2) ^ ((own & 7) << 2)] = ((uint32_t)s << 15) + ((uint32_t)(d - own * p.NPC) << 6) + tag + (q & 0x80000000u);
            } else {
                uint32_t o = atomicAdd(reinterpret_cast<uint32_t*>(smem + MISC_OFF) + 16, 1u);
                p.g->ovf[(size_t)blockIdx.x * (4 * p.gpc + 4) + o] = make_int2(s, d);
                line[31 ^ ((own & 7) << 2)] = (PAY_MARK << 6) | tag;
            }
        }
    }
}
__device__ __forceinline__ void cold_filter(unsigned char* smem, const Params& p, int e0, int e1, uint32_t tag, int redo) {
    if (redo) {
        if (threadIdx.x < MAXG) reinterpret_cast<uint32_t*>(smem + SCNT_OFF)[threadIdx.x] = 0;
        __syncthreads();
    }
    cold_edges(smem, p, redo ? 4 * e0 : 4 * (e0 + 3 * THREADS), 4 * e1, tag);
    if (blockIdx.x == 0) cold_edges(smem, p, p.E & ~3, p.E, tag);
    __syncthreads();
    if (threadIdx.x == 0) p.g->ovfcnt[blockIdx.x] = reinterpret_cast<uint32_t*>(smem + MISC_OFF)[16];
    __threadfence();
    __syncthreads();
}
__device__ __forceinline__ uint3 geometry(uint32_t rxy, uint32_t rz) {
    const uint32_t qxy = hmul2(rxy, rxy), qz = hmul2(rz, rz);
    float d, id;
    asm("sqrt.approx.ftz.f32 %0, %1;" : "=f"(d) : "f"(rbf16(rbf16(bf_lo(qxy) + bf_hi(qxy) + bf_lo(qz)) + 1e-8f)));
    d = rbf16(d);
    asm("rcp.approx.ftz.f32 %0, %1;" : "=f"(id) : "f"(d));
    const float cs = rbf16(__cosf(rbf16(rbf16(3.14159265358979f * d) * 0.2f)));
    const uint32_t zs = pack2(bf_lo(rz) * id, 0.5f * rbf16(cs + 1.0f) * id);
    return d < 5.0f ? make_uint3(pack2(bf_lo(rxy) * id, bf_hi(rxy) * id), zs, __byte_perm(__float_as_uint(d), zs, 0x7632)) : make_uint3(0, 0, 0);
}
__device__ __forceinline__ void cold_messages(unsigned char* smem, const Params& p, int nn) {
    const int nbase = blockIdx.x * p.NPC, lane = threadIdx.x & 31;
    const uint32_t* box = reinterpret_cast<const uint32_t*>(p.g->xbuf) + blockIdx.x * p.G * 32;
    uint32_t* w = reinterpret_cast<uint32_t*>(smem + RING_OFF);
#pragma unroll 1
    for (int i = threadIdx.x; i < 9728; i += THREADS)
        w[i] = i < 2048 ? reinterpret_cast<const uint32_t*>(p.w1)[i] : i < 8192 ? reinterpret_cast<const uint32_t*>(p.w2)[i - 2048] : reinterpret_cast<const uint32_t*>(p.wr)[i - 8192];
#pragma unroll 1
    for (int i = threadIdx.x; i < nn * 32; i += THREADS) reinterpret_cast<uint4*>(p.out)[nbase * 32 + i] = reinterpret_cast<const uint4*>(p.sv)[nbase * 32 + i];
    __threadfence();
    __syncthreads();
    const float freq = __bfloat162float(p.freqs[lane & 15]);
#pragma unroll 1
    for (int m = -1; m < p.G; m++) {
        const int cnt = m < 0 ? p.G * 32 : (__ldcg(box + m * 32 + 31) >> 6) == PAY_MARK ? __ldcg(&p.g->ovfcnt[m]) : 0;
#pragma unroll 1
        for (int i = threadIdx.x; i - lane < cnt; i += THREADS) {
            int2 e = make_int2(0, -1);
            if (i < cnt) {
                if (m < 0) {
                    const uint32_t x = __ldcg(box + i);
                    e = make_int2((x >> 15) & 0xFFFFu, nbase + ((x >> 6) & 511u));
                } else {
                    e = __ldcg(p.g->ovf + (size_t)m * (4 * p.gpc + 4) + i);
                }
            }
            bool in = (uint32_t)(e.y - nbase) < (uint32_t)nn;
            uint3 geo = make_uint3(0, 0, 0);
            if (in) {
                const uint2 ps = __ldcg(p.g->pos8 + e.x), pd = __ldcg(p.g->pos8 + e.y);
                const uint32_t rxy = hsub2(ps.x, pd.x), rz = hsub2(ps.y, pd.y);
                in = inside(rxy, rz);
                geo = geometry(rxy, rz);
            }
#pragma unroll 1
            for (uint32_t todo = __ballot_sync(0xffffffffu, in); todo; todo &= todo - 1) {
                const int l = __ffs(todo) - 1;
                const uint32_t* row = reinterpret_cast<const uint32_t*>(p.sv) + (size_t)__shfl_sync(0xffffffffu, e.x, l) * 128 + lane;
                uint32_t* orow = reinterpret_cast<uint32_t*>(p.out) + (size_t)__shfl_sync(0xffffffffu, e.y, l) * 128 + lane;
                const uint32_t gx = __shfl_sync(0xffffffffu, geo.x, l), gy = __shfl_sync(0xffffffffu, geo.y, l);
                const float rb = rbf16(__sinf(rbf16(bf_lo(__shfl_sync(0xffffffffu, geo.z, l)) * freq)) * bf_hi(gy));
                uint32_t x = row[0];
                float a[12] = {0, 0, 0, 0, 0, 0, 0, 0, 0, 0, 0, 0};
#pragma unroll 2
                for (int k = 0; k < 64; k++) {
                    const uint32_t u = __shfl_sync(0xffffffffu, x, k >> 1), ww = w[k * 32 + lane];
                    const float f = k & 1 ? bf_hi(u) : bf_lo(u);
                    a[0] = fmaf(f, bf_lo(ww), a[0]); a[1] = fmaf(f, bf_hi(ww), a[1]);
                }
                x = pack2(0.5f * fmaf(a[0], tanh_fast(0.5f * a[0]), a[0]), 0.5f * fmaf(a[1], tanh_fast(0.5f * a[1]), a[1]));
                a[0] = a[1] = 0.f;
#pragma unroll 2
                for (int k = 0; k < 64; k++) {
                    const uint32_t u = __shfl_sync(0xffffffffu, x, k >> 1);
                    const float f = k & 1 ? bf_hi(u) : bf_lo(u), r = __shfl_sync(0xffffffffu, rb, k & 15);
#pragma unroll
                    for (int c = 0; c < 3; c++) {
                        const uint32_t ww = w[2048 + k * 96 + c * 32 + lane], wr = k < 16 ? w[8192 + k * 96 + c * 32 + lane] : 0u;
                        a[2 * c] = fmaf(f, bf_lo(ww), a[2 * c]); a[2 * c + 1] = fmaf(f, bf_hi(ww), a[2 * c + 1]);
                        a[6 + 2 * c] = fmaf(r, bf_lo(wr), a[6 + 2 * c]); a[7 + 2 * c] = fmaf(r, bf_hi(wr), a[7 + 2 * c]);
                    }
                }
                const uint32_t mv = pack2(a[2] * a[8], a[3] * a[9]), mr = pack2(a[4] * a[10], a[5] * a[11]);
                const uint32_t o[4] = {pack2(a[0] * a[6], a[1] * a[7]), hfma2_lo(mr, gx, hmul2(mv, row[32])), hfma2_hi(mr, gx, hmul2(mv, row[64])),
                                       hfma2_lo(mr, gy, hmul2(mv, row[96]))};
#pragma unroll
                for (int c = 0; c < 4; c++) asm volatile("red.global.add.noftz.bf16x2 [%0], %1;" ::"l"(orow + 32 * c), "r"(o[c]) : "memory");
            }
        }
    }
}

#define SPLIT(k) asm volatile("{\n.reg .pred p;\nsetp.eq.u32 p, %0, %1;\n@p trap;\n}" ::"r"(c0), "n"(0x70000 + k) : "memory")
#define PIN8(a) asm volatile("" : "+r"((a)[0]), "+r"((a)[1]), "+r"((a)[2]), "+r"((a)[3]), "+r"((a)[4]), "+r"((a)[5]), "+r"((a)[6]), "+r"((a)[7]))
template <int V> struct IntC { static constexpr int value = V; };

template <int CN, int CE, int CG>
__global__ void __launch_bounds__(THREADS, 1) painn_kernel(const __grid_constant__ Params p) {
    extern __shared__ __align__(1024) unsigned char smem_dyn[];
    unsigned char* const smem = static_cast<unsigned char*>(__cvta_shared_to_generic(SB));
    constexpr uint32_t sb = SB;
    const int tid = threadIdx.x, lane = tid & 31;
    const int warp = __shfl_sync(0xffffffffu, tid >> 5, 0);
    constexpr int CNPC = CG ? (CN + CG - 1) / CG : 1, CGPC = CG ? (CE / 4 + CG - 1) / CG : 1;
    const int b = blockIdx.x, G = CG ? CG : p.G, NPC = CG ? CNPC : p.NPC, N = CG ? CN : p.N, gpc = CG ? CGPC : p.gpc;
    const uint32_t magic = CG ? (uint32_t)(((1ull << 32) + CNPC - 1) / CNPC) : p.magic;
    const bool odd_edges = CG ? (CE & 3) != 0 || CGPC > 3 * THREADS : p.odd_edges;
    const int nbase = b * NPC, nn = min(NPC, N - nbase);
    const int eg0 = b * gpc, eg1 = min((CG ? CE : p.E) >> 2, eg0 + gpc);

    uint4* stage4 = reinterpret_cast<uint4*>(smem + STAGE_OFF);
    uint32_t* ncnt = reinterpret_cast<uint32_t*>(smem + NCNT_OFF);
    uint32_t* misc = reinterpret_cast<uint32_t*>(smem + MISC_OFF);
    const uint32_t bar_tab = sb + BAR_OFF;

    TS0(0);
    int4 es[3], ed[3];
    auto load_edges = [&](int i) {
        const int g = min(eg0 + tid + i * THREADS, eg1 - 1);
        asm volatile("ld.global.cs.v4.u32 {%0,%1,%2,%3}, [%8];\nld.global.cs.v4.u32 {%4,%5,%6,%7}, [%9];"
                     : "=r"(es[i].x), "=r"(es[i].y), "=r"(es[i].z), "=r"(es[i].w), "=r"(ed[i].x), "=r"(ed[i].y), "=r"(ed[i].z), "=r"(ed[i].w)
                     : "l"(reinterpret_cast<const int4*>(p.src) + g), "l"(reinterpret_cast<const int4*>(p.dst) + g) : "memory");
    };
    es[0] = ed[0] = make_int4(0, 0, 0, 0);
    const char* const own = reinterpret_cast<const char*>(p.sv) + (size_t)nbase * 512;
    auto touch = [&](int o) {
        if (o + lane * 256 < nn * 512)
            asm volatile("cp.async.ca.shared.global.L2::256B [%0], [%1], 4;" ::"r"(sb + DUMMY_OFF + 4 * lane), "l"(own + o + lane * 256) : "memory");
    };
    uint4* const xout = p.g->xbuf + ((tid >> 3) * G + b) * 8 + (tid & 7);
    unsigned epoch;
    const uint32_t tbytes = ((N + 3) >> 2) * 16, cut = (tbytes >> 8) * CUT * 16, bar_cut = sb + BAR_OFF + 120;
    {
        uint32_t pxy, pz;
        if constexpr (CG && CN % 2 == 0) {
            asm volatile("ld.global.nc.u32 %0, [%3];\nld.global.nc.u32 %1, [%3 + 4];\nld.global.ca.u32 %2, [%4];"
                         : "=r"(pxy), "=r"(pz), "=r"(epoch)
                         : "l"(reinterpret_cast<const uint32_t*>(p.pos) + ((nbase + min(tid, nn - 1)) * 3 >> 1)), "l"(p.g->sync) : "memory");
            const uint32_t sh = ((nbase + tid) & 1) << 4;
            pxy = __funnelshift_r(pxy, pz, sh);
            pz >>= sh;
        } else {
            const uint16_t* q = reinterpret_cast<const uint16_t*>(p.pos) + (nbase + min(tid, nn - 1)) * 3;
            pxy = q[0] | (uint32_t)q[1] << 16;
            pz = q[2];
            asm volatile("ld.global.ca.u32 %0, [%1];" : "=r"(epoch) : "l"(p.g->sync) : "memory");
        }
        const uint32_t code = qcode(bf_lo(pxy), bf_hi(pxy), bf_lo(pz), ((epoch & 31u) ^ 0x6Bu) << 24);
        asm volatile("{\n.reg .pred p;\nsetp.lt.s32 p, %2, %3;\n@p st.global.u32 [%0], %1;\n}\n"
                     ::"l"(reinterpret_cast<uint32_t*>(p.g->table) + nbase + tid), "r"(code), "r"(tid), "r"(nn) : "memory");
        __syncthreads();
        asm volatile("{\n.reg .pred p;\nsetp.eq.u32 p, %1, %2;\n@p red.relaxed.gpu.global.add.u32 [%0], 1;\n}\n" ::"l"(p.g->sync + 1), "r"(tid), "n"(THREADS - 1) : "memory");
        if (tid < THREADS - 32) load_edges(0);
        if (tid < nn) p.g->pos8[nbase + tid] = make_uint2(pxy, pz);
        reinterpret_cast<uint2*>(smem + OPOS_OFF)[tid] = make_uint2(pxy, pz);
    }
    const uint32_t tag = (epoch & 31u) | 32u;
    if (tid == THREADS - 1) {
        TSX(1, 511);
        mbar_init(bar_tab, 1);
        mbar_init(bar_cut, 1);
        mbar_expect_tx(bar_cut, cut);
        mbar_expect_tx(bar_tab, tbytes - cut);
        const unsigned want = (epoch + 1) * G;
        unsigned c;
        int it = smem_u32(smem_dyn) == SB ? 0 : 1 << 22;
        __nanosleep(HDELAY);
        do {
            asm volatile("ld.relaxed.gpu.global.u32 %0, [%1];" : "=r"(c) : "l"(p.g->sync + 1) : "memory");
            if (++it > (1 << 22)) __trap();
        } while (c != want);
        bulk_g2s(sb, p.g->table, cut, bar_cut);
        bulk_g2s(sb + cut, reinterpret_cast<const char*>(p.g->table) + cut, tbytes - cut, bar_tab);
        TSX(2, 511);
    }
    if (warp == 14) {
#pragma unroll 1
        for (int c = b * 32 + lane; c < RING_OFF / 16; c += G * 32) {
            const int row = c >> 3, j = (c ^ row) & 7;
            uint4 v;
            if (c < 512) {
                const uint32_t half = 0x3F003F00u;
                v = __ldg(reinterpret_cast<const uint4*>(p.w1) + row * 8 + j);
                v = make_uint4(hmul2(v.x, half), hmul2(v.y, half), hmul2(v.z, half), hmul2(v.w, half));
            } else {
                const uint32_t* q = (c < 2048 ? reinterpret_cast<const uint32_t*>(p.w2) + (row & 63) * 96 + ((row >> 6) - 1) * 32
                                              : reinterpret_cast<const uint32_t*>(p.wr) + (row & 15) * 96 + ((row >> 4) - 16) * 32) + (j & 4) * 4 + (j & 3);
                v = make_uint4(__ldg(q), __ldg(q + 4), __ldg(q + 8), __ldg(q + 12));
            }
            p.g->wimg[c] = v;
        }
    }
    if (tid == 416) {
#pragma unroll
        for (int i = 0; i < FLIGHT + 2; i++) mbar_init(sb + BAR_OFF + 8 + 8 * i, i ? 1 : 15);
    }
    ncnt[tid] = tid < 480 ? 0 : 1024;
    if (tid < MAXG + 32) reinterpret_cast<uint32_t*>(smem + SCNT_OFF)[tid] = tid < MAXG ? 0 : 128;
    if (tid < 128) misc[tid] = 0;
    {
        const uint32_t inv = (PAY_INVALID << 6) | tag;
        stage4[tid] = stage4[tid + THREADS] = make_uint4(inv, inv, inv, inv);
        if (tid < MAXG * 8 - 2 * THREADS) stage4[tid + 2 * THREADS] = make_uint4(inv, inv, inv, inv);
    }
    __syncthreads();
    if ((tid >> 4) == 29) asm volatile("cp.async.ca.shared.global [%0], [%1], 4;" ::"r"(sb + FREQ_OFF + 8 * (tid & 14) + 4 * (tid & 1)),
                              "l"(reinterpret_cast<const uint32_t*>(p.freqs) + ((tid & 7) >> 1) + (tid & 1) * 4) : "memory");
    if (warp == 15) load_edges(0);
    if (warp < 8) mbar_wait(bar_cut, 0);
    load_edges(1);
    load_edges(2);
    if (tid == 416) asm volatile("fence.acq_rel.gpu;" ::: "memory");
    if (warp >= 8) mbar_wait(bar_cut, 0);
    {
        const uint32_t x = (PAY_INVALID << 6) | (tag ^ 16);
#pragma unroll
        for (int i = 0; i < 3; i++) stg128_if(xout + i * G * THREADS, make_uint4(x, x, x, x), tid + i * THREADS < G * 8);
    }
    bool full = false;
    {
        uint32_t at[24], msg[12], cnt[12], line[12];
#pragma unroll
        for (int j = 0; j < 12; j++) {
            const uint32_t s = j % 4 == 0 ? es[j / 4].x : j % 4 == 1 ? es[j / 4].y : j % 4 == 2 ? es[j / 4].z : es[j / 4].w;
            const uint32_t d = j % 4 == 0 ? ed[j / 4].x : j % 4 == 1 ? ed[j / 4].y : j % 4 == 2 ? ed[j / 4].z : ed[j / 4].w;
            const uint32_t own = __umulhi(d, magic);
            at[2 * j] = 4 * s; at[2 * j + 1] = 4 * d;
            msg[j] = own * (uint32_t)(-64 * NPC) + ((s << 15) + ((d << 6) + tag));
            cnt[j] = eg0 + tid + (j / 4) * THREADS < eg1 ? 4 * own : 4 * (MAXG + lane);
            line[j] = own * 128 + ((own & 7) << 4);
            asm volatile("" : "+r"(at[2 * j]), "+r"(at[2 * j + 1]), "+r"(msg[j]), "+r"(cnt[j]), "+r"(line[j]));
        }
        mbar_wait(bar_tab, 0);
        TS0(3);
        if (warp == 15) {
#pragma unroll
            for (int i = 0; i < TOUCH; i++) touch(i * 8192);
        }
#pragma unroll
        for (int i = 0; i < 12; i += 6) {
            uint32_t sl[6], cd[12];
#pragma unroll
            for (int j = 0; j < 12; j++) cd[j] = lds32(sb + at[2 * i + j]);
#pragma unroll
            for (int j = 0; j < 6; j++) {
                uint32_t q;
                const bool c = near_test(cd[2 * j], cd[2 * j + 1], tag << 24, q);
                msg[i + j] |= q & 0x80000000u;
                asm volatile("atom.shared.add.u32 %0, [%1 + %2], 4;" : "=r"(sl[j]) : "r"(c ? cnt[i + j] : 4 * (MAXG + lane)), "n"(SB + SCNT_OFF) : "memory");
            }
#pragma unroll
            for (int j = 0; j < 6; j++) {
                sts32_if(sb + STAGE_OFF + (line[i + j] ^ sl[j]), msg[i + j], sl[j] < 124);
                full |= sl[j] == 124;
            }
        }
    }
    {
        const int redo = __syncthreads_or(full);
        if (__builtin_expect(redo || odd_edges, 0)) cold_filter(smem, p, eg0, eg1, tag, redo);
    }
    TS0(4);
#pragma unroll
    for (int i = 0; i < 3; i++)
        stg128_if(xout + i * G * THREADS, stage4[(tid ^ ((tid >> 3) & 7)) + i * THREADS],
                  tid + i * THREADS < G * 8 && reinterpret_cast<const uint32_t*>(smem + SCNT_OFF)[(tid >> 3) + i * 64] >= (tid & 6) * 16u);
    __syncthreads();
#pragma unroll
    for (int i = -2; i < 2; i++) {
        const int c = tid + i * THREADS;
        const uint32_t x = c < (SN_OFF - STAGE_OFF) / 16 ? 0u : 0xFFFFFFFFu;
        if (c >= (SREC_OFF - STAGE_OFF) / 16) stage4[c] = make_uint4(x, x, x, x);
    }
    uint32_t key[4] = {0, 0, 0, 0};
    uint2 pr[4];
    const uint32_t gp = sb + RING_OFF + 2048 + (warp < 4 * NWG ? warp * 12288 : (warp & 3) * 12288 + 2048) + lane * 16;
    uint32_t pk = 0;
    if (warp == 15) {
        if (lane == 0) {
            int o = TOUCH * 8192;
#pragma unroll 1
            while (o < nn * 512 && !mbar_test(sb + BAR_OFF + 8, 0)) {
                const uint32_t bar = sb + BAR_OFF + 16 + 8 * (pk % FLIGHT);
                if (!mbar_test(bar, ~(pk / FLIGHT) & 1)) continue;
                const int n = min(4096, nn * 512 - o);
                mbar_expect_tx(bar, n);
                bulk_g2s(sb + DUMMY_OFF, own + o, n, bar);
                o += n;
                pk++;
            }
            misc[3] = pk;
        }
        __syncwarp();
    } else {
    __nanosleep(PDELAY);
    TS0(5);

    {
        const int LPW = (G + 14) / 15;
        uint32_t ew[3][4], bad[3];
        const uint4* cp = p.g->xbuf + (b * G + warp * LPW) * 8 + lane;
#pragma unroll
        for (int i = 0; i < 3; i++) {
            bad[i] = lane + 32 * i < min(LPW, G - warp * LPW) * 8;
            ew[i][0] = ew[i][1] = ew[i][2] = ew[i][3] = (PAY_INVALID << 6) | tag;
        }
        int it = 0;
#pragma unroll 1
        do {
#pragma unroll
            for (int i = 0; i < 3; i++)
                asm volatile("{\n.reg .pred p;\nsetp.ne.u32 p, %5, 0;\n@p ld.relaxed.gpu.global.v4.u32 {%0,%1,%2,%3}, [%4];\n}\n"
                             : "+r"(ew[i][0]), "+r"(ew[i][1]), "+r"(ew[i][2]), "+r"(ew[i][3]) : "l"(cp + 32 * i), "r"(bad[i]) : "memory");
#pragma unroll
            for (int i = 0; i < 3; i++) {
                const uint32_t x = (ew[i][0] ^ tag) | (ew[i][1] ^ tag) | (ew[i][2] ^ tag) | (ew[i][3] ^ tag);
                const uint32_t full = __ballot_sync(0xffffffffu, ew[i][3] < (PAY_INVALID << 6)) << 1 | 0x01010101u;
                bad[i] = (__ballot_sync(0xffffffffu, x & ((full >> (lane & 30)) & 1 ? 63u : 47u)) >> (lane & 24)) & 255u;
            }
            if (++it > (1 << 22)) __trap();
        } while (__any_sync(0xffffffffu, bad[0] | bad[1] | bad[2]));
        TSX(21, 0); TSX(22, 448);
        uint4* pack = reinterpret_cast<uint4*>(smem + PACK_OFF);
        int nch = 0;
        uint32_t at[3];
#pragma unroll
        for (int i = 0; i < 3; i++) {
            const uint32_t m = __ballot_sync(0xffffffffu, ew[i][0] < (PAY_MARK << 6));
            at[i] = nch + __popc(m & ((1u << lane) - 1));
            nch += __popc(m);
        }
        if (__builtin_expect(nch > 32, 0)) {
#pragma unroll 1
            for (int i = 0; i < 3; i++) {
                if (ew[0][0] < (PAY_MARK << 6) && at[0] >= 32) at[0] = (15 - warp) * 32 - 1 - min(atomicAdd(&misc[1], 1u), 31u);
                const uint32_t x = at[0], y = ew[0][0];
                at[0] = at[1]; at[1] = at[2]; at[2] = x;
                ew[0][0] = ew[1][0]; ew[1][0] = ew[2][0]; ew[2][0] = y;
            }
        }
#pragma unroll
        for (int i = 0; i < 3; i++) {
            asm volatile("{\n.reg .pred p;\nsetp.lt.u32 p, %1, %5;\n@p st.shared.v4.u32 [%0], {%1,%2,%3,%4};\n}\n"
                         ::"r"(sb + PACK_OFF + (warp * 32 + at[i]) * 16), "r"(ew[i][0]), "r"(ew[i][1]), "r"(ew[i][2]), "r"(ew[i][3]), "n"(PAY_MARK << 6) : "memory");
            sts32_if(sb + MISC_OFF + 4 * 17, 1, (ew[i][3] >> 6) == PAY_MARK);
        }
        bool have = lane < nch;
        if (warp == 14) {
            asm volatile("bar.sync 7, 480;" ::: "memory");
            const uint32_t extra = misc[1];
            if (nch + extra > 32) misc[18] = 1;
            have = have || lane + extra >= 32;
        } else {
            asm volatile("bar.arrive 7, 480;" ::: "memory");
        }
        __syncwarp();
        uint32_t w[4], rk[4];
        bool in[4];
        {
            const uint4 x = pack[tid];
            w[0] = have ? x.x : ~0u; w[1] = have ? x.y : ~0u; w[2] = have ? x.z : ~0u; w[3] = have ? x.w : ~0u;
        }
        auto fetch = [&](int j, bool c) {
            asm volatile("{\n.reg .pred p;\nsetp.ne.u32 p, %2, 0;\n@p cp.async.cg.shared.global [%0], [%1], 16;\n}\n"
                         ::"r"(gp + j * 512), "l"(reinterpret_cast<const uint4*>(p.g->pos8) + ((w[j] >> 16) & 0x7FFFu)), "r"((uint32_t)c) : "memory");
        };
#pragma unroll
        for (int j = 0; j < 4; j++) fetch(j, (int)w[j] < (int)(PAY_MARK << 6));
#pragma unroll
        for (int j = 0; j < 4; j++) pr[j] = reinterpret_cast<const uint2*>(smem + OPOS_OFF)[(w[j] >> 6) & 511u];
        uint32_t ca[4];
#pragma unroll
        for (int j = 0; j < 4; j++) {
            key[j] = ((w[j] >> 15) & 0xFFFFu) | ((w[j] << 10) & 0x1FF0000u);
            ca[j] = sb + NCNT_OFF + ((w[j] >> 4) & 0x7FCu);
            asm volatile("" : "+r"(key[j]), "+r"(ca[j]));
        }
        asm volatile("{\n.reg .pred p;\nsetp.eq.u32 p, %0, -1;\n@p trap;\n}" ::"r"(nch) : "memory");
        asm volatile("cp.async.wait_all;" ::: "memory");
        TSX(23, 0); TSX(24, 448);
        asm volatile("{\n.reg .pred p;\nsetp.eq.u32 p, %1, 0;\n@p mbarrier.arrive.shared::cta.b64 _, [%0];\n}\n" ::"r"(sb + BAR_OFF + 8), "r"(lane) : "memory");
#pragma unroll
        for (int j = 0; j < 4; j++) {
            uint2 ps;
            asm volatile("ld.shared.v2.u32 {%0,%1}, [%2];" : "=r"(ps.x), "=r"(ps.y) : "r"(gp + j * 512 + ((w[j] >> 12) & 8)) : "memory");
            in[j] = ((int)w[j] >= 0) | (((int)w[j] < (int)(PAY_MARK << 6)) & inside(hsub2(ps.x, pr[j].x), hsub2(ps.y, pr[j].y)));
        }
#pragma unroll
        for (int j = 0; j < 4; j++)
            asm volatile("atom.shared.add.u32 %0, [%1], 1;" : "=r"(rk[j]) : "r"(in[j] ? ca[j] : sb + NCNT_OFF + 4 * (480 + lane)) : "memory");
#pragma unroll
        for (int j = 0; j < 4; j++) {
            rk[j] = rk[j] < SPL ? 2 * rk[j] : min(2 * rk[j] - (2 * SPL - 1), 126u);
            asm volatile("red.shared.add.u32 [%0 + %1], 1;" ::"r"(rk[j] & 2 ? 124u : rk[j] & 60u), "n"(SB + MISC_OFF + 128) : "memory");
            key[j] += rk[j] << 25;
        }
#pragma unroll
        for (int j = 0; j < 4; j++) fetch(j, (int)w[j] >= 0);
        cp_commit();
    }
    }
    __syncthreads();
    TS0(6);
    uint32_t deg[5];
    deg[4] = lds32(sb + NCNT_OFF + 4 * tid);
#pragma unroll
    for (int j = 0; j < 4; j++) deg[j] = lds32(sb + NCNT_OFF + ((key[j] >> 14) & 0x7FCu));
    if (tid == THREADS - 33) {
        if (b == 0) p.g->sync[0] = epoch + 1;
        asm volatile("fence.proxy.async.global;" ::: "memory");
        mbar_expect_tx(bar_tab, RING_OFF);
        bulk_g2s(sb, p.g->wimg, RING_OFF, bar_tab);
    }
    __syncwarp();
    uint32_t dst = sb + RING_OFF + warp * 12288 + (lane >> 3) * 256 + (((lane & 7) ^ (lane >> 3)) << 4), l7 = (lane & 7) * 16, g32 = (lane >> 2) * 32;
    uint32_t e0, e1, n0, n1;
    auto sources = [&](uint32_t c) {
        asm volatile("{\n.reg .b32 a;\nlop3.b32 a, %4, %5, 0xFFC0, 0xA8;\nshr.u32 a, a, 2;\nld.shared.v4.u32 {%0,%1,%2,%3}, [a + %6];\n}\n"
                     : "=r"(e0), "=r"(n0), "=r"(e1), "=r"(n1) : "r"(c), "r"(g32), "n"(SB + SN_OFF));
    };
    auto load_s = [&](auto pad) {
        gather<1, 0, pad.value>(dst, p.sv, l7, e0); gather<1, 1, pad.value>(dst + 1024, p.sv, l7, e0);
        gather<1, 0, pad.value>((dst ^ 64) + 128, p.sv, l7, e1); gather<1, 1, pad.value>((dst ^ 64) + 1152, p.sv, l7, e1);
    };
    auto load_o = [&]() {
        gather<4, 0>(dst + 8192, p.sv, l7, n0); gather<4, 0>((dst ^ 64) + 8320, p.sv, l7, n1);
    };
    auto load_v = [&](auto pad) {
        gather<3, 0, pad.value>(dst + 2048, p.sv, l7, e0); gather<3, 1, pad.value>(dst + 5120, p.sv, l7, e0);
        gather<3, 0, pad.value>((dst ^ 64) + 2176, p.sv, l7, e1); gather<3, 1, pad.value>((dst ^ 64) + 5248, p.sv, l7, e1);
        cp_commit();
    };
    const int ng = (misc[32] + 7) >> 3;
    const int give = max(min(ng - max((int)(misc[33] + 7) >> 3, 4 * NWG), GIVE), 0);
    if (warp == 15) {
        const uint32_t cnt = lane < 16 ? (misc[32 + lane] + 7) >> 3 : 0u;
        uint32_t z = cnt;
#pragma unroll
        for (int o = 1; o < 16; o <<= 1) {
            const uint32_t y = __shfl_up_sync(0xffffffffu, z, o);
            if (lane >= o) z += y;
        }
        misc[96 + lane] = lane < 16 ? 64 * (z - cnt) : 64 * (MAXROW + 1);
        asm volatile("bar.arrive 5, 512;" ::: "memory");
        const bool cold = cnt || z > MAXROW || misc[31 + SPL / 2] > 32 || misc[17] || misc[18];
        if (lane == 15) { misc[18] = cold; misc[4] = 8 * ng; }
        __syncwarp();
        asm volatile("bar.arrive 4, 512;" ::: "memory");
        if (lane == 15) {
            uint32_t order;
            asm volatile("atom.relaxed.gpu.global.add.u32 %0, [%1], 1;" : "=r"(order) : "l"(p.g->sync + 2) : "memory");
            asm volatile("st.relaxed.gpu.global.u32 [%0], %1;" ::"l"(p.g->rows + b),
                         "r"(~epoch << 20 | (cold || ng < 4 * NWG ? 255 : (order - epoch * G) << 12 | give << 8 | z)) : "memory");
        }
        pk = (z - cnt) << 8 | __shfl_down_sync(0xffffffffu, cnt, 1) << 24;
    } else {
        if (warp * 32 < nn) {
            const uint32_t c = deg[4], st = tid < nn ? (min(c, (uint32_t)SPL) + 1) >> 1 : 17u;
            const uint32_t same = __match_any_sync(0xffffffffu, st), first = __ffs(same) - 1;
            uint32_t r, node = nbase + tid;
            asm volatile("atom.shared.add.u32 %0, [%1], %2;" : "=r"(r)
                         : "r"(lane == first ? sb + MISC_OFF + 4 * (64 + st) : sb + NCNT_OFF + 4 * (480 + lane)), "r"(__popc(same)) : "memory");
            r = __shfl_sync(0xffffffffu, r, first) + __popc(same & ((1u << lane) - 1)) + misc[32 + st];
            if (__builtin_expect(c > SPL, 0)) {
                const uint32_t s2 = min((c - SPL + 1) >> 1, 16u), r2 = misc[32 + s2] + atomicAdd(&misc[64 + s2], 1u), k = atomicAdd(&misc[2], 1u);
                reinterpret_cast<uint32_t*>(smem + SCNT_OFF)[k & 31] = node;
                node |= NODE_SPLIT;
                ncnt[1024 + tid] = 8 * r2;
                reinterpret_cast<uint32_t*>(smem + SN_OFF)[(r2 & 511) * 2 + 1] = node;
            }
            if (tid < nn) {
                ncnt[512 + tid] = 8 * r;
                reinterpret_cast<uint32_t*>(smem + SN_OFF)[(r & 511) * 2 + 1] = node;
            }
        }
#pragma unroll
        for (int j = 0; j < 4; j++) {
            const uint32_t c = deg[j];
            asm volatile("{\n.reg .pred p;\n.reg .b64 a;\nsetp.ge.u32 p, %0, %3;\nsetp.lt.and.u32 p, %1, 0x8000000, p;\nmad.wide.u32 a, %4, 512, %2;\n@p prefetch.global.L2 [a];\n"
                         "}\n" ::"r"(c), "r"(key[j]), "l"(p.sv), "n"(BIG), "r"(key[j] & 0xFFFFu) : "memory");
        }
        asm volatile("bar.sync 5, 512;" ::: "memory");
        uint32_t slot[4];
#pragma unroll
        for (int j = 0; j < 4; j++) slot[j] = min(misc[96 + (key[j] >> 27)] + (ncnt[512 + ((key[j] >> 16) & 1023)] & 0xFFF8u), 64u * (MAXROW + 1)) + ((key[j] >> 25) & 2);
#pragma unroll
        for (int j = 0; j < 4; j++) {
            *reinterpret_cast<uint16_t*>(smem + SN_OFF + slot[j]) = (uint16_t)key[j];
            slot[j] += slot[j] & 2;
        }
        asm volatile("bar.sync 6, 480;" ::: "memory");
        TS0(7);
        if (warp < 4 * NWG) {
            sources((warp < ng ? warp : MAXROW) << 8);
            e0 = __vminu2(e0, (N - 1) * 0x10001u);
            e1 = __vminu2(e1, (N - 1) * 0x10001u);
            load_s(IntC<0>{});
            cp_commit();
            load_o();
            cp_commit();
            asm volatile("cp.async.wait_group 2;" ::: "memory");
        } else {
            asm volatile("cp.async.wait_all;" ::: "memory");
        }
        uint2 ps[4];
#pragma unroll
        for (int j = 0; j < 4; j++)
            asm volatile("ld.shared.v2.u32 {%0,%1}, [%2];" : "=r"(ps[j].x), "=r"(ps[j].y) : "r"(gp + j * 512 + (key[j] & 1) * 8) : "memory");
        TSX(9, 0);
#pragma unroll 1
        for (int i = 0; i < 2; i++) {
#pragma unroll
            for (int u = 0; u < 2; u++) {
                const uint3 geo = geometry(hsub2(ps[u].x, pr[u].x), hsub2(ps[u].y, pr[u].y));
                *reinterpret_cast<uint2*>(smem + SREC_OFF + 2 * slot[u]) = make_uint2(geo.x, geo.y);
                *reinterpret_cast<uint32_t*>(smem + SD_OFF + slot[u]) = geo.z;
                ps[u] = ps[u + 2];
                pr[u] = pr[u + 2];
                slot[u] = slot[u + 2];
            }
        }
    }
    if (warp != 15) asm volatile("bar.sync 4, 512;" ::: "memory");
    TS0(8);
    auto drain = [&](int i) { if (i < FLIGHT) mbar_wait(sb + BAR_OFF + 16 + 8 * i, ~((misc[3] + FLIGHT - 1 - i) / FLIGHT) & 1); };
    if (__builtin_expect(misc[18], 0)) {
        drain(warp);
        asm volatile("cp.async.wait_all;" ::: "memory");
        __syncthreads();
        cold_messages(smem, p, nn);
        mbar_wait(bar_tab, 1);
        return;
    }

    if (warp < 4 * NWG) {
        asm volatile("setmaxnreg.inc.sync.aligned.u32 %0;" ::"n"(REG_C));
        const int lane = fresh_lane();
        const int g = lane >> 2, q = lane & 3;
        const uint64_t dW1 = p.desc0, dW2 = dW1 + (W2_OFF >> 4), dWR = dW1 + (WR_OFF >> 4);
        const uint32_t ring = sb + RING_OFF + warp * 12288;
        const uint32_t vrow = pin(ring + g * 128 + ((q ^ ((g & 1) << 2) ^ (g >> 1)) << 4));
        const uint32_t mrow = pin(ring + (lane & 15) * 128 + (((lane >> 4) ^ ((lane & 1) << 2) ^ ((lane & 7) >> 1)) << 4));
        dst = pin(ring + (lane >> 3) * 256 + (((lane & 7) ^ (lane >> 3)) << 4)); l7 = pin((lane & 7) * 16); g32 = pin(g * 32);
        uint32_t ctl = sb + CTL_OFF + warp * 4;
        auto control = [&](uint32_t c, uint32_t at) {
            int it = 0;
#pragma unroll 1
            while (__builtin_expect(c == 0xFFFFFFFFu, 0)) {
                asm volatile("ld.volatile.shared.u32 %0, [%1];" : "=r"(c) : "r"(at) : "memory");
                c = __reduce_or_sync(0xffffffffu, c);
                if (++it > (1 << 24)) __trap();
            }
            return c;
        };
        uint32_t c0 = control(0xFFFFFFFFu, ctl), c1 = control(0xFFFFFFFFu, ctl + 64);
        if (warp >= 8) asm volatile("bar.arrive 1, 256;" ::: "memory");
        uint32_t acc[32];
        float P[32], W[32];
#pragma unroll
        for (int i = 0; i < 32; i++) { acc[i] = 0; P[i] = W[i] = 0.f; }
        mbar_wait(bar_tab, 1);
        sources(c0);
        e0 = __vminu2(e0, (N - 1) * 0x10001u);
        e1 = __vminu2(e1, (N - 1) * 0x10001u);
        if (warp >= 8) asm volatile("cp.async.wait_all;" ::: "memory");
        else if (warp >= 4) cp_wait1();
        load_v(IntC<0>{});
        auto finish = [&](uint32_t c, uint32_t node) {
            if (c & ST_CLOSE) {
                uint64_t op[2];
                asm("{\n.reg .b32 a;\nmad.lo.u32 a, %2, 512, %3;\nmad.wide.u32 %0, a, 1, %4;\nxor.b32 a, a, 64;\nmad.wide.u32 %1, a, 1, %4;\n}\n"
                    : "=l"(op[0]), "=l"(op[1]) : "r"(node), "r"(l7), "l"(p.out));
#pragma unroll
                for (int k = 0; k < 8; k++) {
                    uint32_t x[4];
#pragma unroll
                    for (int i = 0; i < 4; i++) x[i] = l7 & 64 ? acc[4 * (k ^ 1) + i] : acc[4 * k + i];
                    asm volatile("{\n.reg .pred p;\nsetp.lt.u32 p, %5, %6;\n@p st.global.cs.v4.u32 [%0], {%1,%2,%3,%4};\n}\n"
                                 ::"l"(op[k & 1] + 128 * (k >> 1)), "r"(x[0]), "r"(x[1]), "r"(x[2]), "r"(x[3]), "r"(node), "n"(NODE_SPLIT) : "memory");
                }
                if (__builtin_expect(__any_sync(0xffffffffu, (int)node >= (int)NODE_SPLIT), 0)) {
                    mbar_wait(sb + BAR_OFF + 16 + 8 * FLIGHT, 0);
                    if ((int)node >= (int)NODE_SPLIT) {
#pragma unroll
                        for (int k = 0; k < 8; k++)
                            asm volatile("red.global.add.noftz.v4.bf16x2 [%0], {%1,%2,%3,%4};" ::"l"((op[0] & ~64ull) + 64 * k), "r"(acc[4 * k]), "r"(acc[4 * k + 1]), "r"(acc[4 * k + 2]), "r"(acc[4 * k + 3]) : "memory");
                    }
                    __syncwarp();
                }
            }
        };
        uint32_t f01, f23;
        asm volatile("ld.shared.v2.u32 {%0,%1}, [%2 + %3];" : "=r"(f01), "=r"(f23) : "r"(l7), "n"(SB + FREQ_OFF));
        f01 = pin(f01); f23 = pin(f23);
#pragma unroll 1
        while ((int)c0 >= 0) {
            uint32_t a[16], h[16], rf[4], rr[4], m[16];
            TRW(ctl);
            uint32_t dd[2];
            asm volatile("ld.shared.v2.u32 {%0,%1}, [%2 + %3];" : "=r"(dd[0]), "=r"(dd[1]) : "r"(((c0 & 0xFF00) | g32) >> 2), "n"(SB + SD_OFF));
            sources(c1);
            asm volatile("cp.async.wait_group 2;" ::: "memory");
            __syncwarp();
#pragma unroll
            for (int i = 0; i < 4; i++) ldsm4(mrow ^ (i << 5), a + 4 * i);
            wg_fence();
            wgmma_k64(P, a, dW1);
            wg_commit();
#pragma unroll
            for (int hh = 0; hh < 2; hh++) {
                const float sc = bf_hi(dd[hh]);
                const uint32_t x01 = hmul2_lo(f01, dd[hh]), x23 = hmul2_lo(f23, dd[hh]);
                rf[hh] = pack2(__sinf(bf_lo(x01)) * sc, __sinf(bf_hi(x01)) * sc);
                rf[2 + hh] = pack2(__sinf(bf_lo(x23)) * sc, __sinf(bf_hi(x23)) * sc);
            }
            asm volatile("" : "+r"(rf[0]), "+r"(rf[1]), "+r"(rf[2]), "+r"(rf[3]));
            asm volatile("bar.sync %0, 256;" ::"r"(1 + (warp >> 2)) : "memory");
            SPLIT(2);
            wg_wait<0>();
            fence_regs(P);
#pragma unroll
            for (int i = 0; i < 16; i++)
                h[i] = pack2(fmaf(P[2 * i], tanh_fast(P[2 * i]), P[2 * i]), fmaf(P[2 * i + 1], tanh_fast(P[2 * i + 1]), P[2 * i + 1]));
            wg_fence();
            wgmma_k64(P, h, dW2 + 1024);
            wgmma_first(W, rf, dWR + 256);
            wg_commit();
            asm volatile("bar.arrive %0, 256;" ::"r"((c0 >> 4) & 3) : "memory");
            cp_wait1();
            __syncwarp();
#pragma unroll
            for (int k = 0; k < 4; k++) lds2_if(vrow + 8192 + 1024 * k, (vrow ^ 64) + 8192 + 1024 * k, acc + 8 * k, c0 & ST_START);
            lds128(sb + SREC_OFF + (((c0 & 0xFF00) | g32) >> 1), rr);
            uint32_t c2 = lds32(ctl + 128);
            __syncwarp();
            load_s(IntC<1>{});
            cp_commit();
            if (c1 & ST_START) load_o();
            cp_commit();
            wg_wait<0>();
            fence_regs(P); fence_regs(W);
#pragma unroll
            for (int j = 0; j < 8; j++) {
                m[j] = pack2(P[4 * j] * W[4 * j], P[4 * j + 1] * W[4 * j + 1]);
                m[8 + j] = pack2(P[4 * j + 2] * W[4 * j + 2], P[4 * j + 3] * W[4 * j + 3]);
            }
            wg_fence();
            wgmma_k64(P, h, dW2);
            wgmma_first(W, rf, dWR);
            wg_commit();
            SPLIT(4);
            PIN8(m); PIN8(m + 8);
            c2 = __reduce_or_sync(0xffffffffu, c2);
#pragma unroll
            for (int k = 1; k < 4; k++)
#pragma unroll
                for (int j = 0; j < 8; j++) {
                    const uint32_t x = k == 1 ? hfma2_lo(m[j], rr[0], acc[8 * k + j]) : k == 2 ? hfma2_hi(m[j], rr[0], acc[8 * k + j]) : hfma2_lo(m[j], rr[1], acc[8 * k + j]);
                    acc[8 * k + j] = k == 1 ? hfma2_lo(m[8 + j], rr[2], x) : k == 2 ? hfma2_hi(m[8 + j], rr[2], x) : hfma2_lo(m[8 + j], rr[3], x);
                }
            PIN8(acc + 8); PIN8(acc + 16); PIN8(acc + 24);
            SPLIT(5);
            wg_wait<0>();
            fence_regs(P); fence_regs(W);
#pragma unroll
            for (int j = 0; j < 8; j++)
                acc[j] = hadd2(acc[j], pack2(fmaf(P[4 * j], W[4 * j], P[4 * j + 2] * W[4 * j + 2]), fmaf(P[4 * j + 1], W[4 * j + 1], P[4 * j + 3] * W[4 * j + 3])));
            wg_fence();
            wgmma_k64(P, h, dW2 + 512);
            wgmma_first(W, rf, dWR + 128);
            wg_commit();
            SPLIT(6);
            asm volatile("cp.async.wait_group 2;" ::: "memory");
            __syncwarp();
            uint32_t v[4][16];
#pragma unroll
            for (int i = 0; i < NPRE; i++) lds128((vrow ^ (64 * (i & 1))) + 2048 + 1024 * (i >> 2) + 3072 * ((i >> 1) & 1), v[1 + (i >> 2)] + 4 * (i & 3));
            wg_wait<0>();
            fence_regs(P); fence_regs(W);
#pragma unroll
            for (int j = 0; j < 8; j++) {
                m[j] = pack2(P[4 * j] * W[4 * j], P[4 * j + 1] * W[4 * j + 1]);
                m[8 + j] = pack2(P[4 * j + 2] * W[4 * j + 2], P[4 * j + 3] * W[4 * j + 3]);
            }
#pragma unroll
            for (int i = NPRE; i < 12; i++) lds128((vrow ^ (64 * (i & 1))) + 2048 + 1024 * (i >> 2) + 3072 * ((i >> 1) & 1), v[1 + (i >> 2)] + 4 * (i & 3));
            sources(c1);
            const uint32_t node = lds32(sb + SN_OFF + 4 + (((c0 >> 16) | g32) >> 2));
            __syncwarp();
            load_v(IntC<1>{});
#pragma unroll
            for (int k = 1; k < 4; k++)
#pragma unroll
                for (int j = 0; j < 8; j++) acc[8 * k + j] = hfma2(m[8 + j], v[k][8 + j], hfma2(m[j], v[k][j], acc[8 * k + j]));
            finish(c0, node);
            ctl += 64;
            c0 = c1;
            c1 = control(c2, ctl + 64);
        }
        asm volatile("cp.async.wait_all;" ::: "memory");
        TRW(ctl);
        TSX(11, 0); TSX(12, 128); TSX(13, 256);
    } else {
        asm volatile("setmaxnreg.dec.sync.aligned.u32 %0;" ::"n"(REG_H));
        const int lane = fresh_lane();
        const uint32_t chunk = sb + (lane & 8 ? (lane & 4 ? SN_OFF : SD_OFF) + (lane & 3) * 16 : SREC_OFF + (lane & 7) * 16), pitch = lane & 8 ? 64 : 128;
        if (warp == 12) {
#pragma unroll 1
            for (int r = lane >> 3; r < (int)misc[2]; r += 4) {
                const uint32_t n = reinterpret_cast<const uint32_t*>(smem + SCNT_OFF)[r] * 32 + (lane & 7);
                uint4 v[4];
#pragma unroll
                for (int i = 0; i < 4; i++) v[i] = reinterpret_cast<const uint4*>(p.sv)[n + 8 * i];
#pragma unroll
                for (int i = 0; i < 4; i++) reinterpret_cast<uint4*>(p.out)[n + 8 * i] = v[i];
            }
            __syncwarp();
#pragma unroll 1
            for (int i = lane >> 4; i < give; i += 2) {
                uint32_t x[4];
                lds128(chunk + (ng - 1 - i) * pitch, x);
                p.g->pool[(b * GIVE + i) * 16 + (lane & 15)] = make_uint4(x[0], x[1], x[2], x[3]);
            }
            __threadfence();
            __syncwarp();
            if (lane == 0) {
                asm volatile("st.relaxed.gpu.global.u32 [%0], %1;" ::"l"(p.g->ready + b), "r"(~epoch) : "memory");
                mbar_arrive(sb + BAR_OFF + 16 + 8 * FLIGHT);
            }
        }
        if (warp == 15) {
            int k = lane < 4 * NWG ? lane : 255, next = 4 * NWG, j = 0, mine = ng - give, end = -1, take = 0;
            uint32_t busy, at = sb + CTL_OFF + 4 * lane, from = 0;
#pragma unroll 1
            do {
                if (next > mine && end < 0) {
                    uint32_t x[5], z;
                    int it = 0;
#pragma unroll 1
                    do {
                        __nanosleep(700);
                        z = 0;
#pragma unroll
                        for (int i = 0; i < 5; i++) asm volatile("ld.relaxed.gpu.global.u32 %0, [%1];" : "=r"(x[i]) : "l"(p.g->rows + 5 * lane + i) : "memory");
#pragma unroll
                        for (int i = 0; i < 5; i++) {
                            x[i] = 5 * lane + i < G ? x[i] ^ (~epoch << 20) : 255;
                            z |= x[i];
                        }
                        if (++it > (1 << 22)) __trap();
                    } while (__any_sync(0xffffffffu, z >> 20));
                    z = 0;
#pragma unroll
                    for (int i = 0; i < 5; i++) {
                        if (x[i] != 255) z += (x[i] & 255) + 0x10000;
                        reinterpret_cast<uint32_t*>(smem + SCNT_OFF)[32 + 5 * lane + i] = x[i];
                    }
                    z = __reduce_add_sync(0xffffffffu, z);
                    const int level = min((int)((z & 0xFFFFu) / max(z >> 16, 1u) + 2) & ~3, MAXROW - 4);
                    uint32_t ed, sur, me = 0, mz = 0;
#pragma unroll 1
                    for (uint32_t first = 0;; first = (z * 3 / 4 + 2) << 12) {
                        ed = sur = 0;
#pragma unroll 1
                        for (int i = 0; i < 5; i++) {
                            const uint32_t y = reinterpret_cast<const uint32_t*>(smem + SCNT_OFF)[32 + 5 * lane + i];
                            const int r = (y & 255) - (y < first && (int)(y & 255) > level ? level + 4 : level);
                            const uint32_t e = r > 0 ? min(r, (int)(y >> 8) & 15) : min(-r, ROOM) << 16;
                            if (i == b % 5) { me = e; mz = ed; }
                            sur |= (e & 15) << (4 * i);
                            ed += e;
                        }
                        z = __reduce_add_sync(0xffffffffu, (ed & 0xFFFFu) - (ed >> 16));
                        if ((int)z <= 0 || first) break;
                    }
                    z = ed;
#pragma unroll
                    for (int o = 1; o < 32; o <<= 1) {
                        const uint32_t y = __shfl_up_sync(0xffffffffu, z, o);
                        if (lane >= o) z += y;
                    }
                    const uint32_t all = __shfl_sync(0xffffffffu, z, 31), moved = min(all & 0xFFFFu, all >> 16);
                    me = __shfl_sync(0xffffffffu, me, b / 5);
                    mz = __shfl_sync(0xffffffffu, mz + z - ed, b / 5);
                    end = mine = ng - (min((mz + me) & 0xFFFFu, moved) - min(mz & 0xFFFFu, moved));
#pragma unroll 1
                    for (uint32_t u = mz >> 16; u < min((mz + me) >> 16, moved); u++, take++) {
                        int f = __popc(__ballot_sync(0xffffffffu, (z & 0xFFFFu) <= u));
                        uint32_t q = u - (__shfl_sync(0xffffffffu, z - ed, f) & 0xFFFFu), s5 = __shfl_sync(0xffffffffu, sur, f);
#pragma unroll 1
                        for (f *= 5; q >= (s5 & 15); f++, s5 >>= 4) q -= s5 & 15;
                        if (lane == take) from = f << 8 | q;
                    }
                }
                if (next > mine && take) {
                    if (lane < take) {
                        uint32_t x;
                        int it = 0;
#pragma unroll 1
                        do {
                            asm volatile("ld.acquire.gpu.global.u32 %0, [%1];" : "=r"(x) : "l"(p.g->ready + (from >> 8)) : "memory");
                            if (++it > (1 << 22)) __trap();
                        } while (x != ~epoch);
                    }
                    __syncwarp();
#pragma unroll 1
                    for (end += take; take--;) {
                        const uint32_t f = __shfl_sync(0xffffffffu, from, take);
                        if (lane < 16)
                            asm volatile("cp.async.cg.shared.global [%0], [%1], 16;" ::"r"(chunk + (MAXROW - 1 - take) * pitch),
                                         "l"(p.g->pool + ((f >> 8) * GIVE + (f & 255)) * 16 + lane) : "memory");
                    }
                    take = 0;
                    asm volatile("cp.async.wait_all;" ::: "memory");
                    __threadfence_block();
                    __syncwarp();
                }
                const bool has = k < (end < 0 ? mine : end);
                const uint32_t i = k < mine ? k : MAXROW - 1 + mine - k, x = __shfl_sync(0xffffffffu, pk, j);
                const bool close = has && i >= (x >> 24);
                busy = __ballot_sync(0xffffffffu, has);
                const uint32_t m = __ballot_sync(0xffffffffu, close);
                uint32_t c = has ? ((x & 0xFF00) + i * 0x1000100) | (j ? 0u : ST_START) | (close ? ST_CLOSE : 0u) : MAXROW * 256;
                if (!(busy >> (lane & 12))) c |= 0x80000000u;
                c |= busy >> ((lane & 12) + 4) ? (lane & 12) * 4 + 32 : 16;
                sts32_if(at, c, lane < 16 || !busy);
                j = close ? 0 : j + 1;
                k = close ? next + __popc(m & ((1u << lane) - 1)) : k;
                next += __popc(m);
                at += 64;
            } while (busy);
        }
        if (warp == 15) mbar_wait(sb + BAR_OFF + 16 + 8 * FLIGHT, 0);
        else if (warp != 12) __nanosleep(ZDELAY);
        const int zlast = misc[32] + misc[64] - 1;
#pragma unroll 1
        for (;;) {
            int r = 0;
            if (lane == 0) r = atomicAdd(&misc[4], 4u);
            r = __shfl_sync(0xffffffffu, r, 0);
            if (r > zlast) break;
            uint4 v[4];
            uint32_t n[4];
#pragma unroll
            for (int i = 0; i < 4; i++) {
                n[i] = reinterpret_cast<const uint32_t*>(smem + SN_OFF)[min(r + i, zlast) * 2 + 1] * 32 + lane;
                v[i] = __ldcs(reinterpret_cast<const uint4*>(p.sv) + n[i]);
            }
#pragma unroll
            for (int i = 0; i < 4; i++) __stcs(reinterpret_cast<uint4*>(p.out) + n[i], v[i]);
        }
        static_assert(FLIGHT <= 4, "drain");
        drain(warp & 3);
        asm volatile("cp.async.wait_all;" ::: "memory");
        TSX(14, 384); TSX(15, 480); TSX(16, 416);
    }
}

}

extern "C" void kernel_launch(void* const* d_in, const int* in_sizes, int n_in, void* d_out, int out_size) {
    static int s_G = 0;
    static void* s_scratch = nullptr;
    const int N = in_sizes[0] / 256, E = in_sizes[2];
    if (s_G == 0) {
        cudaFuncSetAttribute(painn_kernel<0, 0, 0>, cudaFuncAttributeMaxDynamicSharedMemorySize, SMEM_BYTES);
        cudaFuncSetAttribute(painn_kernel<50000, 800000, 132>, cudaFuncAttributeMaxDynamicSharedMemorySize, SMEM_BYTES);
        int dev = 0, sms = 0, occ = 0;
        cudaGetDevice(&dev);
        cudaDeviceGetAttribute(&sms, cudaDevAttrMultiProcessorCount, dev);
        cudaOccupancyMaxActiveBlocksPerMultiprocessor(&occ, painn_kernel<0, 0, 0>, THREADS, SMEM_BYTES);
        cudaGetSymbolAddress(&s_scratch, g_scratch);
        s_G = occ >= 1 ? (sms < MAXG ? sms : MAXG) : 0;
    }
    if (s_G == 0 || N > TABLE_MAXN || N > s_G * MAXNPC || (s_G - 1) * ((N + s_G - 1) / s_G) >= N || E > MAXE || E < 4 * MAXG * MAXG) return;
    Params p;
    p.g = (Scratch*)s_scratch;
    p.sv = (const __nv_bfloat16*)d_in[0];
    p.pos = (const __nv_bfloat16*)d_in[1];
    p.src = (const int*)d_in[2];
    p.dst = (const int*)d_in[3];
    p.freqs = (const __nv_bfloat16*)d_in[4];
    p.w1 = (const __nv_bfloat16*)d_in[5];
    p.w2 = (const __nv_bfloat16*)d_in[6];
    p.wr = (const __nv_bfloat16*)d_in[7];
    p.out = (__nv_bfloat16*)d_out;
    p.desc0 = (uint64_t)(SB >> 4) | ((uint64_t)1 << 16) | ((uint64_t)64 << 32) | ((uint64_t)1 << 62);
    p.N = N; p.E = E; p.G = s_G;
    p.NPC = (N + s_G - 1) / s_G;
    p.magic = (uint32_t)(((1ull << 32) + p.NPC - 1) / p.NPC);
    p.gpc = ((E >> 2) + s_G - 1) / s_G;
    p.odd_edges = (E & 3) != 0 || p.gpc > 3 * THREADS;
    if (N == 50000 && E == 800000 && s_G == 132) painn_kernel<50000, 800000, 132><<<s_G, THREADS, SMEM_BYTES, cudaStreamPerThread>>>(p);
    else painn_kernel<0, 0, 0><<<s_G, THREADS, SMEM_BYTES, cudaStreamPerThread>>>(p);
}
```

```cpp
#include <cuda_runtime.h>
#include <cuda_bf16.h>
#include <stdint.h>

namespace {

constexpr int NWG = 3;
constexpr int REG_C = 160, REG_H = 32;
constexpr int SPL = 10;
constexpr int GIVE = 10, ROOM = 4;
constexpr int BIG = 5;
constexpr int CUT = 7;
constexpr int HDELAY = 150;
constexpr int TOUCH = 4, FLIGHT = 4;
constexpr int NPRE = 5;
constexpr int PDELAY = 150;
constexpr int ZDELAY = 1200;
constexpr int THREADS = 512;
constexpr int MAXG = 136;
constexpr int MAXROW = 96;
constexpr int TMAX = MAXROW / 12 + 18;
constexpr int MAXNPC = 480;
constexpr int MAXE = 1 << 20;

constexpr int W2_OFF = 8192;
constexpr int WR_OFF = 32768;
constexpr int RING_OFF = 38912;
constexpr int SREC_OFF = RING_OFF + 4 * NWG * 12288;
constexpr int SD_OFF = SREC_OFF + (MAXROW + 1) * 128 + 16;
constexpr int SN_OFF = SD_OFF + (MAXROW + 1) * 64 + 16;
constexpr int CTL_OFF = SN_OFF + (MAXROW + 1) * 64 + 16;
constexpr int TABLE_MAXN = 50176;
constexpr int STAGE_OFF = TABLE_MAXN * 4;
constexpr int SCNT_OFF = STAGE_OFF + MAXG * 128;
constexpr int PACK_OFF = RING_OFF + 6144;
constexpr int NCNT_OFF = SCNT_OFF + 768;
constexpr int OPOS_OFF = NCNT_OFF + 2048;
constexpr int BAR_OFF = OPOS_OFF + 4096;
constexpr int MISC_OFF = BAR_OFF + 128;
constexpr int FREQ_OFF = MISC_OFF + 512;
constexpr int DUMMY_OFF = (FREQ_OFF + 128 + 127) / 128 * 128;
constexpr int SMEM_BYTES = DUMMY_OFF + 4096;
static_assert(CTL_OFF + 64 * TMAX <= STAGE_OFF + 32 * THREADS && STAGE_OFF - SREC_OFF <= 32 * THREADS && 4 * (MAXG + 32) <= 768, "smem map");
static_assert(GIVE < 16 && MAXG <= 160, "levelling");
static_assert(SMEM_BYTES <= 232448 && BAR_OFF % 8 == 0 && RING_OFF % 128 == 0 && SREC_OFF % 128 == 0 && (MAXG + 14) / 15 <= 12, "smem map");

constexpr uint32_t PAY_INVALID = 0x3FFFFFFu;
constexpr uint32_t PAY_MARK = 0x3FFFDFFu;
constexpr uint32_t NODE_SPLIT = 0x40000000u;
constexpr uint32_t ST_START = 1, ST_CLOSE = 2;
constexpr float QINVP = 9.0f / 510.0f;
constexpr uint32_t QTHRESH = 2134;
constexpr uint32_t QSURE = 1870;

struct Scratch {
    unsigned sync[32];
    uint4 table[TABLE_MAXN / 4];
    uint4 wimg[RING_OFF / 16];
    uint2 pos8[TABLE_MAXN];
    uint4 xbuf[MAXG * MAXG * 8 + 3 * THREADS];
    uint4 pool[MAXG * GIVE * 16];
    unsigned rows[160];
    unsigned ready[MAXG];
    int ovfcnt[MAXG];
    int2 ovf[MAXE + 8 * MAXG + 8];
};
__device__ __align__(128) Scratch g_scratch;

struct Params {
    const __nv_bfloat16* pos;
    Scratch* g;
    const int* src;
    const int* dst;
    int N, NPC, E, gpc;
    const __nv_bfloat16* w2;
    const __nv_bfloat16* wr;
    const __nv_bfloat16* w1;
    const __nv_bfloat16* freqs;
    const __nv_bfloat16* sv;
    __nv_bfloat16* out;
    uint64_t desc0;
    int G;
    uint32_t magic;
    int odd_edges;
};
constexpr uint32_t SB = 1024;

#define TSX(i, thr)
#define TS0(i) TSX(i, 0)
#define TRW(ctl)

__device__ __forceinline__ uint32_t smem_u32(const void* p) { return (uint32_t)__cvta_generic_to_shared(p); }
__device__ __forceinline__ void mbar_init(uint32_t bar, uint32_t cnt) {
    asm volatile("mbarrier.init.shared::cta.b64 [%0], %1;" ::"r"(bar), "r"(cnt) : "memory");
}
__device__ __forceinline__ void mbar_arrive(uint32_t bar) {
    asm volatile("mbarrier.arrive.shared::cta.b64 _, [%0];" ::"r"(bar) : "memory");
}
__device__ __forceinline__ void mbar_expect_tx(uint32_t bar, uint32_t bytes) {
    asm volatile("mbarrier.arrive.expect_tx.shared::cta.b64 _, [%0], %1;" ::"r"(bar), "r"(bytes) : "memory");
}
__device__ __forceinline__ void mbar_wait(uint32_t bar, uint32_t parity) {
    uint32_t ok;
    int it = 0;
    do {
        asm volatile(
            "{\n.reg .pred p;\n"
            "mbarrier.try_wait.parity.shared::cta.b64 p, [%1], %2, 2000;\n"
            "selp.u32 %0, 1, 0, p;\n}\n"
            : "=r"(ok) : "r"(bar), "r"(parity) : "memory");
        if (++it > (1 << 20)) __trap();
    } while (!ok);
}
__device__ __forceinline__ uint32_t mbar_test(uint32_t bar, uint32_t parity) {
    uint32_t ok;
    asm volatile("{\n.reg .pred p;\nmbarrier.test_wait.parity.shared::cta.b64 p, [%1], %2;\nselp.u32 %0, 1, 0, p;\n}\n"
                 : "=r"(ok) : "r"(bar), "r"(parity) : "memory");
    return ok;
}
__device__ __forceinline__ uint32_t pin(uint32_t x) {
    uint32_t r;
    asm volatile("shfl.sync.bfly.b32 %0, %1, 0, 31, -1;" : "=r"(r) : "r"(x));
    return r;
}
__device__ __forceinline__ void bulk_g2s(uint32_t dst, const void* src, uint32_t bytes, uint32_t bar) {
    asm volatile("cp.async.bulk.shared::cluster.global.mbarrier::complete_tx::bytes [%0], [%1], %2, [%3];"
                 ::"r"(dst), "l"(src), "r"(bytes), "r"(bar) : "memory");
}
__device__ __forceinline__ void ldsm4(uint32_t addr, uint32_t* r) {
    asm volatile("ldmatrix.sync.aligned.m8n8.x4.shared.b16 {%0,%1,%2,%3}, [%4];"
                 : "=r"(r[0]), "=r"(r[1]), "=r"(r[2]), "=r"(r[3]) : "r"(addr) : "memory");
}
__device__ __forceinline__ uint32_t pack2(float lo, float hi) {
    uint32_t r;
    asm("cvt.rn.bf16x2.f32 %0, %1, %2;" : "=r"(r) : "f"(hi), "f"(lo));
    return r;
}
__device__ __forceinline__ float bf_lo(uint32_t w) { return __uint_as_float(w << 16); }
__device__ __forceinline__ float bf_hi(uint32_t w) { return __uint_as_float(w & 0xFFFF0000u); }
__device__ __forceinline__ float rbf16(float x) { return __uint_as_float(pack2(0.f, x)); }
__device__ __forceinline__ uint32_t hmul2(uint32_t a, uint32_t b) {
    uint32_t r;
    asm("mul.rn.bf16x2 %0, %1, %2;" : "=r"(r) : "r"(a), "r"(b));
    return r;
}
__device__ __forceinline__ uint32_t hfma2(uint32_t a, uint32_t b, uint32_t c) {
    uint32_t r;
    asm("fma.rn.bf16x2 %0, %1, %2, %3;" : "=r"(r) : "r"(a), "r"(b), "r"(c));
    return r;
}
__device__ __forceinline__ uint32_t hfma2_lo(uint32_t a, uint32_t b, uint32_t c) {
    uint32_t r;
    asm("{\n.reg .b16 l, h;\n.reg .b32 t;\nmov.b32 {l, h}, %2;\nmov.b32 t, {l, l};\nfma.rn.bf16x2 %0, %1, t, %3;\n}\n" : "=r"(r) : "r"(a), "r"(b), "r"(c));
    return r;
}
__device__ __forceinline__ uint32_t hfma2_hi(uint32_t a, uint32_t b, uint32_t c) {
    uint32_t r;
    asm("{\n.reg .b16 l, h;\n.reg .b32 t;\nmov.b32 {l, h}, %2;\nmov.b32 t, {h, h};\nfma.rn.bf16x2 %0, %1, t, %3;\n}\n" : "=r"(r) : "r"(a), "r"(b), "r"(c));
    return r;
}
__device__ __forceinline__ uint32_t hadd2(uint32_t a, uint32_t b) {
    uint32_t r;
    asm("add.rn.bf16x2 %0, %1, %2;" : "=r"(r) : "r"(a), "r"(b));
    return r;
}
__device__ __forceinline__ uint32_t hsub2(uint32_t a, uint32_t b) {
    uint32_t r;
    asm("sub.rn.bf16x2 %0, %1, %2;" : "=r"(r) : "r"(a), "r"(b));
    return r;
}
__device__ __forceinline__ float tanh_fast(float x) {
    float r;
    asm("tanh.approx.f32 %0, %1;" : "=f"(r) : "f"(x));
    return r;
}
__device__ __forceinline__ void wg_fence() { asm volatile("wgmma.fence.sync.aligned;" ::: "memory"); }
__device__ __forceinline__ void wg_commit() { asm volatile("wgmma.commit_group.sync.aligned;" ::: "memory"); }
template <int N>
__device__ __forceinline__ void wg_wait() { asm volatile("wgmma.wait_group.sync.aligned %0;" ::"n"(N) : "memory"); }

#define WG_REGS "{%0,%1,%2,%3,%4,%5,%6,%7,%8,%9,%10,%11,%12,%13,%14,%15,%16,%17,%18,%19,%20,%21,%22,%23,%24,%25,%26,%27,%28,%29,%30,%31}"
#define WG_OPS(c) c(d[0]), c(d[1]), c(d[2]), c(d[3]), c(d[4]), c(d[5]), c(d[6]), c(d[7]), c(d[8]), c(d[9]), c(d[10]), \
    c(d[11]), c(d[12]), c(d[13]), c(d[14]), c(d[15]), c(d[16]), c(d[17]), c(d[18]), c(d[19]), c(d[20]), c(d[21]),     \
    c(d[22]), c(d[23]), c(d[24]), c(d[25]), c(d[26]), c(d[27]), c(d[28]), c(d[29]), c(d[30]), c(d[31])
__device__ __forceinline__ void wgmma_first(float* d, const uint32_t* a, uint64_t desc) {
    asm volatile("wgmma.mma_async.sync.aligned.m64n64k16.f32.bf16.bf16 " WG_REGS ", {%32,%33,%34,%35}, %36, 0, 1, 1, 1;"
                 : WG_OPS("+f") : "r"(a[0]), "r"(a[1]), "r"(a[2]), "r"(a[3]), "l"(desc));
}
__device__ __forceinline__ void wgmma_acc(float* d, const uint32_t* a, uint64_t desc) {
    asm volatile("wgmma.mma_async.sync.aligned.m64n64k16.f32.bf16.bf16 " WG_REGS ", {%32,%33,%34,%35}, %36, 1, 1, 1, 1;"
                 : WG_OPS("+f") : "r"(a[0]), "r"(a[1]), "r"(a[2]), "r"(a[3]), "l"(desc));
}
__device__ __forceinline__ void wgmma_k64(float* d, const uint32_t* a, uint64_t desc) {
    wgmma_first(d, a, desc);
    wgmma_acc(d, a + 4, desc + 128);
    wgmma_acc(d, a + 8, desc + 256);
    wgmma_acc(d, a + 12, desc + 384);
}
__device__ __forceinline__ void fence_regs(float* d) { asm volatile("" : WG_OPS("+f")::"memory"); }
__device__ __forceinline__ uint32_t qaxis(float x) {
    const float u = fmaf(x, QINVP, 0.25f);
    const float f = u - ((u + 12582912.f) - 12582912.f);
    return __float_as_uint(fmaf(fabsf(f), 510.f, 12582912.f));
}
__device__ __forceinline__ uint32_t qcode(float x, float y, float z, uint32_t tx) {
    return __byte_perm(__byte_perm(qaxis(x), qaxis(y), 0x3340), qaxis(z), 0x3410) ^ tx;
}
__device__ __forceinline__ bool near_test(uint32_t ca, uint32_t cb, uint32_t tag24, uint32_t& q) {
    const uint32_t D = __vabsdiffu4(ca, cb);
    q = __dp4a(D, D, 0x7FFFFFFFu - QSURE);
    return q <= 0x7FFFFFFFu - QSURE + QTHRESH || ((ca ^ tag24) | (cb ^ tag24)) >= 0x1000000u;
}
__device__ __forceinline__ bool inside(uint32_t rxy, uint32_t rz) {
    const uint32_t qxy = hmul2(rxy, rxy), qz = hmul2(rz, rz);
    return bf_lo(qxy) + bf_hi(qxy) + bf_lo(qz) < 23.9375f;
}

__device__ __forceinline__ uint32_t lds32(uint32_t addr) {
    uint32_t r;
    asm volatile("ld.shared.u32 %0, [%1];" : "=r"(r) : "r"(addr));
    return r;
}
__device__ __forceinline__ void sts32_if(uint32_t addr, uint32_t v, bool c) {
    asm volatile("{\n.reg .pred p;\nsetp.ne.u32 p, %2, 0;\n@p st.shared.u32 [%0], %1;\n}\n" ::"r"(addr), "r"(v), "r"((uint32_t)c) : "memory");
}
__device__ __forceinline__ void stg128_if(void* ptr, uint4 v, bool c) {
    asm volatile("{\n.reg .pred p;\nsetp.ne.u32 p, %5, 0;\n@p st.relaxed.gpu.global.v4.u32 [%0], {%1,%2,%3,%4};\n}\n"
                 ::"l"(ptr), "r"(v.x), "r"(v.y), "r"(v.z), "r"(v.w), "r"((uint32_t)c) : "memory");
}
__device__ __forceinline__ void lds128(uint32_t addr, uint32_t* r) {
    asm volatile("ld.shared.v4.u32 {%0,%1,%2,%3}, [%4];" : "=r"(r[0]), "=r"(r[1]), "=r"(r[2]), "=r"(r[3]) : "r"(addr) : "memory");
}
template <int NP, int HI, int PAD = 1>
__device__ __forceinline__ void gather(uint32_t dst, const void* base, uint32_t c, uint32_t e) {
#define GATHER_HEAD "{\n.reg .pred p;\n.reg .b32 n;\n.reg .b64 a;\nprmt.b32 n, %2, 0, %3;\nsetp.ne.u32 p, n, 0xFFFF;\nmad.lo.u32 n, n, 512, %4;\nmad.wide.u32 a, n, 1, %1;\n"
#define GATHER_1(P) P "cp.async.cg.shared.global [%0], [a], 16;\n}\n"
#define GATHER_3(P) P "cp.async.cg.shared.global [%0], [a + 128], 16;\n" P "cp.async.cg.shared.global [%0 + 1024], [a + 256], 16;\n" \
                    P "cp.async.cg.shared.global [%0 + 2048], [a + 384], 16;\n}\n"
#define GATHER_ARGS(z) ::"r"(dst), "l"(base), "r"(e), "n"((HI ? 0x32 : 0x10) + z), "r"(c) : "memory"
    if constexpr (NP == 1 && PAD) asm volatile(GATHER_HEAD GATHER_1("@p ") GATHER_ARGS(0x4400));
    if constexpr (NP == 1 && !PAD) asm volatile(GATHER_HEAD GATHER_1("") GATHER_ARGS(0x4400));
    if constexpr (NP == 3 && PAD) asm volatile(GATHER_HEAD GATHER_3("@p ") GATHER_ARGS(0x5500));
    if constexpr (NP == 3 && !PAD) asm volatile(GATHER_HEAD GATHER_3("") GATHER_ARGS(0x4400));
    if constexpr (NP == 4)
        asm volatile(GATHER_HEAD "setp.ge.u32 p, %2, 0x40000000;\ncp.async.cg.shared.global [%0], [a], 16, p;\ncp.async.cg.shared.global [%0 + 1024], [a + 128], 16, p;\n"
                     "cp.async.cg.shared.global [%0 + 2048], [a + 256], 16, p;\ncp.async.cg.shared.global [%0 + 3072], [a + 384], 16, p;\n}\n" GATHER_ARGS(0x4400));
}
__device__ __forceinline__ void cp_commit() { asm volatile("cp.async.commit_group;" ::: "memory"); }
__device__ __forceinline__ void cp_wait1() { asm volatile("cp.async.wait_group 1;" ::: "memory"); }
__device__ __forceinline__ uint32_t hmul2_lo(uint32_t a, uint32_t b) {
    uint32_t r;
    asm("{\n.reg .b16 l, h;\n.reg .b32 t;\nmov.b32 {l, h}, %2;\nmov.b32 t, {l, l};\nmul.rn.bf16x2 %0, %1, t;\n}\n" : "=r"(r) : "r"(a), "r"(b));
    return r;
}
__device__ __forceinline__ void lds2_if(uint32_t a0, uint32_t a1, uint32_t* r, uint32_t c) {
    asm volatile("{\n.reg .pred p;\nsetp.ne.u32 p, %10, 0;\n@p ld.shared.v4.u32 {%0,%1,%2,%3}, [%8];\n@p ld.shared.v4.u32 {%4,%5,%6,%7}, [%9];\n}\n"
                 : "+r"(r[0]), "+r"(r[1]), "+r"(r[2]), "+r"(r[3]), "+r"(r[4]), "+r"(r[5]), "+r"(r[6]), "+r"(r[7])
                 : "r"(a0), "r"(a1), "r"(c) : "memory");
}
__device__ __forceinline__ int fresh_lane() {
    int l;
    asm volatile("mov.u32 %0, %%laneid;" : "=r"(l));
    return l;
}

__device__ __forceinline__ void cold_edges(unsigned char* smem, const Params& p, int lo, int hi, uint32_t tag) {
#pragma unroll 1
    for (int e = lo + threadIdx.x; e < hi; e += THREADS) {
        const int s = p.src[e], d = p.dst[e];
        uint32_t q;
        if (near_test(reinterpret_cast<const uint32_t*>(smem)[s], reinterpret_cast<const uint32_t*>(smem)[d], tag << 24, q)) {
            const uint32_t own = __umulhi((uint32_t)d, p.magic);
            const uint32_t slot4 = atomicAdd(reinterpret_cast<uint32_t*>(smem + SCNT_OFF) + own, 4u);
            uint32_t* line = reinterpret_cast<uint32_t*>(smem + STAGE_OFF) + own * 32;
            if (slot4 < 124) {
                line[(slot4 >> 2) ^ ((own & 7) << 2)] = ((uint32_t)s << 15) + ((uint32_t)(d - own * p.NPC) << 6) + tag + (q & 0x80000000u);
            } else {
                uint32_t o = atomicAdd(reinterpret_cast<uint32_t*>(smem + MISC_OFF) + 16, 1u);
                p.g->ovf[(size_t)blockIdx.x * (4 * p.gpc + 4) + o] = make_int2(s, d);
                line[31 ^ ((own & 7) << 2)] = (PAY_MARK << 6) | tag;
            }
        }
    }
}
__device__ __forceinline__ void cold_filter(unsigned char* smem, const Params& p, int e0, int e1, uint32_t tag, int redo) {
    if (redo) {
        if (threadIdx.x < MAXG) reinterpret_cast<uint32_t*>(smem + SCNT_OFF)[threadIdx.x] = 0;
        __syncthreads();
    }
    cold_edges(smem, p, redo ? 4 * e0 : 4 * (e0 + 3 * THREADS), 4 * e1, tag);
    if (blockIdx.x == 0) cold_edges(smem, p, p.E & ~3, p.E, tag);
    __syncthreads();
    if (threadIdx.x == 0) p.g->ovfcnt[blockIdx.x] = reinterpret_cast<uint32_t*>(smem + MISC_OFF)[16];
    __threadfence();
    __syncthreads();
}
__device__ __forceinline__ uint3 geometry(uint32_t rxy, uint32_t rz) {
    const uint32_t qxy = hmul2(rxy, rxy), qz = hmul2(rz, rz);
    float d, id;
    asm("sqrt.approx.ftz.f32 %0, %1;" : "=f"(d) : "f"(rbf16(rbf16(bf_lo(qxy) + bf_hi(qxy) + bf_lo(qz)) + 1e-8f)));
    d = rbf16(d);
    asm("rcp.approx.ftz.f32 %0, %1;" : "=f"(id) : "f"(d));
    const float cs = rbf16(__cosf(rbf16(rbf16(3.14159265358979f * d) * 0.2f)));
    const uint32_t zs = pack2(bf_lo(rz) * id, 0.5f * rbf16(cs + 1.0f) * id);
    return d < 5.0f ? make_uint3(pack2(bf_lo(rxy) * id, bf_hi(rxy) * id), zs, __byte_perm(__float_as_uint(d), zs, 0x7632)) : make_uint3(0, 0, 0);
}
__device__ __forceinline__ void cold_messages(unsigned char* smem, const Params& p, int nn) {
    const int nbase = blockIdx.x * p.NPC, lane = threadIdx.x & 31;
    const uint32_t* box = reinterpret_cast<const uint32_t*>(p.g->xbuf) + blockIdx.x * p.G * 32;
    uint32_t* w = reinterpret_cast<uint32_t*>(smem + RING_OFF);
#pragma unroll 1
    for (int i = threadIdx.x; i < 9728; i += THREADS)
        w[i] = i < 2048 ? reinterpret_cast<const uint32_t*>(p.w1)[i] : i < 8192 ? reinterpret_cast<const uint32_t*>(p.w2)[i - 2048] : reinterpret_cast<const uint32_t*>(p.wr)[i - 8192];
#pragma unroll 1
    for (int i = threadIdx.x; i < nn * 32; i += THREADS) reinterpret_cast<uint4*>(p.out)[nbase * 32 + i] = reinterpret_cast<const uint4*>(p.sv)[nbase * 32 + i];
    __threadfence();
    __syncthreads();
    const float freq = __bfloat162float(p.freqs[lane & 15]);
#pragma unroll 1
    for (int m = -1; m < p.G; m++) {
        const int cnt = m < 0 ? p.G * 32 : (__ldcg(box + m * 32 + 31) >> 6) == PAY_MARK ? __ldcg(&p.g->ovfcnt[m]) : 0;
#pragma unroll 1
        for (int i = threadIdx.x; i - lane < cnt; i += THREADS) {
            int2 e = make_int2(0, -1);
            if (i < cnt) {
                if (m < 0) {
                    const uint32_t x = __ldcg(box + i);
                    e = make_int2((x >> 15) & 0xFFFFu, nbase + ((x >> 6) & 511u));
                } else {
                    e = __ldcg(p.g->ovf + (size_t)m * (4 * p.gpc + 4) + i);
                }
            }
            bool in = (uint32_t)(e.y - nbase) < (uint32_t)nn;
            uint3 geo = make_uint3(0, 0, 0);
            if (in) {
                const uint2 ps = __ldcg(p.g->pos8 + e.x), pd = __ldcg(p.g->pos8 + e.y);
                const uint32_t rxy = hsub2(ps.x, pd.x), rz = hsub2(ps.y, pd.y);
                in = inside(rxy, rz);
                geo = geometry(rxy, rz);
            }
#pragma unroll 1
            for (uint32_t todo = __ballot_sync(0xffffffffu, in); todo; todo &= todo - 1) {
                const int l = __ffs(todo) - 1;
                const uint32_t* row = reinterpret_cast<const uint32_t*>(p.sv) + (size_t)__shfl_sync(0xffffffffu, e.x, l) * 128 + lane;
                uint32_t* orow = reinterpret_cast<uint32_t*>(p.out) + (size_t)__shfl_sync(0xffffffffu, e.y, l) * 128 + lane;
                const uint32_t gx = __shfl_sync(0xffffffffu, geo.x, l), gy = __shfl_sync(0xffffffffu, geo.y, l);
                const float rb = rbf16(__sinf(rbf16(bf_lo(__shfl_sync(0xffffffffu, geo.z, l)) * freq)) * bf_hi(gy));
                uint32_t x = row[0];
                float a[12] = {0, 0, 0, 0, 0, 0, 0, 0, 0, 0, 0, 0};
#pragma unroll 2
                for (int k = 0; k < 64; k++) {
                    const uint32_t u = __shfl_sync(0xffffffffu, x, k >> 1), ww = w[k * 32 + lane];
                    const float f = k & 1 ? bf_hi(u) : bf_lo(u);
                    a[0] = fmaf(f, bf_lo(ww), a[0]); a[1] = fmaf(f, bf_hi(ww), a[1]);
                }
                x = pack2(0.5f * fmaf(a[0], tanh_fast(0.5f * a[0]), a[0]), 0.5f * fmaf(a[1], tanh_fast(0.5f * a[1]), a[1]));
                a[0] = a[1] = 0.f;
#pragma unroll 2
                for (int k = 0; k < 64; k++) {
                    const uint32_t u = __shfl_sync(0xffffffffu, x, k >> 1);
                    const float f = k & 1 ? bf_hi(u) : bf_lo(u), r = __shfl_sync(0xffffffffu, rb, k & 15);
#pragma unroll
                    for (int c = 0; c < 3; c++) {
                        const uint32_t ww = w[2048 + k * 96 + c * 32 + lane], wr = k < 16 ? w[8192 + k * 96 + c * 32 + lane] : 0u;
                        a[2 * c] = fmaf(f, bf_lo(ww), a[2 * c]); a[2 * c + 1] = fmaf(f, bf_hi(ww), a[2 * c + 1]);
                        a[6 + 2 * c] = fmaf(r, bf_lo(wr), a[6 + 2 * c]); a[7 + 2 * c] = fmaf(r, bf_hi(wr), a[7 + 2 * c]);
                    }
                }
                const uint32_t mv = pack2(a[2] * a[8], a[3] * a[9]), mr = pack2(a[4] * a[10], a[5] * a[11]);
                const uint32_t o[4] = {pack2(a[0] * a[6], a[1] * a[7]), hfma2_lo(mr, gx, hmul2(mv, row[32])), hfma2_hi(mr, gx, hmul2(mv, row[64])),
                                       hfma2_lo(mr, gy, hmul2(mv, row[96]))};
#pragma unroll
                for (int c = 0; c < 4; c++) asm volatile("red.global.add.noftz.bf16x2 [%0], %1;" ::"l"(orow + 32 * c), "r"(o[c]) : "memory");
            }
        }
    }
}

#define SPLIT(k) asm volatile("{\n.reg .pred p;\nsetp.eq.u32 p, %0, %1;\n@p trap;\n}" ::"r"(c0), "n"(0x70000 + k) : "memory")
#define PIN8(a) asm volatile("" : "+r"((a)[0]), "+r"((a)[1]), "+r"((a)[2]), "+r"((a)[3]), "+r"((a)[4]), "+r"((a)[5]), "+r"((a)[6]), "+r"((a)[7]))
template <int V> struct IntC { static constexpr int value = V; };

template <int CN, int CE, int CG>
__global__ void __launch_bounds__(THREADS, 1) painn_kernel(const __grid_constant__ Params p) {
    extern __shared__ __align__(1024) unsigned char smem_dyn[];
    unsigned char* const smem = static_cast<unsigned char*>(__cvta_shared_to_generic(SB));
    constexpr uint32_t sb = SB;
    const int tid = threadIdx.x, lane = tid & 31;
    const int warp = __shfl_sync(0xffffffffu, tid >> 5, 0);
    constexpr int CNPC = CG ? (CN + CG - 1) / CG : 1, CGPC = CG ? (CE / 4 + CG - 1) / CG : 1;
    const int b = blockIdx.x, G = CG ? CG : p.G, NPC = CG ? CNPC : p.NPC, N = CG ? CN : p.N, gpc = CG ? CGPC : p.gpc;
    const uint32_t magic = CG ? (uint32_t)(((1ull << 32) + CNPC - 1) / CNPC) : p.magic;
    const bool odd_edges = CG ? (CE & 3) != 0 || CGPC > 3 * THREADS : p.odd_edges;
    const int nbase = b * NPC, nn = min(NPC, N - nbase);
    const int eg0 = b * gpc, eg1 = min((CG ? CE : p.E) >> 2, eg0 + gpc);

    uint4* stage4 = reinterpret_cast<uint4*>(smem + STAGE_OFF);
    uint32_t* ncnt = reinterpret_cast<uint32_t*>(smem + NCNT_OFF);
    uint32_t* misc = reinterpret_cast<uint32_t*>(smem + MISC_OFF);
    const uint32_t bar_tab = sb + BAR_OFF;

    TS0(0);
    int4 es[3], ed[3];
    auto load_edges = [&](int i) {
        const int g = min(eg0 + tid + i * THREADS, eg1 - 1);
        asm volatile("ld.global.cs.v4.u32 {%0,%1,%2,%3}, [%8];\nld.global.cs.v4.u32 {%4,%5,%6,%7}, [%9];"
                     : "=r"(es[i].x), "=r"(es[i].y), "=r"(es[i].z), "=r"(es[i].w), "=r"(ed[i].x), "=r"(ed[i].y), "=r"(ed[i].z), "=r"(ed[i].w)
                     : "l"(reinterpret_cast<const int4*>(p.src) + g), "l"(reinterpret_cast<const int4*>(p.dst) + g) : "memory");
    };
    es[0] = ed[0] = make_int4(0, 0, 0, 0);
    const char* const own = reinterpret_cast<const char*>(p.sv) + (size_t)nbase * 512;
    auto touch = [&](int o) {
        if (o + lane * 256 < nn * 512)
            asm volatile("cp.async.ca.shared.global.L2::256B [%0], [%1], 4;" ::"r"(sb + DUMMY_OFF + 4 * lane), "l"(own + o + lane * 256) : "memory");
    };
    uint4* const xout = p.g->xbuf + ((tid >> 3) * G + b) * 8 + (tid & 7);
    unsigned epoch;
    const uint32_t tbytes = ((N + 3) >> 2) * 16, cut = (tbytes >> 8) * CUT * 16, bar_cut = sb + BAR_OFF + 120;
    {
        uint32_t pxy, pz;
        if constexpr (CG && CN % 2 == 0) {
            asm volatile("ld.global.nc.u32 %0, [%3];\nld.global.nc.u32 %1, [%3 + 4];\nld.global.ca.u32 %2, [%4];"
                         : "=r"(pxy), "=r"(pz), "=r"(epoch)
                         : "l"(reinterpret_cast<const uint32_t*>(p.pos) + ((nbase + min(tid, nn - 1)) * 3 >> 1)), "l"(p.g->sync) : "memory");
            const uint32_t sh = ((nbase + tid) & 1) << 4;
            pxy = __funnelshift_r(pxy, pz, sh);
            pz >>= sh;
        } else {
            const uint16_t* q = reinterpret_cast<const uint16_t*>(p.pos) + (nbase + min(tid, nn - 1)) * 3;
            pxy = q[0] | (uint32_t)q[1] << 16;
            pz = q[2];
            asm volatile("ld.global.ca.u32 %0, [%1];" : "=r"(epoch) : "l"(p.g->sync) : "memory");
        }
        const uint32_t code = qcode(bf_lo(pxy), bf_hi(pxy), bf_lo(pz), ((epoch & 31u) ^ 0x6Bu) << 24);
        asm volatile("{\n.reg .pred p;\nsetp.lt.s32 p, %2, %3;\n@p st.global.u32 [%0], %1;\n}\n"
                     ::"l"(reinterpret_cast<uint32_t*>(p.g->table) + nbase + tid), "r"(code), "r"(tid), "r"(nn) : "memory");
        __syncthreads();
        asm volatile("{\n.reg .pred p;\nsetp.eq.u32 p, %1, %2;\n@p red.relaxed.gpu.global.add.u32 [%0], 1;\n}\n" ::"l"(p.g->sync + 1), "r"(tid), "n"(THREADS - 1) : "memory");
        if (tid < nn) p.g->pos8[nbase + tid] = make_uint2(pxy, (pz & 0xFFFFu) | ~epoch << 16);
        if (tid < THREADS - 32) load_edges(0);
        reinterpret_cast<uint2*>(smem + OPOS_OFF)[tid] = make_uint2(pxy, pz);
    }
    const uint32_t tag = (epoch & 31u) | 32u;
    if (tid == THREADS - 1) {
        TSX(1, 511);
        mbar_init(bar_tab, 1);
        mbar_init(bar_cut, 1);
        mbar_expect_tx(bar_cut, cut);
        mbar_expect_tx(bar_tab, tbytes - cut);
        const unsigned want = (epoch + 1) * G;
        unsigned c;
        int it = smem_u32(smem_dyn) == SB ? 0 : 1 << 22;
        __nanosleep(HDELAY);
        do {
            asm volatile("ld.relaxed.gpu.global.u32 %0, [%1];" : "=r"(c) : "l"(p.g->sync + 1) : "memory");
            if (++it > (1 << 22)) __trap();
        } while (c != want);
        bulk_g2s(sb, p.g->table, cut, bar_cut);
        bulk_g2s(sb + cut, reinterpret_cast<const char*>(p.g->table) + cut, tbytes - cut, bar_tab);
        TSX(2, 511);
    }
    if (warp == 14) {
#pragma unroll 1
        for (int c = b * 32 + lane; c < RING_OFF / 16; c += G * 32) {
            const int row = c >> 3, j = (c ^ row) & 7;
            uint4 v;
            if (c < 512) {
                const uint32_t half = 0x3F003F00u;
                v = __ldg(reinterpret_cast<const uint4*>(p.w1) + row * 8 + j);
                v = make_uint4(hmul2(v.x, half), hmul2(v.y, half), hmul2(v.z, half), hmul2(v.w, half));
            } else {
                const uint32_t* q = (c < 2048 ? reinterpret_cast<const uint32_t*>(p.w2) + (row & 63) * 96 + ((row >> 6) - 1) * 32
                                              : reinterpret_cast<const uint32_t*>(p.wr) + (row & 15) * 96 + ((row >> 4) - 16) * 32) + (j & 4) * 4 + (j & 3);
                v = make_uint4(__ldg(q), __ldg(q + 4), __ldg(q + 8), __ldg(q + 12));
            }
            p.g->wimg[c] = v;
        }
    }
    if (tid == 416) {
#pragma unroll
        for (int i = 0; i < FLIGHT + 2; i++) mbar_init(sb + BAR_OFF + 8 + 8 * i, i ? 1 : 15);
    }
    ncnt[tid] = tid < 480 ? 0 : 1024;
    if (tid < MAXG + 32) reinterpret_cast<uint32_t*>(smem + SCNT_OFF)[tid] = tid < MAXG ? 0 : 128;
    if (tid < 128) misc[tid] = 0;
    {
        const uint32_t inv = (PAY_INVALID << 6) | tag;
        stage4[tid] = stage4[tid + THREADS] = make_uint4(inv, inv, inv, inv);
        if (tid < MAXG * 8 - 2 * THREADS) stage4[tid + 2 * THREADS] = make_uint4(inv, inv, inv, inv);
    }
    __syncthreads();
    if ((tid >> 4) == 29) asm volatile("cp.async.ca.shared.global [%0], [%1], 4;" ::"r"(sb + FREQ_OFF + 8 * (tid & 14) + 4 * (tid & 1)),
                              "l"(reinterpret_cast<const uint32_t*>(p.freqs) + ((tid & 7) >> 1) + (tid & 1) * 4) : "memory");
    if (warp == 15) load_edges(0);
    if (warp < 8) mbar_wait(bar_cut, 0);
    load_edges(1);
    load_edges(2);
    if (tid == 416) asm volatile("fence.acq_rel.gpu;" ::: "memory");
    if (warp >= 8) mbar_wait(bar_cut, 0);
    {
        const uint32_t x = (PAY_INVALID << 6) | (tag ^ 16);
#pragma unroll
        for (int i = 0; i < 3; i++) stg128_if(xout + i * G * THREADS, make_uint4(x, x, x, x), tid + i * THREADS < G * 8);
    }
    bool full = false;
    {
        uint32_t at[24], msg[12], cnt[12], line[12];
#pragma unroll
        for (int j = 0; j < 12; j++) {
            const uint32_t s = j % 4 == 0 ? es[j / 4].x : j % 4 == 1 ? es[j / 4].y : j % 4 == 2 ? es[j / 4].z : es[j / 4].w;
            const uint32_t d = j % 4 == 0 ? ed[j / 4].x : j % 4 == 1 ? ed[j / 4].y : j % 4 == 2 ? ed[j / 4].z : ed[j / 4].w;
            const uint32_t own = __umulhi(d, magic);
            at[2 * j] = 4 * s; at[2 * j + 1] = 4 * d;
            msg[j] = own * (uint32_t)(-64 * NPC) + ((s << 15) + ((d << 6) + tag));
            cnt[j] = eg0 + tid + (j / 4) * THREADS < eg1 ? 4 * own : 4 * (MAXG + lane);
            line[j] = own * 128 + ((own & 7) << 4);
            asm volatile("" : "+r"(at[2 * j]), "+r"(at[2 * j + 1]), "+r"(msg[j]), "+r"(cnt[j]), "+r"(line[j]));
        }
        mbar_wait(bar_tab, 0);
        TS0(3);
        if (warp == 15) {
#pragma unroll
            for (int i = 0; i < TOUCH; i++) touch(i * 8192);
        }
#pragma unroll
        for (int i = 0; i < 12; i += 6) {
            uint32_t sl[6], cd[12];
#pragma unroll
            for (int j = 0; j < 12; j++) cd[j] = lds32(sb + at[2 * i + j]);
#pragma unroll
            for (int j = 0; j < 6; j++) {
                uint32_t q;
                const bool c = near_test(cd[2 * j], cd[2 * j + 1], tag << 24, q);
                msg[i + j] |= q & 0x80000000u;
                asm volatile("atom.shared.add.u32 %0, [%1 + %2], 4;" : "=r"(sl[j]) : "r"(c ? cnt[i + j] : 4 * (MAXG + lane)), "n"(SB + SCNT_OFF) : "memory");
            }
#pragma unroll
            for (int j = 0; j < 6; j++) {
                sts32_if(sb + STAGE_OFF + (line[i + j] ^ sl[j]), msg[i + j], sl[j] < 124);
                full |= sl[j] == 124;
            }
        }
    }
    {
        const int redo = __syncthreads_or(full);
        if (__builtin_expect(redo || odd_edges, 0)) cold_filter(smem, p, eg0, eg1, tag, redo);
    }
    TS0(4);
#pragma unroll
    for (int i = 0; i < 3; i++)
        stg128_if(xout + i * G * THREADS, stage4[(tid ^ ((tid >> 3) & 7)) + i * THREADS],
                  tid + i * THREADS < G * 8 && reinterpret_cast<const uint32_t*>(smem + SCNT_OFF)[(tid >> 3) + i * 64] >= (tid & 6) * 16u);
    __syncthreads();
#pragma unroll
    for (int i = -2; i < 2; i++) {
        const int c = tid + i * THREADS;
        const uint32_t x = c < (SN_OFF - STAGE_OFF) / 16 ? 0u : 0xFFFFFFFFu;
        if (c >= (SREC_OFF - STAGE_OFF) / 16) stage4[c] = make_uint4(x, x, x, x);
    }
    uint32_t key[4] = {0, 0, 0, 0};
    uint2 pr[4];
    const uint32_t gp = sb + RING_OFF + 2048 + (warp < 4 * NWG ? warp * 12288 : (warp & 3) * 12288 + 2048) + lane * 16;
    uint32_t pk = 0;
    if (warp == 15) {
        if (lane == 0) {
            int o = TOUCH * 8192;
#pragma unroll 1
            while (o < nn * 512 && !mbar_test(sb + BAR_OFF + 8, 0)) {
                const uint32_t bar = sb + BAR_OFF + 16 + 8 * (pk % FLIGHT);
                if (!mbar_test(bar, ~(pk / FLIGHT) & 1)) continue;
                const int n = min(4096, nn * 512 - o);
                mbar_expect_tx(bar, n);
                bulk_g2s(sb + DUMMY_OFF, own + o, n, bar);
                o += n;
                pk++;
            }
            misc[3] = pk;
        }
        __syncwarp();
    } else {
    __nanosleep(PDELAY);
    TS0(5);

    {
        const int LPW = (G + 14) / 15;
        uint32_t ew[3][4], bad[3];
        const uint4* cp = p.g->xbuf + (b * G + warp * LPW) * 8 + lane;
#pragma unroll
        for (int i = 0; i < 3; i++) {
            bad[i] = lane + 32 * i < min(LPW, G - warp * LPW) * 8;
            ew[i][0] = ew[i][1] = ew[i][2] = ew[i][3] = (PAY_INVALID << 6) | tag;
        }
        int it = 0;
#pragma unroll 1
        do {
#pragma unroll
            for (int i = 0; i < 3; i++)
                asm volatile("{\n.reg .pred p;\nsetp.ne.u32 p, %5, 0;\n@p ld.relaxed.gpu.global.v4.u32 {%0,%1,%2,%3}, [%4];\n}\n"
                             : "+r"(ew[i][0]), "+r"(ew[i][1]), "+r"(ew[i][2]), "+r"(ew[i][3]) : "l"(cp + 32 * i), "r"(bad[i]) : "memory");
#pragma unroll
            for (int i = 0; i < 3; i++) {
                const uint32_t x = (ew[i][0] ^ tag) | (ew[i][1] ^ tag) | (ew[i][2] ^ tag) | (ew[i][3] ^ tag);
                const uint32_t full = __ballot_sync(0xffffffffu, ew[i][3] < (PAY_INVALID << 6)) << 1 | 0x01010101u;
                bad[i] = (__ballot_sync(0xffffffffu, x & ((full >> (lane & 30)) & 1 ? 63u : 47u)) >> (lane & 24)) & 255u;
            }
            if (++it > (1 << 22)) __trap();
        } while (__any_sync(0xffffffffu, bad[0] | bad[1] | bad[2]));
        TSX(21, 0); TSX(22, 448);
        uint4* pack = reinterpret_cast<uint4*>(smem + PACK_OFF);
        int nch = 0;
        uint32_t at[3];
#pragma unroll
        for (int i = 0; i < 3; i++) {
            const uint32_t m = __ballot_sync(0xffffffffu, ew[i][0] < (PAY_MARK << 6));
            at[i] = nch + __popc(m & ((1u << lane) - 1));
            nch += __popc(m);
        }
        if (__builtin_expect(nch > 32, 0)) {
#pragma unroll 1
            for (int i = 0; i < 3; i++) {
                if (ew[0][0] < (PAY_MARK << 6) && at[0] >= 32) at[0] = (15 - warp) * 32 - 1 - min(atomicAdd(&misc[1], 1u), 31u);
                const uint32_t x = at[0], y = ew[0][0];
                at[0] = at[1]; at[1] = at[2]; at[2] = x;
                ew[0][0] = ew[1][0]; ew[1][0] = ew[2][0]; ew[2][0] = y;
            }
        }
#pragma unroll
        for (int i = 0; i < 3; i++) {
            asm volatile("{\n.reg .pred p;\nsetp.lt.u32 p, %1, %5;\n@p st.shared.v4.u32 [%0], {%1,%2,%3,%4};\n}\n"
                         ::"r"(sb + PACK_OFF + (warp * 32 + at[i]) * 16), "r"(ew[i][0]), "r"(ew[i][1]), "r"(ew[i][2]), "r"(ew[i][3]), "n"(PAY_MARK << 6) : "memory");
            sts32_if(sb + MISC_OFF + 4 * 17, 1, (ew[i][3] >> 6) == PAY_MARK);
        }
        bool have = lane < nch;
        if (warp == 14) {
            asm volatile("bar.sync 7, 480;" ::: "memory");
            const uint32_t extra = misc[1];
            if (nch + extra > 32) misc[18] = 1;
            have = have || lane + extra >= 32;
        } else {
            asm volatile("bar.arrive 7, 480;" ::: "memory");
        }
        __syncwarp();
        uint32_t w[4], rk[4];
        bool in[4];
        {
            const uint4 x = pack[tid];
            w[0] = have ? x.x : ~0u; w[1] = have ? x.y : ~0u; w[2] = have ? x.z : ~0u; w[3] = have ? x.w : ~0u;
        }
        auto fetch = [&](int j, bool c) {
            asm volatile("{\n.reg .pred p;\nsetp.ne.u32 p, %2, 0;\n@p cp.async.cg.shared.global [%0], [%1], 16;\n}\n"
                         ::"r"(gp + j * 512), "l"(reinterpret_cast<const uint4*>(p.g->pos8) + ((w[j] >> 16) & 0x7FFFu)), "r"((uint32_t)c) : "memory");
        };
#pragma unroll
        for (int j = 0; j < 4; j++) fetch(j, (int)w[j] < (int)(PAY_MARK << 6));
#pragma unroll
        for (int j = 0; j < 4; j++) pr[j] = reinterpret_cast<const uint2*>(smem + OPOS_OFF)[(w[j] >> 6) & 511u];
        uint32_t ca[4];
#pragma unroll
        for (int j = 0; j < 4; j++) {
            key[j] = ((w[j] >> 15) & 0xFFFFu) | ((w[j] << 10) & 0x1FF0000u);
            ca[j] = sb + NCNT_OFF + ((w[j] >> 4) & 0x7FCu);
            asm volatile("" : "+r"(key[j]), "+r"(ca[j]));
        }
        asm volatile("{\n.reg .pred p;\nsetp.eq.u32 p, %0, -1;\n@p trap;\n}" ::"r"(nch) : "memory");
        asm volatile("cp.async.wait_all;" ::: "memory");
        TSX(23, 0); TSX(24, 448);
        asm volatile("{\n.reg .pred p;\nsetp.eq.u32 p, %1, 0;\n@p mbarrier.arrive.shared::cta.b64 _, [%0];\n}\n" ::"r"(sb + BAR_OFF + 8), "r"(lane) : "memory");
#pragma unroll
        for (int j = 0; j < 4; j++) {
            uint2 ps;
            asm volatile("ld.shared.v2.u32 {%0,%1}, [%2];" : "=r"(ps.x), "=r"(ps.y) : "r"(gp + j * 512 + ((w[j] >> 12) & 8)) : "memory");
            in[j] = ((int)w[j] >= 0) | (((int)w[j] < (int)(PAY_MARK << 6)) & (inside(hsub2(ps.x, pr[j].x), hsub2(ps.y, pr[j].y)) | ((ps.y ^ ~epoch << 16) > 0xFFFFu)));
        }
#pragma unroll
        for (int j = 0; j < 4; j++)
            asm volatile("atom.shared.add.u32 %0, [%1], 1;" : "=r"(rk[j]) : "r"(in[j] ? ca[j] : sb + NCNT_OFF + 4 * (480 + lane)) : "memory");
#pragma unroll
        for (int j = 0; j < 4; j++) {
            rk[j] = rk[j] < SPL ? 2 * rk[j] : min(2 * rk[j] - (2 * SPL - 1), 126u);
            asm volatile("red.shared.add.u32 [%0 + %1], 1;" ::"r"(rk[j] & 2 ? 124u : rk[j] & 60u), "n"(SB + MISC_OFF + 128) : "memory");
            key[j] += rk[j] << 25;
        }
#pragma unroll
        for (int j = 0; j < 4; j++) fetch(j, (int)w[j] >= 0);
        cp_commit();
    }
    }
    __syncthreads();
    TS0(6);
    uint32_t deg[5];
    deg[4] = lds32(sb + NCNT_OFF + 4 * tid);
#pragma unroll
    for (int j = 0; j < 4; j++) deg[j] = lds32(sb + NCNT_OFF + ((key[j] >> 14) & 0x7FCu));
    if (tid == THREADS - 33) {
        if (b == 0) p.g->sync[0] = epoch + 1;
        asm volatile("fence.proxy.async.global;" ::: "memory");
        mbar_expect_tx(bar_tab, RING_OFF);
        bulk_g2s(sb, p.g->wimg, RING_OFF, bar_tab);
    }
    __syncwarp();
    uint32_t dst = sb + RING_OFF + warp * 12288 + (lane >> 3) * 256 + (((lane & 7) ^ (lane >> 3)) << 4), l7 = (lane & 7) * 16, g32 = (lane >> 2) * 32;
    uint32_t e0, e1, n0, n1;
    auto sources = [&](uint32_t c) {
        asm volatile("{\n.reg .b32 a;\nlop3.b32 a, %4, %5, 0xFFC0, 0xA8;\nshr.u32 a, a, 2;\nld.shared.v4.u32 {%0,%1,%2,%3}, [a + %6];\n}\n"
                     : "=r"(e0), "=r"(n0), "=r"(e1), "=r"(n1) : "r"(c), "r"(g32), "n"(SB + SN_OFF));
    };
    auto load_s = [&](auto pad) {
        gather<1, 0, pad.value>(dst, p.sv, l7, e0); gather<1, 1, pad.value>(dst + 1024, p.sv, l7, e0);
        gather<1, 0, pad.value>((dst ^ 64) + 128, p.sv, l7, e1); gather<1, 1, pad.value>((dst ^ 64) + 1152, p.sv, l7, e1);
    };
    auto load_o = [&]() {
        gather<4, 0>(dst + 8192, p.sv, l7, n0); gather<4, 0>((dst ^ 64) + 8320, p.sv, l7, n1);
    };
    auto load_v = [&](auto pad) {
        gather<3, 0, pad.value>(dst + 2048, p.sv, l7, e0); gather<3, 1, pad.value>(dst + 5120, p.sv, l7, e0);
        gather<3, 0, pad.value>((dst ^ 64) + 2176, p.sv, l7, e1); gather<3, 1, pad.value>((dst ^ 64) + 5248, p.sv, l7, e1);
        cp_commit();
    };
    const int ng = (misc[32] + 7) >> 3;
    const int give = max(min(ng - max((int)(misc[33] + 7) >> 3, 4 * NWG), GIVE), 0);
    if (warp == 15) {
        const uint32_t cnt = lane < 16 ? (misc[32 + lane] + 7) >> 3 : 0u;
        uint32_t z = cnt;
#pragma unroll
        for (int o = 1; o < 16; o <<= 1) {
            const uint32_t y = __shfl_up_sync(0xffffffffu, z, o);
            if (lane >= o) z += y;
        }
        misc[96 + lane] = lane < 16 ? 64 * (z - cnt) : 64 * (MAXROW + 1);
        asm volatile("bar.arrive 5, 512;" ::: "memory");
        const bool cold = cnt || z > MAXROW || misc[31 + SPL / 2] > 32 || misc[17] || misc[18];
        if (lane == 15) { misc[18] = cold; misc[4] = 8 * ng; }
        __syncwarp();
        asm volatile("bar.arrive 4, 512;" ::: "memory");
        if (lane == 15) {
            uint32_t order;
            asm volatile("atom.relaxed.gpu.global.add.u32 %0, [%1], 1;" : "=r"(order) : "l"(p.g->sync + 2) : "memory");
            asm volatile("st.relaxed.gpu.global.u32 [%0], %1;" ::"l"(p.g->rows + b),
                         "r"(~epoch << 20 | (cold || ng < 4 * NWG ? 255 : (order - epoch * G) << 12 | give << 8 | z)) : "memory");
        }
        pk = (z - cnt) << 8 | __shfl_down_sync(0xffffffffu, cnt, 1) << 24;
    } else {
        if (warp * 32 < nn) {
            const uint32_t c = deg[4], st = tid < nn ? (min(c, (uint32_t)SPL) + 1) >> 1 : 17u;
            const uint32_t same = __match_any_sync(0xffffffffu, st), first = __ffs(same) - 1;
            uint32_t r, node = nbase + tid;
            asm volatile("atom.shared.add.u32 %0, [%1], %2;" : "=r"(r)
                         : "r"(lane == first ? sb + MISC_OFF + 4 * (64 + st) : sb + NCNT_OFF + 4 * (480 + lane)), "r"(__popc(same)) : "memory");
            r = __shfl_sync(0xffffffffu, r, first) + __popc(same & ((1u << lane) - 1)) + misc[32 + st];
            if (__builtin_expect(c > SPL, 0)) {
                const uint32_t s2 = min((c - SPL + 1) >> 1, 16u), r2 = misc[32 + s2] + atomicAdd(&misc[64 + s2], 1u), k = atomicAdd(&misc[2], 1u);
                reinterpret_cast<uint32_t*>(smem + SCNT_OFF)[k & 31] = node;
                node |= NODE_SPLIT;
                ncnt[1024 + tid] = 8 * r2;
                reinterpret_cast<uint32_t*>(smem + SN_OFF)[(r2 & 511) * 2 + 1] = node;
            }
            if (tid < nn) {
                ncnt[512 + tid] = 8 * r;
                reinterpret_cast<uint32_t*>(smem + SN_OFF)[(r & 511) * 2 + 1] = node;
            }
        }
#pragma unroll
        for (int j = 0; j < 4; j++) {
            const uint32_t c = deg[j];
            asm volatile("{\n.reg .pred p;\n.reg .b64 a;\nsetp.ge.u32 p, %0, %3;\nsetp.lt.and.u32 p, %1, 0x8000000, p;\nmad.wide.u32 a, %4, 512, %2;\n@p prefetch.global.L2 [a];\n"
                         "}\n" ::"r"(c), "r"(key[j]), "l"(p.sv), "n"(BIG), "r"(key[j] & 0xFFFFu) : "memory");
        }
        asm volatile("bar.sync 5, 512;" ::: "memory");
        uint32_t slot[4];
#pragma unroll
        for (int j = 0; j < 4; j++) slot[j] = min(misc[96 + (key[j] >> 27)] + (ncnt[512 + ((key[j] >> 16) & 1023)] & 0xFFF8u), 64u * (MAXROW + 1)) + ((key[j] >> 25) & 2);
#pragma unroll
        for (int j = 0; j < 4; j++) {
            *reinterpret_cast<uint16_t*>(smem + SN_OFF + slot[j]) = (uint16_t)key[j];
            slot[j] += slot[j] & 2;
        }
        asm volatile("bar.sync 6, 480;" ::: "memory");
        TS0(7);
        if (warp < 4 * NWG) {
            sources((warp < ng ? warp : MAXROW) << 8);
            e0 = __vminu2(e0, (N - 1) * 0x10001u);
            e1 = __vminu2(e1, (N - 1) * 0x10001u);
            load_s(IntC<0>{});
            cp_commit();
            load_o();
            cp_commit();
            asm volatile("cp.async.wait_group 2;" ::: "memory");
        } else {
            asm volatile("cp.async.wait_all;" ::: "memory");
        }
        uint2 ps[4];
#pragma unroll
        for (int j = 0; j < 4; j++)
            asm volatile("ld.shared.v2.u32 {%0,%1}, [%2];" : "=r"(ps[j].x), "=r"(ps[j].y) : "r"(gp + j * 512 + (key[j] & 1) * 8) : "memory");
        if (__builtin_expect(((((int)key[0] < 0 ? 0u : ps[0].y ^ ~epoch << 16) | ((int)key[1] < 0 ? 0u : ps[1].y ^ ~epoch << 16) |
                               ((int)key[2] < 0 ? 0u : ps[2].y ^ ~epoch << 16) | ((int)key[3] < 0 ? 0u : ps[3].y ^ ~epoch << 16)) >> 16) != 0, 0)) {
#pragma unroll
            for (int j = 0; j < 4; j++) ps[j] = __ldcg(p.g->pos8 + min(key[j] & 0xFFFFu, (uint32_t)N - 1));
        }
        TSX(9, 0);
#pragma unroll 1
        for (int i = 0; i < 2; i++) {
#pragma unroll
            for (int u = 0; u < 2; u++) {
                const uint3 geo = geometry(hsub2(ps[u].x, pr[u].x), hsub2(ps[u].y, pr[u].y));
                *reinterpret_cast<uint2*>(smem + SREC_OFF + 2 * slot[u]) = make_uint2(geo.x, geo.y);
                *reinterpret_cast<uint32_t*>(smem + SD_OFF + slot[u]) = geo.z;
                ps[u] = ps[u + 2];
                pr[u] = pr[u + 2];
                slot[u] = slot[u + 2];
            }
        }
    }
    if (warp != 15) asm volatile("bar.sync 4, 512;" ::: "memory");
    TS0(8);
    auto drain = [&](int i) { if (i < FLIGHT) mbar_wait(sb + BAR_OFF + 16 + 8 * i, ~((misc[3] + FLIGHT - 1 - i) / FLIGHT) & 1); };
    if (__builtin_expect(misc[18], 0)) {
        drain(warp);
        asm volatile("cp.async.wait_all;" ::: "memory");
        __syncthreads();
        cold_messages(smem, p, nn);
        mbar_wait(bar_tab, 1);
        return;
    }

    if (warp < 4 * NWG) {
        asm volatile("setmaxnreg.inc.sync.aligned.u32 %0;" ::"n"(REG_C));
        const int lane = fresh_lane();
        const int g = lane >> 2, q = lane & 3;
        const uint64_t dW1 = p.desc0, dW2 = dW1 + (W2_OFF >> 4), dWR = dW1 + (WR_OFF >> 4);
        const uint32_t ring = sb + RING_OFF + warp * 12288;
        const uint32_t vrow = pin(ring + g * 128 + ((q ^ ((g & 1) << 2) ^ (g >> 1)) << 4));
        const uint32_t mrow = pin(ring + (lane & 15) * 128 + (((lane >> 4) ^ ((lane & 1) << 2) ^ ((lane & 7) >> 1)) << 4));
        dst = pin(ring + (lane >> 3) * 256 + (((lane & 7) ^ (lane >> 3)) << 4)); l7 = pin((lane & 7) * 16); g32 = pin(g * 32);
        uint32_t ctl = sb + CTL_OFF + warp * 4;
        auto control = [&](uint32_t c, uint32_t at) {
            int it = 0;
#pragma unroll 1
            while (__builtin_expect(c == 0xFFFFFFFFu, 0)) {
                asm volatile("ld.volatile.shared.u32 %0, [%1];" : "=r"(c) : "r"(at) : "memory");
                c = __reduce_or_sync(0xffffffffu, c);
                if (++it > (1 << 24)) __trap();
            }
            return c;
        };
        uint32_t c0 = control(0xFFFFFFFFu, ctl), c1 = control(0xFFFFFFFFu, ctl + 64);
        if (warp >= 8) asm volatile("bar.arrive 1, 256;" ::: "memory");
        uint32_t acc[32];
        float P[32], W[32];
#pragma unroll
        for (int i = 0; i < 32; i++) { acc[i] = 0; P[i] = W[i] = 0.f; }
        mbar_wait(bar_tab, 1);
        sources(c0);
        e0 = __vminu2(e0, (N - 1) * 0x10001u);
        e1 = __vminu2(e1, (N - 1) * 0x10001u);
        if (warp >= 8) asm volatile("cp.async.wait_all;" ::: "memory");
        else if (warp >= 4) cp_wait1();
        load_v(IntC<0>{});
        auto finish = [&](uint32_t c, uint32_t node) {
            if (c & ST_CLOSE) {
                uint64_t op[2];
                asm("{\n.reg .b32 a;\nmad.lo.u32 a, %2, 512, %3;\nmad.wide.u32 %0, a, 1, %4;\nxor.b32 a, a, 64;\nmad.wide.u32 %1, a, 1, %4;\n}\n"
                    : "=l"(op[0]), "=l"(op[1]) : "r"(node), "r"(l7), "l"(p.out));
#pragma unroll
                for (int k = 0; k < 8; k++) {
                    uint32_t x[4];
#pragma unroll
                    for (int i = 0; i < 4; i++) x[i] = l7 & 64 ? acc[4 * (k ^ 1) + i] : acc[4 * k + i];
                    asm volatile("{\n.reg .pred p;\nsetp.lt.u32 p, %5, %6;\n@p st.global.cs.v4.u32 [%0], {%1,%2,%3,%4};\n}\n"
                                 ::"l"(op[k & 1] + 128 * (k >> 1)), "r"(x[0]), "r"(x[1]), "r"(x[2]), "r"(x[3]), "r"(node), "n"(NODE_SPLIT) : "memory");
                }
                if (__builtin_expect(__any_sync(0xffffffffu, (int)node >= (int)NODE_SPLIT), 0)) {
                    mbar_wait(sb + BAR_OFF + 16 + 8 * FLIGHT, 0);
                    if ((int)node >= (int)NODE_SPLIT) {
#pragma unroll
                        for (int k = 0; k < 8; k++)
                            asm volatile("red.global.add.noftz.v4.bf16x2 [%0], {%1,%2,%3,%4};" ::"l"((op[0] & ~64ull) + 64 * k), "r"(acc[4 * k]), "r"(acc[4 * k + 1]), "r"(acc[4 * k + 2]), "r"(acc[4 * k + 3]) : "memory");
                    }
                    __syncwarp();
                }
            }
        };
        uint32_t f01, f23;
        asm volatile("ld.shared.v2.u32 {%0,%1}, [%2 + %3];" : "=r"(f01), "=r"(f23) : "r"(l7), "n"(SB + FREQ_OFF));
        f01 = pin(f01); f23 = pin(f23);
#pragma unroll 1
        while ((int)c0 >= 0) {
            uint32_t a[16], h[16], rf[4], rr[4], m[16];
            TRW(ctl);
            uint32_t dd[2];
            asm volatile("ld.shared.v2.u32 {%0,%1}, [%2 + %3];" : "=r"(dd[0]), "=r"(dd[1]) : "r"(((c0 & 0xFF00) | g32) >> 2), "n"(SB + SD_OFF));
            sources(c1);
            asm volatile("cp.async.wait_group 2;" ::: "memory");
            __syncwarp();
#pragma unroll
            for (int i = 0; i < 4; i++) ldsm4(mrow ^ (i << 5), a + 4 * i);
            wg_fence();
            wgmma_k64(P, a, dW1);
            wg_commit();
#pragma unroll
            for (int hh = 0; hh < 2; hh++) {
                const float sc = bf_hi(dd[hh]);
                const uint32_t x01 = hmul2_lo(f01, dd[hh]), x23 = hmul2_lo(f23, dd[hh]);
                rf[hh] = pack2(__sinf(bf_lo(x01)) * sc, __sinf(bf_hi(x01)) * sc);
                rf[2 + hh] = pack2(__sinf(bf_lo(x23)) * sc, __sinf(bf_hi(x23)) * sc);
            }
            asm volatile("" : "+r"(rf[0]), "+r"(rf[1]), "+r"(rf[2]), "+r"(rf[3]));
            asm volatile("bar.sync %0, 256;" ::"r"(1 + (warp >> 2)) : "memory");
            SPLIT(2);
            wg_wait<0>();
            fence_regs(P);
#pragma unroll
            for (int i = 0; i < 16; i++)
                h[i] = pack2(fmaf(P[2 * i], tanh_fast(P[2 * i]), P[2 * i]), fmaf(P[2 * i + 1], tanh_fast(P[2 * i + 1]), P[2 * i + 1]));
            wg_fence();
            wgmma_k64(P, h, dW2 + 1024);
            wgmma_first(W, rf, dWR + 256);
            wg_commit();
            asm volatile("bar.arrive %0, 256;" ::"r"((c0 >> 4) & 3) : "memory");
            cp_wait1();
            __syncwarp();
#pragma unroll
            for (int k = 0; k < 4; k++) lds2_if(vrow + 8192 + 1024 * k, (vrow ^ 64) + 8192 + 1024 * k, acc + 8 * k, c0 & ST_START);
            lds128(sb + SREC_OFF + (((c0 & 0xFF00) | g32) >> 1), rr);
            uint32_t c2 = lds32(ctl + 128);
            __syncwarp();
            load_s(IntC<1>{});
            cp_commit();
            if (c1 & ST_START) load_o();
            cp_commit();
            wg_wait<0>();
            fence_regs(P); fence_regs(W);
#pragma unroll
            for (int j = 0; j < 8; j++) {
                m[j] = pack2(P[4 * j] * W[4 * j], P[4 * j + 1] * W[4 * j + 1]);
                m[8 + j] = pack2(P[4 * j + 2] * W[4 * j + 2], P[4 * j + 3] * W[4 * j + 3]);
            }
            wg_fence();
            wgmma_k64(P, h, dW2);
            wgmma_first(W, rf, dWR);
            wg_commit();
            SPLIT(4);
            PIN8(m); PIN8(m + 8);
            c2 = __reduce_or_sync(0xffffffffu, c2);
#pragma unroll
            for (int k = 1; k < 4; k++)
#pragma unroll
                for (int j = 0; j < 8; j++) {
                    const uint32_t x = k == 1 ? hfma2_lo(m[j], rr[0], acc[8 * k + j]) : k == 2 ? hfma2_hi(m[j], rr[0], acc[8 * k + j]) : hfma2_lo(m[j], rr[1], acc[8 * k + j]);
                    acc[8 * k + j] = k == 1 ? hfma2_lo(m[8 + j], rr[2], x) : k == 2 ? hfma2_hi(m[8 + j], rr[2], x) : hfma2_lo(m[8 + j], rr[3], x);
                }
            PIN8(acc + 8); PIN8(acc + 16); PIN8(acc + 24);
            SPLIT(5);
            wg_wait<0>();
            fence_regs(P); fence_regs(W);
#pragma unroll
            for (int j = 0; j < 8; j++)
                acc[j] = hadd2(acc[j], pack2(fmaf(P[4 * j], W[4 * j], P[4 * j + 2] * W[4 * j + 2]), fmaf(P[4 * j + 1], W[4 * j + 1], P[4 * j + 3] * W[4 * j + 3])));
            wg_fence();
            wgmma_k64(P, h, dW2 + 512);
            wgmma_first(W, rf, dWR + 128);
            wg_commit();
            SPLIT(6);
            asm volatile("cp.async.wait_group 2;" ::: "memory");
            __syncwarp();
            uint32_t v[4][16];
#pragma unroll
            for (int i = 0; i < NPRE; i++) lds128((vrow ^ (64 * (i & 1))) + 2048 + 1024 * (i >> 2) + 3072 * ((i >> 1) & 1), v[1 + (i >> 2)] + 4 * (i & 3));
            wg_wait<0>();
            fence_regs(P); fence_regs(W);
#pragma unroll
            for (int j = 0; j < 8; j++) {
                m[j] = pack2(P[4 * j] * W[4 * j], P[4 * j + 1] * W[4 * j + 1]);
                m[8 + j] = pack2(P[4 * j + 2] * W[4 * j + 2], P[4 * j + 3] * W[4 * j + 3]);
            }
#pragma unroll
            for (int i = NPRE; i < 12; i++) lds128((vrow ^ (64 * (i & 1))) + 2048 + 1024 * (i >> 2) + 3072 * ((i >> 1) & 1), v[1 + (i >> 2)] + 4 * (i & 3));
            sources(c1);
            const uint32_t node = lds32(sb + SN_OFF + 4 + (((c0 >> 16) | g32) >> 2));
            __syncwarp();
            load_v(IntC<1>{});
#pragma unroll
            for (int k = 1; k < 4; k++)
#pragma unroll
                for (int j = 0; j < 8; j++) acc[8 * k + j] = hfma2(m[8 + j], v[k][8 + j], hfma2(m[j], v[k][j], acc[8 * k + j]));
            finish(c0, node);
            ctl += 64;
            c0 = c1;
            c1 = control(c2, ctl + 64);
        }
        asm volatile("cp.async.wait_all;" ::: "memory");
        TRW(ctl);
        TSX(11, 0); TSX(12, 128); TSX(13, 256);
    } else {
        asm volatile("setmaxnreg.dec.sync.aligned.u32 %0;" ::"n"(REG_H));
        const int lane = fresh_lane();
        const uint32_t chunk = sb + (lane & 8 ? (lane & 4 ? SN_OFF : SD_OFF) + (lane & 3) * 16 : SREC_OFF + (lane & 7) * 16), pitch = lane & 8 ? 64 : 128;
        if (warp == 12) {
#pragma unroll 1
            for (int r = lane >> 3; r < (int)misc[2]; r += 4) {
                const uint32_t n = reinterpret_cast<const uint32_t*>(smem + SCNT_OFF)[r] * 32 + (lane & 7);
                uint4 v[4];
#pragma unroll
                for (int i = 0; i < 4; i++) v[i] = reinterpret_cast<const uint4*>(p.sv)[n + 8 * i];
#pragma unroll
                for (int i = 0; i < 4; i++) reinterpret_cast<uint4*>(p.out)[n + 8 * i] = v[i];
            }
            __syncwarp();
#pragma unroll 1
            for (int i = lane >> 4; i < give; i += 2) {
                uint32_t x[4];
                lds128(chunk + (ng - 1 - i) * pitch, x);
                p.g->pool[(b * GIVE + i) * 16 + (lane & 15)] = make_uint4(x[0], x[1], x[2], x[3]);
            }
            __threadfence();
            __syncwarp();
            if (lane == 0) {
                asm volatile("st.relaxed.gpu.global.u32 [%0], %1;" ::"l"(p.g->ready + b), "r"(~epoch) : "memory");
                mbar_arrive(sb + BAR_OFF + 16 + 8 * FLIGHT);
            }
        }
        if (warp == 15) {
            int k = lane < 4 * NWG ? lane : 255, next = 4 * NWG, j = 0, mine = ng - give, end = -1, take = 0;
            uint32_t busy, at = sb + CTL_OFF + 4 * lane, from = 0;
#pragma unroll 1
            do {
                if (next > mine && end < 0) {
                    uint32_t x[5], z;
                    int it = 0;
#pragma unroll 1
                    do {
                        __nanosleep(700);
                        z = 0;
#pragma unroll
                        for (int i = 0; i < 5; i++) asm volatile("ld.relaxed.gpu.global.u32 %0, [%1];" : "=r"(x[i]) : "l"(p.g->rows + 5 * lane + i) : "memory");
#pragma unroll
                        for (int i = 0; i < 5; i++) {
                            x[i] = 5 * lane + i < G ? x[i] ^ (~epoch << 20) : 255;
                            z |= x[i];
                        }
                        if (++it > (1 << 22)) __trap();
                    } while (__any_sync(0xffffffffu, z >> 20));
                    z = 0;
#pragma unroll
                    for (int i = 0; i < 5; i++) {
                        if (x[i] != 255) z += (x[i] & 255) + 0x10000;
                        reinterpret_cast<uint32_t*>(smem + SCNT_OFF)[32 + 5 * lane + i] = x[i];
                    }
                    z = __reduce_add_sync(0xffffffffu, z);
                    const int level = min((int)((z & 0xFFFFu) / max(z >> 16, 1u) + 2) & ~3, MAXROW - 4);
                    uint32_t ed, sur, me = 0, mz = 0;
#pragma unroll 1
                    for (uint32_t first = 0;; first = (z * 3 / 4 + 2) << 12) {
                        ed = sur = 0;
#pragma unroll 1
                        for (int i = 0; i < 5; i++) {
                            const uint32_t y = reinterpret_cast<const uint32_t*>(smem + SCNT_OFF)[32 + 5 * lane + i];
                            const int r = (y & 255) - (y < first && (int)(y & 255) > level ? level + 4 : level);
                            const uint32_t e = r > 0 ? min(r, (int)(y >> 8) & 15) : min(-r, ROOM) << 16;
                            if (i == b % 5) { me = e; mz = ed; }
                            sur |= (e & 15) << (4 * i);
                            ed += e;
                        }
                        z = __reduce_add_sync(0xffffffffu, (ed & 0xFFFFu) - (ed >> 16));
                        if ((int)z <= 0 || first) break;
                    }
                    z = ed;
#pragma unroll
                    for (int o = 1; o < 32; o <<= 1) {
                        const uint32_t y = __shfl_up_sync(0xffffffffu, z, o);
                        if (lane >= o) z += y;
                    }
                    const uint32_t all = __shfl_sync(0xffffffffu, z, 31), moved = min(all & 0xFFFFu, all >> 16);
                    me = __shfl_sync(0xffffffffu, me, b / 5);
                    mz = __shfl_sync(0xffffffffu, mz + z - ed, b / 5);
                    end = mine = ng - (min((mz + me) & 0xFFFFu, moved) - min(mz & 0xFFFFu, moved));
#pragma unroll 1
                    for (uint32_t u = mz >> 16; u < min((mz + me) >> 16, moved); u++, take++) {
                        int f = __popc(__ballot_sync(0xffffffffu, (z & 0xFFFFu) <= u));
                        uint32_t q = u - (__shfl_sync(0xffffffffu, z - ed, f) & 0xFFFFu), s5 = __shfl_sync(0xffffffffu, sur, f);
#pragma unroll 1
                        for (f *= 5; q >= (s5 & 15); f++, s5 >>= 4) q -= s5 & 15;
                        if (lane == take) from = f << 8 | q;
                    }
                }
                if (next > mine && take) {
                    if (lane < take) {
                        uint32_t x;
                        int it = 0;
#pragma unroll 1
                        do {
                            asm volatile("ld.acquire.gpu.global.u32 %0, [%1];" : "=r"(x) : "l"(p.g->ready + (from >> 8)) : "memory");
                            if (++it > (1 << 22)) __trap();
                        } while (x != ~epoch);
                    }
                    __syncwarp();
#pragma unroll 1
                    for (end += take; take--;) {
                        const uint32_t f = __shfl_sync(0xffffffffu, from, take);
                        if (lane < 16)
                            asm volatile("cp.async.cg.shared.global [%0], [%1], 16;" ::"r"(chunk + (MAXROW - 1 - take) * pitch),
                                         "l"(p.g->pool + ((f >> 8) * GIVE + (f & 255)) * 16 + lane) : "memory");
                    }
                    take = 0;
                    asm volatile("cp.async.wait_all;" ::: "memory");
                    __threadfence_block();
                    __syncwarp();
                }
                const bool has = k < (end < 0 ? mine : end);
                const uint32_t i = k < mine ? k : MAXROW - 1 + mine - k, x = __shfl_sync(0xffffffffu, pk, j);
                const bool close = has && i >= (x >> 24);
                busy = __ballot_sync(0xffffffffu, has);
                const uint32_t m = __ballot_sync(0xffffffffu, close);
                uint32_t c = has ? ((x & 0xFF00) + i * 0x1000100) | (j ? 0u : ST_START) | (close ? ST_CLOSE : 0u) : MAXROW * 256;
                if (!(busy >> (lane & 12))) c |= 0x80000000u;
                c |= busy >> ((lane & 12) + 4) ? (lane & 12) * 4 + 32 : 16;
                sts32_if(at, c, lane < 16 || !busy);
                j = close ? 0 : j + 1;
                k = close ? next + __popc(m & ((1u << lane) - 1)) : k;
                next += __popc(m);
                at += 64;
            } while (busy);
        }
        if (warp == 15) mbar_wait(sb + BAR_OFF + 16 + 8 * FLIGHT, 0);
        else if (warp != 12) __nanosleep(ZDELAY);
        const int zlast = misc[32] + misc[64] - 1;
#pragma unroll 1
        for (;;) {
            int r = 0;
            if (lane == 0) r = atomicAdd(&misc[4], 4u);
            r = __shfl_sync(0xffffffffu, r, 0);
            if (r > zlast) break;
            uint4 v[4];
            uint32_t n[4];
#pragma unroll
            for (int i = 0; i < 4; i++) {
                n[i] = reinterpret_cast<const uint32_t*>(smem + SN_OFF)[min(r + i, zlast) * 2 + 1] * 32 + lane;
                v[i] = __ldcs(reinterpret_cast<const uint4*>(p.sv) + n[i]);
            }
#pragma unroll
            for (int i = 0; i < 4; i++) __stcs(reinterpret_cast<uint4*>(p.out) + n[i], v[i]);
        }
        static_assert(FLIGHT <= 4, "drain");
        drain(warp & 3);
        asm volatile("cp.async.wait_all;" ::: "memory");
        TSX(14, 384); TSX(15, 480); TSX(16, 416);
    }
}

}

extern "C" void kernel_launch(void* const* d_in, const int* in_sizes, int n_in, void* d_out, int out_size) {
    static int s_G = 0;
    static void* s_scratch = nullptr;
    const int N = in_sizes[0] / 256, E = in_sizes[2];
    if (s_G == 0) {
        cudaFuncSetAttribute(painn_kernel<0, 0, 0>, cudaFuncAttributeMaxDynamicSharedMemorySize, SMEM_BYTES);
        cudaFuncSetAttribute(painn_kernel<50000, 800000, 132>, cudaFuncAttributeMaxDynamicSharedMemorySize, SMEM_BYTES);
        int dev = 0, sms = 0, occ = 0;
        cudaGetDevice(&dev);
        cudaDeviceGetAttribute(&sms, cudaDevAttrMultiProcessorCount, dev);
        cudaOccupancyMaxActiveBlocksPerMultiprocessor(&occ, painn_kernel<0, 0, 0>, THREADS, SMEM_BYTES);
        cudaGetSymbolAddress(&s_scratch, g_scratch);
        s_G = occ >= 1 ? (sms < MAXG ? sms : MAXG) : 0;
    }
    if (s_G == 0 || N > TABLE_MAXN || N > s_G * MAXNPC || (s_G - 1) * ((N + s_G - 1) / s_G) >= N || E > MAXE || E < 4 * MAXG * MAXG) return;
    Params p;
    p.g = (Scratch*)s_scratch;
    p.sv = (const __nv_bfloat16*)d_in[0];
    p.pos = (const __nv_bfloat16*)d_in[1];
    p.src = (const int*)d_in[2];
    p.dst = (const int*)d_in[3];
    p.freqs = (const __nv_bfloat16*)d_in[4];
    p.w1 = (const __nv_bfloat16*)d_in[5];
    p.w2 = (const __nv_bfloat16*)d_in[6];
    p.wr = (const __nv_bfloat16*)d_in[7];
    p.out = (__nv_bfloat16*)d_out;
    p.desc0 = (uint64_t)(SB >> 4) | ((uint64_t)1 << 16) | ((uint64_t)64 << 32) | ((uint64_t)1 << 62);
    p.N = N; p.E = E; p.G = s_G;
    p.NPC = (N + s_G - 1) / s_G;
    p.magic = (uint32_t)(((1ull << 32) + p.NPC - 1) / p.NPC);
    p.gpc = ((E >> 2) + s_G - 1) / s_G;
    p.odd_edges = (E & 3) != 0 || p.gpc > 3 * THREADS;
    if (N == 50000 && E == 800000 && s_G == 132) painn_kernel<50000, 800000, 132><<<s_G, THREADS, SMEM_BYTES, cudaStreamPerThread>>>(p);
    else painn_kernel<0, 0, 0><<<s_G, THREADS, SMEM_BYTES, cudaStreamPerThread>>>(p);
}
```
